```python
import torch

def _softmax(x, axis=-1):
    return torch.softmax(x, dim=axis)

def _gelu(x):
    return torch.nn.functional.gelu(x, approximate='tanh')

def _silu(x):
    return torch.nn.functional.silu(x)

def _sigmoid(x):
    return torch.sigmoid(x)

def _layernorm(x, axis=-1, eps=1e-05):
    m = x.mean(dim=axis, keepdim=True)
    v = x.var(dim=axis, keepdim=True, unbiased=False)
    return (x - m) / torch.sqrt(v + eps)

def _scatter_add(tgt, idx, src, axis=0):
    return tgt.clone().index_add_(axis, idx, src)

def _segment_sum(src, seg, n):
    out = torch.zeros((n,) + src.shape[1:], dtype=src.dtype)
    return out.index_add_(0, seg, src)

def _pad(x, pw):
    flat = tuple((v for pair in reversed(pw) for v in pair))
    return torch.nn.functional.pad(x, flat)
kernel_name = 'adaLN_cond__sliding_block_cached__dense_activation_gelu__decode'

def setup_inputs():

    _w = lambda a: (lambda t: t.to(torch.bfloat16) if t.is_floating_point() else t)(torch.as_tensor(a))

    def _A_setup():
        B, Sq, D = (4, 1, 640)
        Hq, Hkv, Sk, Dh = (32, 32, 8192, 128)
        assert Hq % Hkv == 0, (Hq, Hkv)
        return {'x': _w((lambda *s: torch.randn(*s, dtype=torch.bfloat16) * 0.1)(B, Sq, D)), 'k_cache': _w((lambda *s: torch.randn(*s, dtype=torch.bfloat16) * 0.8)(B, Hkv, Sk, Dh)), 'v_cache': _w((lambda *s: torch.randn(*s, dtype=torch.bfloat16) * 3.2)(B, Hkv, Sk, Dh)), 'wq': _w((lambda *s: torch.randn(*s, dtype=torch.bfloat16) * 0.8)(D, Hq * Dh) * D ** (-0.5)), 'wo': _w((lambda *s: torch.randn(*s, dtype=torch.bfloat16) * 3.2)(Hq * Dh, D) * (Hq * Dh) ** (-0.5))}
    _A_in = _A_setup()

    def _B_setup():
        B, S, D, F = (4, 1, 640, 1728)
        return {'x': _w((lambda *s: torch.randn(*s, dtype=torch.bfloat16) * 0.1)(B, S, D)), 'w1': _w((lambda *s: torch.randn(*s, dtype=torch.bfloat16) * 3.2)(D, F) * D ** (-0.5)), 'b1': _w((lambda *s: torch.randn(*s, dtype=torch.bfloat16) * 3.2)(F) * 0.01), 'w2': _w((lambda *s: torch.randn(*s, dtype=torch.bfloat16) * 3.2)(F, D) * F ** (-0.5)), 'b2': _w((lambda *s: torch.randn(*s, dtype=torch.bfloat16) * 3.2)(D) * 0.01)}
    _B_in = _B_setup()
    return {'A_x': _A_in['x'], 'A_k_cache': _A_in['k_cache'], 'A_v_cache': _A_in['v_cache'], 'A_wq': _A_in['wq'], 'A_wo': _A_in['wo'], 'B_x': _B_in['x'], 'B_w1': _B_in['w1'], 'B_b1': _B_in['b1'], 'B_w2': _B_in['w2'], 'B_b2': _B_in['b2'], 'c': _w((lambda *s: torch.randn(*s, dtype=torch.bfloat16) * 0.1)(4, 640) * 8.0), 'w_mod': _w((lambda *s: torch.randn(*s, dtype=torch.bfloat16) * 0.1)(640, 6 * 640) * 640 ** (-0.5) * 8.0)}

def reference(A_x, A_k_cache, A_v_cache, A_wq, A_wo, B_x, B_w1, B_b1, B_w2, B_b2, c, w_mod):

    def _A_ref(x, k_cache, v_cache, wq, wo):
        B, Sq, D = x.shape
        Hq, Dh = (32, 128)
        Hkv, Sk = (k_cache.shape[1], k_cache.shape[2])
        W = min(4096, max(256, Sk // 4))
        rep = Hq // Hkv
        q = (lambda x, *d: x.permute(*d))((x @ wq).reshape(B, Sq, Hq, Dh), 0, 2, 1, 3)
        k = (lambda x, n, axis: torch.repeat_interleave(x, n, dim=axis))(k_cache[:, :, Sk - W:, :], rep, axis=1)
        v = (lambda x, n, axis: torch.repeat_interleave(x, n, dim=axis))(v_cache[:, :, Sk - W:, :], rep, axis=1)
        scores = torch.einsum('bhqd,bhkd->bhqk', q, k) * Dh ** (-0.5)
        p = _softmax(scores, axis=-1)
        o = torch.einsum('bhqk,bhkd->bhqd', p, v)
        return (lambda x, *d: x.permute(*d))(o, 0, 2, 1, 3).reshape(B, Sq, Hq * Dh) @ wo

    def _B_ref(x, w1, b1, w2, b2):
        h = torch.einsum('bsd,df->bsf', x, w1) + b1
        h = _gelu(h)
        return torch.einsum('bsf,fd->bsd', h, w2) + b2
    x = A_x
    mod = (_silu(c) @ w_mod).reshape(c.shape[0], 6, 1, -1)
    sa, ca, ga, sb, cb, gb = (mod[:, 0].clone(), mod[:, 1].clone(), mod[:, 2].clone(), mod[:, 3].clone(), mod[:, 4].clone(), mod[:, 5].clone())
    h = _layernorm(x, axis=-1) * (1 + ca) + sa
    x = x + ga * _A_ref(h, A_k_cache, A_v_cache, A_wq, A_wo)
    h = _layernorm(x, axis=-1) * (1 + cb) + sb
    x = x + gb * _B_ref(h, B_w1, B_b1, B_w2, B_b2)
    return x
```

```cpp
#include <cuda_runtime.h>
#include <cuda.h>
#include <cuda_bf16.h>
#include <stdint.h>

namespace {

constexpr int NB = 4, D = 640, NH = 32, DH = 128, SK = 8192, WIN = 2048, FF = 1728, NMOD = 6 * D;
constexpr int NCTA = 128;
constexpr int NOWN = 80;
constexpr int NF = 54;
constexpr int NTHREADS = 320;
constexpr int TILE_KEYS = 64;
constexpr int TILE_BYTES = TILE_KEYS * DH * 2;
constexpr int NITEM = 2 * WIN / TILE_KEYS;
constexpr int NS = 8;
constexpr int NMODC = 120;
constexpr int SPIN_LIMIT = 1 << 18;
#define INFLIGHT 3
#define PACE_A 8600
#define PACE_TAU 635
#define WQ_DELAY 800
#define WO_GATE 2
#define WF_GATE 4
#define WF_DELAY 0
#define W2_DELAY 0
#define WF_ALL 0
#define CLR_CHECK 28000
constexpr int SEG_J = 8;

constexpr int OFF_RING = 0;
constexpr int OFF_X = OFF_RING + NS * TILE_BYTES;
constexpr int X_WM = OFF_X;
constexpr int X_WQ = OFF_X + D * 64;
constexpr int X_WO = OFF_X;
constexpr int X_W1 = X_WO + 5 * DH * 64;
constexpr int X_END = X_W1 + D * 64;
constexpr int X_W2 = OFF_RING;
static_assert(X_WQ + D * 64 <= X_END, "prologue weights must fit");
constexpr int VEC_STRIDE = 1296;
constexpr int OFF_VA = X_END;
constexpr int OFF_VB = OFF_VA + 4 * VEC_STRIDE;
constexpr int OFF_RED = OFF_VB + 4 * VEC_STRIDE;
constexpr int OFF_ML = OFF_RED + 4096;
constexpr int O_STRIDE = 288;
constexpr int OFF_O = OFF_ML + 64;
constexpr int OFF_Q = OFF_O + 4 * O_STRIDE;
constexpr int OFF_OWN = OFF_Q + 256;
constexpr int OWN_X = OFF_OWN, OWN_B2 = OWN_X + 64, OWN_B1 = OWN_B2 + 64;
constexpr int OFF_STAT = OWN_B1 + 128;
constexpr int OFF_BAR = OFF_STAT + 32;
constexpr int NBAR = 2 * NS + 15;
constexpr int SMEM_BYTES = OFF_BAR + NBAR * 8;
constexpr int SC_OP = OFF_RING + 4 * TILE_BYTES;
constexpr int SC_AB = SC_OP + 4096;
constexpr int SC_Y = SC_AB + 8192;
constexpr int SC_ST = SC_Y + 4096;
constexpr int SC_E4 = SC_ST + 256;
constexpr int SC_E6 = SC_E4 + 1024;
constexpr int SC_P = SC_E6 + 1024;
constexpr int SC_H1 = SC_P + 256;
static_assert(SMEM_BYTES <= 232448, "smem");
static_assert(OFF_BAR % 8 == 0 && OFF_X % 1024 == 0 && X_WQ % 512 == 0 && X_W1 % 512 == 0 && OFF_VA % 16 == 0 && OFF_RED % 16 == 0 && OFF_ML % 16 == 0 && OFF_O % 16 == 0 && OFF_Q % 16 == 0, "align");
constexpr int NB_O = 2  , NB_E4 = 10, NB_E6 = 11, NB_AB = 12, NB_Y = 13, NB_H1 = 14;

__device__ uint32_t g_mod[NMODC * 64];
__device__ uint32_t g_q[NCTA * 64];
__device__ uint32_t g_o[NCTA * 64];
__device__ uint32_t g_p1[NOWN * NH * 32];
__device__ uint32_t g_clr[NCTA];
__device__ uint32_t g_x1[NB * 320];
__device__ uint32_t g_p2[NOWN * NF * 32];
#define PROF_DECL
#define HPROF(i) do { } while (0)
#define PROF(i) do { } while (0)
#define PROF_DUMP do { } while (0)

__device__ __forceinline__ uint32_t smem_u32(const void* p) { return (uint32_t)__cvta_generic_to_shared(p); }
__device__ __forceinline__ void mbar_init(uint32_t bar, uint32_t cnt) { asm volatile("mbarrier.init.shared::cta.b64 [%0], %1;" ::"r"(bar), "r"(cnt) : "memory"); }
__device__ __forceinline__ void mbar_expect_tx(uint32_t bar, uint32_t bytes) { asm volatile("mbarrier.arrive.expect_tx.shared::cta.b64 _, [%0], %1;" ::"r"(bar), "r"(bytes) : "memory"); }
__device__ __forceinline__ void mbar_arrive(uint32_t bar) { asm volatile("mbarrier.arrive.shared::cta.b64 _, [%0];" ::"r"(bar) : "memory"); }
__device__ __forceinline__ void mbar_wait(uint32_t bar, uint32_t parity) {
    uint32_t ok;
    int it = 0;
    while (true) {
        asm volatile("{\n.reg .pred p;\nmbarrier.try_wait.parity.shared::cta.b64 p, [%1], %2;\nselp.u32 %0, 1, 0, p;\n}" : "=r"(ok) : "r"(bar), "r"(parity) : "memory");
        if (ok) break;
        if (++it > SPIN_LIMIT) __trap();
    }
}
__device__ __forceinline__ void bulk_load(uint32_t dst, const void* src, uint32_t bytes, uint32_t bar, uint64_t pol) {
    asm volatile("cp.async.bulk.shared::cluster.global.mbarrier::complete_tx::bytes.L2::cache_hint [%0], [%1], %2, [%3], %4;"
                 ::"r"(dst), "l"(src), "r"(bytes), "r"(bar), "l"(pol) : "memory");
}
__device__ __forceinline__ void bar_cons() { asm volatile("bar.sync 1, 256;" ::: "memory"); }
template <int ID> __device__ __forceinline__ void nbar_sync() { asm volatile("bar.sync %0, 256;" ::"n"(ID) : "memory"); }
template <int ID> __device__ __forceinline__ void nbar_arrive() { asm volatile("bar.arrive %0, 256;" ::"n"(ID) : "memory"); }
__device__ __forceinline__ bool mbar_test(uint32_t bar, uint32_t parity) {
    uint32_t ok;
    asm volatile("{\n.reg .pred p;\nmbarrier.test_wait.parity.shared::cta.b64 p, [%1], %2;\nselp.u32 %0, 1, 0, p;\n}" : "=r"(ok) : "r"(bar), "r"(parity) : "memory");
    return ok;
}
__device__ __forceinline__ uint32_t pin(uint32_t v) { asm volatile("" : "+r"(v)); return v; }
template <class T> __device__ __forceinline__ T* pin(T* v) { asm volatile("" : "+l"(v)); return v; }
__device__ __forceinline__ void ldsm4(uint32_t (&a)[4], uint32_t addr) {
    asm volatile("ldmatrix.sync.aligned.m8n8.x4.shared.b16 {%0,%1,%2,%3}, [%4];" : "=r"(a[0]), "=r"(a[1]), "=r"(a[2]), "=r"(a[3]) : "r"(addr) : "memory");
}
__device__ __forceinline__ void ldsm4t(uint32_t (&a)[4], uint32_t addr) {
    asm volatile("ldmatrix.sync.aligned.m8n8.x4.trans.shared.b16 {%0,%1,%2,%3}, [%4];" : "=r"(a[0]), "=r"(a[1]), "=r"(a[2]), "=r"(a[3]) : "r"(addr) : "memory");
}
__device__ __forceinline__ void mma16816(float (&c)[4], const uint32_t (&a)[4], uint32_t b0, uint32_t b1) {
    asm volatile("mma.sync.aligned.m16n8k16.row.col.f32.bf16.bf16.f32 {%0,%1,%2,%3}, {%4,%5,%6,%7}, {%8,%9}, {%0,%1,%2,%3};"
                 : "+f"(c[0]), "+f"(c[1]), "+f"(c[2]), "+f"(c[3]) : "r"(a[0]), "r"(a[1]), "r"(a[2]), "r"(a[3]), "r"(b0), "r"(b1));
}
__device__ __forceinline__ uint32_t lds32(uint32_t addr) { uint32_t v; asm volatile("ld.shared.u32 %0, [%1];" : "=r"(v) : "r"(addr) : "memory"); return v; }
__device__ __forceinline__ float lds_f32(uint32_t addr) { float v; asm volatile("ld.shared.f32 %0, [%1];" : "=f"(v) : "r"(addr) : "memory"); return v; }
__device__ __forceinline__ float2 lds_f32x2(uint32_t addr) { float2 v; asm volatile("ld.shared.v2.f32 {%0,%1}, [%2];" : "=f"(v.x), "=f"(v.y) : "r"(addr) : "memory"); return v; }
__device__ __forceinline__ float4 lds_f32x4(uint32_t addr) { float4 v; asm volatile("ld.shared.v4.f32 {%0,%1,%2,%3}, [%4];" : "=f"(v.x), "=f"(v.y), "=f"(v.z), "=f"(v.w) : "r"(addr) : "memory"); return v; }
__device__ __forceinline__ uint2 lds64(uint32_t addr) { uint2 v; asm volatile("ld.shared.v2.u32 {%0,%1}, [%2];" : "=r"(v.x), "=r"(v.y) : "r"(addr) : "memory"); return v; }
__device__ __forceinline__ uint4 lds128(uint32_t addr) { uint4 v; asm volatile("ld.shared.v4.u32 {%0,%1,%2,%3}, [%4];" : "=r"(v.x), "=r"(v.y), "=r"(v.z), "=r"(v.w) : "r"(addr) : "memory"); return v; }
__device__ __forceinline__ void sts16(uint32_t addr, uint32_t v) { asm volatile("st.shared.b16 [%0], %1;" ::"r"(addr), "h"((unsigned short)v) : "memory"); }
__device__ __forceinline__ void sts32(uint32_t addr, uint32_t v) { asm volatile("st.shared.u32 [%0], %1;" ::"r"(addr), "r"(v) : "memory"); }
__device__ __forceinline__ void sts_f32(uint32_t addr, float v) { asm volatile("st.shared.f32 [%0], %1;" ::"r"(addr), "f"(v) : "memory"); }
__device__ __forceinline__ void sts_f32x2(uint32_t addr, float a, float b) { asm volatile("st.shared.v2.f32 [%0], {%1,%2};" ::"r"(addr), "f"(a), "f"(b) : "memory"); }
__device__ __forceinline__ void sts128(uint32_t addr, uint4 v) { asm volatile("st.shared.v4.u32 [%0], {%1,%2,%3,%4};" ::"r"(addr), "r"(v.x), "r"(v.y), "r"(v.z), "r"(v.w) : "memory"); }
__device__ __forceinline__ uint4 ldg_relaxed(const uint32_t* p) {
    uint4 v;
    asm volatile("ld.relaxed.gpu.global.v4.u32 {%0,%1,%2,%3}, [%4];" : "=r"(v.x), "=r"(v.y), "=r"(v.z), "=r"(v.w) : "l"(p) : "memory");
    return v;
}
__device__ __forceinline__ uint2 ldg_relaxed64(const uint32_t* p) { uint2 v; asm volatile("ld.relaxed.gpu.global.v2.u32 {%0,%1}, [%2];" : "=r"(v.x), "=r"(v.y) : "l"(p) : "memory"); return v; }
__device__ __forceinline__ uint32_t ldg_relaxed32(const uint32_t* p) { uint32_t v; asm volatile("ld.relaxed.gpu.global.u32 %0, [%1];" : "=r"(v) : "l"(p) : "memory"); return v; }
__device__ __forceinline__ void stg_relaxed(uint32_t* p, uint32_t v) { asm volatile("st.relaxed.gpu.global.u32 [%0], %1;" ::"l"(p), "r"(v) : "memory"); }
__device__ __forceinline__ void stg_relaxed2(uint32_t* p, uint32_t a, uint32_t b) { asm volatile("st.relaxed.gpu.global.v2.u32 [%0], {%1,%2};" ::"l"(p), "r"(a), "r"(b) : "memory"); }
__device__ __forceinline__ void stg_zero4(uint32_t* p) { asm volatile("st.relaxed.gpu.global.v4.u32 [%0], {%1,%1,%1,%1};" ::"l"(p), "r"(0u) : "memory"); }
__device__ __forceinline__ bool ready(const uint4& v) { return (v.x != 0u) & (v.y != 0u) & (v.z != 0u) & (v.w != 0u); }
__device__ __forceinline__ uint4 inv4(const uint4& v) { return make_uint4(~v.x, ~v.y, ~v.z, ~v.w); }
__device__ __forceinline__ uint32_t pack_bf(float lo, float hi) {
    uint32_t r;
    asm("cvt.rn.bf16x2.f32 %0, %1, %2;" : "=r"(r) : "f"(hi), "f"(lo));
    return r;
}
__device__ __forceinline__ float bfr(float x) { return __uint_as_float(pack_bf(0.f, x) & 0xffff0000u); }
__device__ __forceinline__ float bf_lo(uint32_t w) { return __uint_as_float(w << 16); }
__device__ __forceinline__ float bf_hi(uint32_t w) { return __uint_as_float(w & 0xffff0000u); }
__device__ __forceinline__ float bf2f(__nv_bfloat16 v) { return __bfloat162float(v); }
__device__ __forceinline__ float ex2(float x) { float y; asm("ex2.approx.ftz.f32 %0, %1;" : "=f"(y) : "f"(x)); return y; }
__device__ __forceinline__ float rcp_fast(float x) { float y; asm("rcp.approx.ftz.f32 %0, %1;" : "=f"(y) : "f"(x)); return y; }
__device__ __forceinline__ float rsqrt_fast(float x) { float y; asm("rsqrt.approx.ftz.f32 %0, %1;" : "=f"(y) : "f"(x)); return y; }
__device__ __forceinline__ float sqrt_fast(float x) { float y; asm("sqrt.approx.f32 %0, %1;" : "=f"(y) : "f"(x)); return y; }
__device__ __forceinline__ uint32_t bf2_add(uint32_t a, uint32_t b) { uint32_t r; asm("add.rn.bf16x2 %0, %1, %2;" : "=r"(r) : "r"(a), "r"(b)); return r; }
__device__ __forceinline__ uint32_t bf2_sub(uint32_t a, uint32_t b) { uint32_t r; asm("sub.rn.bf16x2 %0, %1, %2;" : "=r"(r) : "r"(a), "r"(b)); return r; }
__device__ __forceinline__ uint32_t bf2_mul(uint32_t a, uint32_t b) { uint32_t r; asm("mul.rn.bf16x2 %0, %1, %2;" : "=r"(r) : "r"(a), "r"(b)); return r; }
__device__ __forceinline__ uint32_t gtime32() { uint32_t c; asm volatile("mov.u32 %0, %%globaltimer_lo;" : "=r"(c)); return c; }
__device__ __forceinline__ uint32_t clock32() { uint32_t c; asm volatile("mov.u32 %0, %%clock;" : "=r"(c)); return c; }

__device__ __forceinline__ float warp_sum(float v) {
#pragma unroll
    for (int o = 16; o > 0; o >>= 1) v += __shfl_xor_sync(0xffffffffu, v, o);
    return v;
}

struct Params {
    const __nv_bfloat16 *x, *kc, *vc, *b1, *b2, *c;
    __nv_bfloat16* out;
};

__device__ __forceinline__ void tma2d(uint32_t dst, const CUtensorMap* tm, int x, int y, uint32_t bar) {
    asm volatile("cp.async.bulk.tensor.2d.shared::cluster.global.mbarrier::complete_tx::bytes [%0], [%1, {%2, %3}], [%4];"
                 ::"r"(dst), "l"(tm), "r"(x), "r"(y), "r"(bar) : "memory");
}

__device__ __forceinline__ void tma2d_hint(uint32_t dst, const CUtensorMap* tm, int x, int y, uint32_t bar, uint64_t pol) {
    asm volatile("cp.async.bulk.tensor.2d.shared::cluster.global.mbarrier::complete_tx::bytes.L2::cache_hint [%0], [%1, {%2, %3}], [%4], %5;"
                 ::"r"(dst), "l"(tm), "r"(x), "r"(y), "r"(bar), "l"(pol) : "memory");
}
__device__ __forceinline__ uint32_t flag(float v) { return __float_as_uint(v) | 1u; }

__device__ __forceinline__ void load_bfrag(uint32_t vec, int stride, int k0, int g, int t, uint32_t& b0, uint32_t& b1) {
    uint32_t a = vec + (g & 3) * stride + (k0 + 2 * t) * 2;
    b0 = lds32(a);
    b1 = lds32(a + 16);
}

__device__ __forceinline__ void ln_finish(float pivot, float sum, float sumsq, uint32_t& m2, float& rden) {
    float dm = sum * (1.f / D);
    float var = fmaxf(sumsq * (1.f / D) - dm * dm, 0.f);
    float mean = pivot + dm;
    m2 = pack_bf(mean, mean);
    rden = rcp_fast(bfr(sqrt_fast(bfr(bfr(var) + 1e-5f))));
}
__device__ __forceinline__ uint32_t ln_mod_pair(uint32_t xw, uint32_t cw, uint32_t sw, uint32_t m2, float rden) {
    uint32_t d = bf2_sub(xw, m2);
    uint32_t ln = pack_bf(bf_lo(d) * rden, bf_hi(d) * rden);
    return bf2_add(bf2_mul(ln, bf2_add(cw, 0x3f803f80u)), sw);
}
__device__ __forceinline__ uint4 ln_mod4(const uint4& x, const uint4& c, const uint4& s, uint32_t m2, float rden) {
    return make_uint4(ln_mod_pair(x.x, c.x, s.x, m2, rden), ln_mod_pair(x.y, c.y, s.y, m2, rden),
                      ln_mod_pair(x.z, c.z, s.z, m2, rden), ln_mod_pair(x.w, c.w, s.w, m2, rden));
}
__device__ __forceinline__ void acc_stats(const uint4& v, float pv, float& s, float& q) {
    const float a0 = bf_lo(v.x) - pv, a1 = bf_hi(v.x) - pv, a2 = bf_lo(v.y) - pv, a3 = bf_hi(v.y) - pv;
    const float a4 = bf_lo(v.z) - pv, a5 = bf_hi(v.z) - pv, a6 = bf_lo(v.w) - pv, a7 = bf_hi(v.w) - pv;
    s += ((a0 + a1) + (a2 + a3)) + ((a4 + a5) + (a6 + a7));
    q += (fmaf(a0, a0, a1 * a1) + fmaf(a2, a2, a3 * a3)) + (fmaf(a4, a4, a5 * a5) + fmaf(a6, a6, a7 * a7));
}
__device__ __forceinline__ uint32_t* mod_slot(int kind, int j, int b) { return g_mod + (kind * 20 + (j >> 2)) * 64 + b * 16 + (j & 3) * 4; }

template <int N>
__device__ __forceinline__ void poll_n(uint4 (&v)[N], const uint32_t* const* ptr, const bool* on) {
    bool pend[N];
#pragma unroll
    for (int i = 0; i < N; i++) pend[i] = on[i];
    int it = 0;
    while (true) {
#pragma unroll
        for (int i = 0; i < N; i++) if (pend[i]) v[i] = ldg_relaxed(ptr[i]);
        bool any = false;
#pragma unroll
        for (int i = 0; i < N; i++) { pend[i] = pend[i] && !ready(v[i]); any |= pend[i]; }
        if (!__any_sync(0xffffffffu, any)) break;
        if (++it > SPIN_LIMIT) __trap();
    }
#pragma unroll
    for (int i = 0; i < N; i++) v[i] = inv4(v[i]);
}
__device__ __forceinline__ uint4 poll1(const uint32_t* p, bool on) {
    uint4 v[1] = {make_uint4(0, 0, 0, 0)};
    const uint32_t* const ptr[1] = {p};
    const bool o[1] = {on};
    poll_n<1>(v, ptr, o);
    return v[0];
}

__global__ void __launch_bounds__(NTHREADS, 1)
fused_kernel(const Params p, const __grid_constant__ CUtensorMap tm_wmod, const __grid_constant__ CUtensorMap tm_wq,
             const __grid_constant__ CUtensorMap tm_wo, const __grid_constant__ CUtensorMap tm_w1, const __grid_constant__ CUtensorMap tm_w2,
             const __grid_constant__ CUtensorMap tm_v) {
    extern __shared__ __align__(1024) unsigned char smem[];
    const uint32_t sb = smem_u32(smem);
    const int cta = blockIdx.x;
    const int head = cta >> 2, bown = cta & 3;
    const uint32_t bar_full = sb + OFF_BAR, bar_empty = bar_full + NS * 8;
    const uint32_t bar_wm = bar_empty + NS * 8, bar_wq = bar_wm + 8, bar_xfree = bar_wq + 8, bar_wo = bar_xfree + 8  ;
    const uint32_t bar_w1 = bar_wo + 40, bar_w2 = bar_w1 + 8, bar_help = bar_w2 + 8, bar_v = bar_help + 8  ;
    const int tid = threadIdx.x, warp = tid >> 5, lane = tid & 31;
    const int f = (cta * 27) >> 6;
    const bool is_f = (((cta + 1) * 27) >> 6) != f;
    const bool is_owner = !is_f || f % 9 == 4;
    const int own = is_f ? 74 + f / 9 : cta - f;
    const bool crit = (((cta + 1) * 5) >> 4) != ((cta * 5) >> 4);
    const int mr = cta - ((cta * 5) >> 4);
    const bool late = !crit && mr % 11 != 10;
    const int mc = crit ? (cta * 5) >> 4 : 40 + mr - mr / 11;

    const uint32_t t_start = gtime32();
    PROF_DECL
    PROF(0);
    uint4 xa = make_uint4(0, 0, 0, 0), xb = xa, ca0 = xa, ca1 = xa, xs[3] = {xa, xa, xa};
    uint32_t own0 = 0;
    __nv_bfloat16 own2 = __float2bfloat16(0.f);
    if (warp < 8) {
        xa = *(const uint4*)(p.x + (tid & 3) * D + (tid >> 2) * 8);
        ca0 = ((const uint4*)p.c)[tid];
        if (tid < 64) { xb = *(const uint4*)(p.x + (tid & 3) * D + (64 + (tid >> 2)) * 8); ca1 = ((const uint4*)p.c)[256 + tid]; }
        if (warp < 4) {
#pragma unroll
            for (int i = 0; i < 3; i++) if (lane + 32 * i < 80) xs[i] = ((const uint4*)p.x)[warp * 80 + lane + 32 * i];
        } else if (warp == 4) {
            if (is_owner) own0 = *(const uint32_t*)((lane < 16 ? p.x + (lane >> 2) * D : p.b2) + 8 * own + 2 * (lane & 3));
            if (is_f) own2 = p.b1[32 * f + lane];
        }
    }
    const int rot = (head & 1) * (NITEM / 4);
    const char* const kb = (const char*)(p.kc + ((size_t)(bown * NH + head) * SK + (SK - WIN)) * DH);
    const char* const vb = (const char*)(p.vc + ((size_t)(bown * NH + head) * SK + (SK - WIN)) * DH);
    const uint32_t bar_first = crit ? bar_wm : bar_wq;
    uint64_t pol = 0;
    if (threadIdx.x == 256) {
        mbar_init(bar_first, 1);
        mbar_init(bar_full, 1);
        asm volatile("fence.mbarrier_init.release.cluster;" ::: "memory");
        asm volatile("createpolicy.fractional.L2::evict_first.b64 %0, 1.0;" : "=l"(pol));
        const uint32_t dst = sb + (crit ? X_WM : X_WQ);
        const CUtensorMap* tm = crit ? &tm_wmod : &tm_wq;
        mbar_expect_tx(bar_first, D * 64);
        if (crit) {
#pragma unroll
            for (int r = 0; r < D; r += 160) tma2d(dst + r * 64, tm, 32 * mc, r, bar_first);
        }
        mbar_expect_tx(bar_full, TILE_BYTES);
        bulk_load(sb + OFF_RING, kb + (size_t)rot * TILE_BYTES, TILE_BYTES, bar_full, pol);
        if (!crit) {
            const uint32_t c0 = clock32();
            while (clock32() - c0 < WQ_DELAY) { }
#pragma unroll
            for (int r = 0; r < D; r += 160) tma2d(dst + r * 64, tm, 32 * cta, r, bar_first);
        }
    } else if (threadIdx.x == 0) {
#pragma unroll
        for (int s = 0; s < NS; s++) { if (s) mbar_init(bar_full + s * 8, 1); mbar_init(bar_empty + s * 8, 4); }
        mbar_init(crit ? bar_wq : bar_wm, 1);
        mbar_init(bar_xfree, 1);
#pragma unroll
        for (int i = 0; i < 5; i++) mbar_init(bar_wo + i * 8, 1);
        mbar_init(bar_w1, 1); mbar_init(bar_w2, 1); mbar_init(bar_help, 1);
#pragma unroll
        for (int i = 0; i < 4; i++) mbar_init(bar_v + i * 8, 1);
        asm volatile("fence.mbarrier_init.release.cluster;" ::: "memory");
    }
    __syncthreads();

    if (warp == 8) {
        if (lane == 0) {
#pragma unroll 1
            for (int t = 1; t <= NITEM; t++) {
                if (t == 1) mbar_wait(bar_full, 0);
                if (t == 2) {
                    mbar_wait(bar_first, 0);
                    if (crit) {
                        mbar_expect_tx(bar_wq, D * 64);
#pragma unroll 1
                        for (int r = 0; r < D; r += 160) tma2d(sb + X_WQ + r * 64, &tm_wq, 32 * cta, r, bar_wq);
                    }
                }
                if (t == 3) {
                    asm volatile("prefetch.tensormap [%0];" ::"l"(&tm_v) : "memory");
                    asm volatile("prefetch.tensormap [%0];" ::"l"(&tm_wo) : "memory");
                    asm volatile("prefetch.tensormap [%0];" ::"l"(&tm_w1) : "memory");
                    asm volatile("prefetch.tensormap [%0];" ::"l"(&tm_w2) : "memory");
                }
                if (t == NS && late) {
                    mbar_wait(bar_full + (NS - INFLIGHT) * 8, 0);
                    mbar_expect_tx(bar_wm, D * 64);
#pragma unroll 1
                    for (int r = 0; r < D; r += 160) tma2d(sb + X_WM + r * 64, &tm_wmod, 32 * mc, r, bar_wm);
                }
                if (t == NITEM) {
                    mbar_wait(bar_xfree, 0);
                    if (WO_GATE <= 2) { mbar_wait(bar_v + (2 - WO_GATE) * 16, 0); mbar_wait(bar_v + (2 - WO_GATE) * 16 + 8, 0); }
                    else mbar_wait(bar_full + ((NITEM - WO_GATE) & (NS - 1)) * 8, ((NITEM - WO_GATE) >> 3) & 1);
#pragma unroll 1
                    for (int i = 0; i < 5; i++) {
                        mbar_expect_tx(bar_wo + i * 8, DH * 64);
                        tma2d(sb + X_WO + i * (DH * 64), &tm_wo, bown * 160 + i * 32, head * DH, bar_wo + i * 8);
                    }
                    if (is_f) {
                        mbar_wait(bar_wo + WF_GATE * 8, 0);
                        { const uint32_t c0 = clock32(); while (clock32() - c0 < WF_DELAY) { } }
                        mbar_expect_tx(bar_w1, D * 64);
#pragma unroll 1
                        for (int r = 0; r < D; r += 160) tma2d(sb + X_W1 + r * 64, &tm_w1, 32 * f, r, bar_w1);
#pragma unroll 1
                        for (int i = 0; i < 3; i++) mbar_wait(bar_empty + i * 8, ((NITEM >> 3) - 1) & 1);
                        { const uint32_t c0 = clock32(); while (clock32() - c0 < W2_DELAY) { } }
                        mbar_expect_tx(bar_w2, D * 64);
#pragma unroll 1
                        for (int i = 0; i < 10; i++) tma2d(sb + X_W2 + i * 4096, &tm_w2, 64 * i, 32 * f, bar_w2);
                    }
                    break;
                }
                const int s = t & (NS - 1);
                if (t >= NS) {
                    mbar_wait(bar_empty + s * 8, ((t >> 3) - 1) & 1);
                    while ((int)(gtime32() - t_start) < PACE_A + (t - NS) * PACE_TAU) { }
                } else if (t >= INFLIGHT) {
                    mbar_wait(bar_full + (t - INFLIGHT) * 8, 0);
                }
                if (t < NITEM - 2) {
                    const int pair = t == NITEM - 3 ? NITEM / 2 - 1 : t >> 1;
                    mbar_expect_tx(bar_full + s * 8, TILE_BYTES);
                    bulk_load(sb + OFF_RING + s * TILE_BYTES, ((t & 1) && t != NITEM - 3 ? vb : kb) + (size_t)((pair + rot) & (NITEM / 2 - 1)) * TILE_BYTES, TILE_BYTES, bar_full + s * 8, pol);
                } else {
                    const int row = (bown * NH + head) * SK + (SK - WIN) + ((t - NITEM / 2 + rot) & (NITEM / 2 - 1)) * TILE_KEYS;
#pragma unroll 1
                    for (int i = 0; i < 2; i++) {
                        const uint32_t bar = bar_v + (2 * (t - (NITEM - 2)) + i) * 8;
                        mbar_expect_tx(bar, TILE_BYTES / 2);
                        tma2d_hint(sb + OFF_RING + s * TILE_BYTES + i * (TILE_BYTES / 2), &tm_v, 64 * i, row, bar, pol);
                    }
                }
            }
        }
        return;
    }

    if (warp == 9) {
        mbar_wait(bar_full + (NS - 1) * 8, 0);
        if (lane < 16) stg_zero4(g_o + cta * 64 + lane * 4);
        if (is_owner) {
#pragma unroll 1
            for (int i = lane; i < NH * 8; i += 32) stg_zero4(g_p1 + own * (NH * 32) + i * 4);
#pragma unroll 1
            for (int i = lane; i < NF * 8; i += 32) stg_zero4(g_p2 + own * (NF * 32) + i * 4);
            if (lane < 4) stg_zero4(g_x1 + own * 16 + lane * 4);
        }
        __threadfence();
        __syncwarp();
        if (lane == 0) stg_relaxed(g_clr + cta, 1u);
        HPROF(0);
        HPROF(2);
        while ((int)(gtime32() - t_start) < CLR_CHECK) __nanosleep(1000);
        {
            int it = 0;
            while (!__all_sync(0xffffffffu, ready(ldg_relaxed(g_clr + lane * 4)))) { __nanosleep(2000); if (++it > SPIN_LIMIT) __trap(); }
        }
        __threadfence();
        __syncwarp();
        HPROF(3);
        if (lane == 0) mbar_arrive(bar_help);
        {
            const uint32_t* const src = pin(g_o + (cta & ~3) * 64 + lane * 4);
            const uint32_t dst = pin(sb + OFF_O + (lane >> 4) * O_STRIDE + (lane & 15) * 16);
            mbar_wait(bar_v + 16, 0);
            mbar_wait(bar_v + 24, 0);
            uint4 v[2];
            const uint32_t* const ptr[2] = {src, src + 128};
            const bool on[2] = {true, true};
            poll_n<2>(v, ptr, on);
            sts128(dst, v[0]);
            sts128(dst + 2 * O_STRIDE, v[1]);
#pragma unroll
            for (int w = 0; w < 8; w++) asm volatile("bar.arrive %0, 64;" ::"r"(NB_O + w) : "memory");
        }
        HPROF(4);
        return;
    }

    const int g = lane >> 2, t4 = lane & 3;
    const int mi = lane >> 3, r8 = lane & 7;

    {
        auto silu4 = [&](const uint4& cv) {
            uint32_t w4[4] = {cv.x, cv.y, cv.z, cv.w};
#pragma unroll
            for (int e = 0; e < 4; e++) {
                float c0 = bf_lo(w4[e]), c1 = bf_hi(w4[e]);
                w4[e] = pack_bf(c0 * rcp_fast(1.f + ex2(-1.4426950408889634f * c0)), c1 * rcp_fast(1.f + ex2(-1.4426950408889634f * c1)));
            }
            return make_uint4(w4[0], w4[1], w4[2], w4[3]);
        };
        if (crit || late) {
            uint4 v = silu4(ca0);
            sts128(sb + OFF_VA + (tid / 80) * VEC_STRIDE + (tid % 80) * 16, v);
            if (tid < 64) { v = silu4(ca1); sts128(sb + OFF_VA + 3 * VEC_STRIDE + (16 + tid) * 16, v); }
        }
        if (warp < 4) {
            float s = 0.f, q = 0.f;
            const float pv = __shfl_sync(0xffffffffu, bf_lo(xs[0].x), 0);
#pragma unroll
            for (int i = 0; i < 3; i++) if (i < 2 || lane < 16) acc_stats(xs[i], pv, s, q);
#pragma unroll
            for (int of = 16; of > 0; of >>= 1) { s += __shfl_xor_sync(0xffffffffu, s, of); q += __shfl_xor_sync(0xffffffffu, q, of); }
            uint32_t m2; float rden;
            ln_finish(pv, s, q, m2, rden);
            if (lane == 0) { sts32(sb + OFF_STAT + warp * 8, m2); sts_f32(sb + OFF_STAT + warp * 8 + 4, rden); }
        } else if (warp == 4) {
            sts32(sb + OWN_X + lane * 4, bf2_add(own0, 0u));
            sts_f32(sb + OWN_B1 + lane * 4, bf2f(own2));
        }
    }
    bar_cons();
    PROF(24);
    uint32_t qf[8][2];
    float o[8][4];
#pragma unroll
    for (int c = 0; c < 8; c++) { o[c][0] = o[c][1] = o[c][2] = o[c][3] = 0.f; }
    float m_run = -INFINITY, l_run = 0.f;
    const bool diag = (t4 == (g >> 1));
    const bool odd = g & 1;
    const uint32_t koff = (warp & 3) * 4096 + (r8 + 8 * (mi & 1)) * 256 + (mi >> 1) * 128 + (r8 << 4);
    const uint32_t voff = TILE_BYTES + (warp & 3) * 4096 + (r8 + 8 * (mi >> 1)) * 256 + (mi & 1) * 128 + (r8 << 4);
    const int src0 = (2 * t4) * 4 + t4, src1 = (2 * t4 + 1) * 4 + t4;
#pragma unroll 1
    for (int step = crit ? 0 : 1; step < 3; step++) {
        if (step < 2 || late) {
            if (step == 1) {
                if (!crit) mbar_wait(bar_wq, 0);
                const uint32_t m2 = lds32(sb + OFF_STAT + (tid & 3) * 8);
                const float rden = lds_f32(sb + OFF_STAT + (tid & 3) * 8 + 4);
                uint4 v[4] = {xa, xa, xa, xa};
                const uint32_t* const ptr[4] = {mod_slot(0, tid >> 2, tid & 3), mod_slot(1, tid >> 2, tid & 3),
                                                mod_slot(0, 64 + ((tid & 63) >> 2), tid & 3), mod_slot(1, 64 + ((tid & 63) >> 2), tid & 3)};
                const bool on[4] = {true, true, tid < 64, tid < 64};
                poll_n<4>(v, ptr, on);
                uint4 h0 = ln_mod4(xa, v[1], v[0], m2, rden);
                sts128(sb + OFF_VB + (tid & 3) * VEC_STRIDE + (tid >> 2) * 16, h0);
                if (tid < 64) {
                    h0 = ln_mod4(xb, v[3], v[2], m2, rden);
                    sts128(sb + OFF_VB + (tid & 3) * VEC_STRIDE + (64 + (tid >> 2)) * 16, h0);
                }
            }
            mbar_wait(step == 1 ? bar_wq : bar_wm, 0);
            bar_cons();
            const uint32_t strip = sb + (step == 1 ? X_WQ : X_WM), vec = sb + (step == 1 ? OFF_VB : OFF_VA);
            float acc[2][4];
#pragma unroll
            for (int m = 0; m < 2; m++) { acc[m][0] = acc[m][1] = acc[m][2] = acc[m][3] = 0.f; }
#pragma unroll
            for (int i = 0; i < 5; i++) {
                int k0 = (warp * 5 + i) * 16;
                uint32_t b0, b1;
                load_bfrag(vec, VEC_STRIDE, k0, g, t4, b0, b1);
                int krow = k0 + r8 + 8 * (mi >> 1);
#pragma unroll
                for (int m = 0; m < 2; m++) {
                    uint32_t a[4];
                    int ch = 2 * m + (mi & 1);
                    ldsm4t(a, strip + krow * 64 + ((ch ^ ((krow >> 1) & 3)) << 4));
                    mma16816(acc[m], a, b0, b1);
                }
            }
            if (t4 < 2) {
#pragma unroll
                for (int m = 0; m < 2; m++) {
                    sts_f32x2(sb + OFF_RED + ((warp * 32 + m * 16 + g) * 4 + 2 * t4) * 4, acc[m][0], acc[m][1]);
                    sts_f32x2(sb + OFF_RED + ((warp * 32 + m * 16 + g + 8) * 4 + 2 * t4) * 4, acc[m][2], acc[m][3]);
                }
            }
            bar_cons();
            if (tid < 128) {
                float v = 0.f;
#pragma unroll
                for (int w = 0; w < 8; w++) v += lds_f32(sb + OFF_RED + (w * 128 + tid) * 4);
                float vn = __shfl_down_sync(0xffffffffu, v, 4);
                uint32_t* dst = step == 1 ? g_q + ((cta & ~3) + (tid & 3)) * 64 + bown * 16 + (tid >> 3) : g_mod + mc * 64 + (tid & 3) * 16 + (tid >> 3);
                if (!((tid >> 2) & 1)) stg_relaxed(dst, ~pack_bf(v, vn));
            }
        }
        if (step == 0) continue;
        if (step == 1) {
            if (warp == 0) {
                uint4 v = poll1(g_q + cta * 64 + (lane & 15) * 4, lane < 16);
                if (lane < 16) {
                    sts128(sb + OFF_Q + lane * 16, v);
                    stg_zero4(g_q + cta * 64 + lane * 4);
                }
            }
            bar_cons();
            PROF(4);

#pragma unroll
            for (int c = 0; c < 8; c++) {
                qf[c][0] = lds32(sb + OFF_Q + (((c ^ g) * 4 + t4) << 2));
                qf[c][1] = lds32(sb + OFF_Q + 128 + (((c ^ g) * 4 + t4) << 2));
            }
        } else {
            bar_cons();
            if (tid == 0) mbar_arrive(bar_xfree);
        }
#pragma unroll 1
        for (int j = (step == 1 ? 0 : SEG_J) + (warp >> 2); j < (step == 1 ? SEG_J : NITEM / 2 - 2); j += 2) {
            const int s = (2 * j) & (NS - 1);
            const uint32_t par = (j >> 2) & 1;
            mbar_wait(bar_full + s * 8, par);
            const uint32_t base = sb + OFF_RING + s * TILE_BYTES;
            float sa[4] = {0.f, 0.f, 0.f, 0.f}, sb2[4] = {0.f, 0.f, 0.f, 0.f};
#pragma unroll
            for (int c = 0; c < 8; c += 2) {
                uint32_t a[4], a2[4];
                ldsm4(a, (base + koff) ^ (c << 4));
                ldsm4(a2, (base + koff) ^ ((c + 1) << 4));
                mma16816(sa, a, qf[c][0], qf[c][1]);
                mma16816(sb2, a2, qf[c + 1][0], qf[c + 1][1]);
            }
            const uint32_t sw = pack_bf(odd ? sa[1] + sb2[1] : sa[0] + sb2[0], odd ? sa[3] + sb2[3] : sa[2] + sb2[2]);
            const uint32_t sv = pack_bf(bf_lo(sw) * 0.08838834764831845f, bf_hi(sw) * 0.08838834764831845f);
            const float s0 = bf_lo(sv) * 1.4426950408889634f, s1 = bf_hi(sv) * 1.4426950408889634f;
            float m_new = fmaxf(m_run, fmaxf(s0, s1));
            const bool grow = __any_sync(0xffffffffu, (diag && (m_new > m_run)));
            if (lane == 0) mbar_arrive(bar_empty + s * 8);
            if (grow) {
                float al = ex2(m_run - m_new);
                float a0 = __shfl_sync(0xffffffffu, al, src0), a1 = __shfl_sync(0xffffffffu, al, src1);
#pragma unroll
                for (int c = 0; c < 8; c++) { o[c][0] *= a0; o[c][1] *= a1; o[c][2] *= a0; o[c][3] *= a1; }
                l_run *= al;
                m_run = m_new;
            }
            uint32_t pw = pack_bf(ex2(s0 - m_run), ex2(s1 - m_run));
            l_run += bf_lo(pw) + bf_hi(pw);
            uint32_t b0 = odd ? (pw << 16) : (pw & 0xffffu);
            uint32_t b1 = odd ? (pw & 0xffff0000u) : (pw >> 16);
            if (!diag) { b0 = 0u; b1 = 0u; }
            mbar_wait(bar_full + (s + 1) * 8, par);
#pragma unroll
            for (int c = 0; c < 8; c++) {
                uint32_t a[4];
                ldsm4t(a, (base + voff) ^ (c << 4));
                mma16816(o[c], a, b0, b1);
            }
            __syncwarp();
            if (lane == 0) mbar_arrive(bar_empty + (s + 1) * 8);
        }
    }
    PROF(5);
    uint32_t ga_w = 1, gb_w = 1;
    uint32_t cs[10];
    const uint32_t* const ga_p = mod_slot(2, own, (lane >> 2) & 3) + (lane & 3);
    const uint32_t* const gb_p = mod_slot(5, own, (lane >> 2) & 3) + (lane & 3);
    if (is_owner && warp == 0) { ga_w = ldg_relaxed32(ga_p); gb_w = ldg_relaxed32(gb_p); }
#pragma unroll
    for (int j = 0; j < 10; j++) cs[j] = is_f ? ldg_relaxed32(mod_slot(g < 4 ? 4 : 3, 10 * warp + j, g & 3) + t4) : 1u;
    float acc[4][4];
    uint32_t pa[8][2];
    float rinv;
    {
        const int s = 4 + (warp >> 2);
        mbar_wait(bar_full + s * 8, 1);
        const uint32_t base = sb + OFF_RING + s * TILE_BYTES;
        float sa[4] = {0.f, 0.f, 0.f, 0.f}, sb2[4] = {0.f, 0.f, 0.f, 0.f};
#pragma unroll
        for (int c = 0; c < 8; c += 2) {
            uint32_t a[4], a2[4];
            ldsm4(a, (base + koff) ^ (c << 4));
            ldsm4(a2, (base + koff) ^ ((c + 1) << 4));
            mma16816(sa, a, qf[c][0], qf[c][1]);
            mma16816(sb2, a2, qf[c + 1][0], qf[c + 1][1]);
        }
        const uint32_t sw = pack_bf(odd ? sa[1] + sb2[1] : sa[0] + sb2[0], odd ? sa[3] + sb2[3] : sa[2] + sb2[2]);
        const uint32_t sv = pack_bf(bf_lo(sw) * 0.08838834764831845f, bf_hi(sw) * 0.08838834764831845f);
        const float s0 = bf_lo(sv) * 1.4426950408889634f, s1 = bf_hi(sv) * 1.4426950408889634f;
        int mi_ = __float_as_int(diag ? fmaxf(m_run, fmaxf(s0, s1)) : -INFINITY);
        mi_ ^= (mi_ >> 31) & 0x7fffffff;
        mi_ = __reduce_max_sync(0xffffffffu, mi_);
        mi_ ^= (mi_ >> 31) & 0x7fffffff;
        if (lane == 0) sts32(sb + OFF_ML + warp * 4, mi_);
        bar_cons();
        const float4 m0 = lds_f32x4(sb + OFF_ML), m1 = lds_f32x4(sb + OFF_ML + 16);
        const float mx = fmaxf(fmaxf(fmaxf(m0.x, m0.y), fmaxf(m0.z, m0.w)), fmaxf(fmaxf(m1.x, m1.y), fmaxf(m1.z, m1.w)));
        const float scl = ex2(m_run - mx);
        const uint32_t pw = pack_bf(ex2(s0 - mx), ex2(s1 - mx));
        if (diag) { sts16(sb + SC_P + (warp * 16 + g) * 2, pw); sts16(sb + SC_P + (warp * 16 + g + 8) * 2, pw >> 16); }
        const float lw = warp_sum(diag ? fmaf(l_run, scl, bf_lo(pw) + bf_hi(pw)) : 0.f);
        const float a0 = __shfl_sync(0xffffffffu, scl, src0), a1 = __shfl_sync(0xffffffffu, scl, src1);
        float v[8], u[8];
#pragma unroll
        for (int c = 0; c < 8; c++) {
            v[c] = a0 * o[c][0] + a1 * o[c ^ 1][1];
            u[c] = a0 * o[c][2] + a1 * o[c ^ 1][3];
        }
#pragma unroll
        for (int c = 0; c < 8; c++) {
            if (!(c & 2)) {
                v[c] += __shfl_xor_sync(0xffffffffu, v[c ^ 2], 1);
                u[c] += __shfl_xor_sync(0xffffffffu, u[c ^ 2], 1);
            }
        }
#pragma unroll
        for (int c = 0; c < 2; c++) {
            v[c] += __shfl_xor_sync(0xffffffffu, v[c ^ 4], 2);
            u[c] += __shfl_xor_sync(0xffffffffu, u[c ^ 4], 2);
        }
        const uint32_t dst = sb + SC_OP + (warp * 128 + 16 * t4 + g) * 4;
        sts_f32(dst, v[0]); sts_f32(dst + 32, v[1]); sts_f32(dst + 256, u[0]); sts_f32(dst + 288, u[1]);
        if (lane == 0) sts_f32(sb + OFF_ML + 32 + warp * 4, lw);
        mbar_wait(bar_help, 0);
        bar_cons();
        const float4 l0 = lds_f32x4(sb + OFF_ML + 32), l1 = lds_f32x4(sb + OFF_ML + 48);
        rinv = rcp_fast(((l0.x + l0.y) + (l0.z + l0.w)) + ((l1.x + l1.y) + (l1.z + l1.w)));
#pragma unroll
        for (int i = 0; i < 4; i++) acc[i][0] = acc[i][1] = acc[i][2] = acc[i][3] = 0.f;
#pragma unroll
        for (int w = 0; w < 8; w++) {
            const float2 x0 = lds_f32x2(sb + SC_OP + (w * 128 + 16 * warp + 2 * t4) * 4), x1 = lds_f32x2(sb + SC_OP + (w * 128 + 16 * warp + 8 + 2 * t4) * 4);
            acc[2 * (w & 1)][0] += x0.x; acc[2 * (w & 1)][1] += x0.y;
            acc[2 * (w & 1) + 1][0] += x1.x; acc[2 * (w & 1) + 1][1] += x1.y;
        }
#pragma unroll
        for (int ks = 0; ks < 8; ks++) { pa[ks][0] = lds32(sb + SC_P + (8 * ks + t4) * 4); pa[ks][1] = lds32(sb + SC_P + (8 * ks + 4 + t4) * 4); }
    }
    PROF(20);
    const int mt = warp < 2 ? warp : warp + 2;
    {
        const uint32_t va = pin(sb + OFF_RING + 6 * TILE_BYTES + (warp >> 2) * (TILE_BYTES / 2) + (8 * (mi & 1) + r8) * 128 + (((2 * (warp & 3) + (mi >> 1)) ^ r8) << 4));
        const uint32_t vbar = pin(bar_v + (warp >> 2) * 8);
        uint32_t* const o_dst = pin(g_o + cta * 64 + warp * 8 + 2 * t4);
#pragma unroll
        for (int tl = 0; tl < 2; tl++) {
            mbar_wait(vbar + tl * 16, 0);
            uint32_t r[4][4];
#pragma unroll
            for (int ks = 0; ks < 4; ks++) ldsm4t(r[ks], va + tl * TILE_BYTES + ks * 2048);
#pragma unroll
            for (int ks = 0; ks < 4; ks++) {
                const uint32_t a[4] = {pa[4 * tl + ks][0], 0u, pa[4 * tl + ks][1], 0u};
                mma16816(acc[2 * (ks & 1)], a, r[ks][0], r[ks][1]);
                mma16816(acc[2 * (ks & 1) + 1], a, r[ks][2], r[ks][3]);
            }
        }
        if (g == 0) stg_relaxed2(o_dst, ~pack_bf((acc[0][0] + acc[2][0]) * rinv, (acc[0][1] + acc[2][1]) * rinv),
                                 ~pack_bf((acc[1][0] + acc[3][0]) * rinv, (acc[1][1] + acc[3][1]) * rinv));
    }
    PROF(7);
    {
        const int kap = 2 * (head & 1) + ((head >> 1) & 1);
        const uint32_t wa = pin(sb + X_WO + (mt >> 1) * (DH * 64) + (r8 + 8 * (mi >> 1)) * 64 + ((((mt & 1) * 2 + (mi & 1)) ^ ((r8 >> 1) & 3)) << 4));
        const uint32_t oa = pin(sb + OFF_O + ((g & 3) ^ kap) * O_STRIDE + t4 * 8);
        uint32_t* const dst = pin(g_p1 + (((bown * 20 + 2 * mt) * NH + head) * 8 + g) * 4 + 2 * t4);
        const uint32_t obar = pin(NB_O + warp);
        uint32_t wf[8][4], wg[8][4];
        mbar_wait(bar_wo + (mt >> 1) * 8, 0);
#pragma unroll
        for (int ks = 0; ks < 8; ks++) ldsm4t(wf[ks], wa + ks * 1024);
        if (warp < 2) {
            mbar_wait(bar_wo + 8, 0);
#pragma unroll
            for (int ks = 0; ks < 8; ks++) ldsm4t(wg[ks], wa + DH * 64 + ks * 1024);
        }
        asm volatile("bar.sync %0, 64;" ::"r"(obar) : "memory");
        PROF(8);
        uint2 ob[8];
#pragma unroll
        for (int ks = 0; ks < 8; ks++) ob[ks] = lds64(oa + ks * 32);
        float c0[4] = {0.f, 0.f, 0.f, 0.f}, c1[4] = {0.f, 0.f, 0.f, 0.f};
        if (warp < 2) {
            float c2[4] = {0.f, 0.f, 0.f, 0.f}, c3[4] = {0.f, 0.f, 0.f, 0.f};
#pragma unroll
            for (int ks = 0; ks < 8; ks += 2) {
                mma16816(c0, wf[ks], ob[ks].x, ob[ks].y);
                mma16816(c2, wg[ks], ob[ks].x, ob[ks].y);
                mma16816(c1, wf[ks + 1], ob[ks + 1].x, ob[ks + 1].y);
                mma16816(c3, wg[ks + 1], ob[ks + 1].x, ob[ks + 1].y);
            }
            if (t4 < 2) {
                stg_relaxed2(dst + 4 * NH * 32, flag(c2[0] + c3[0]), flag(c2[1] + c3[1]));
                stg_relaxed2(dst + 5 * NH * 32, flag(c2[2] + c3[2]), flag(c2[3] + c3[3]));
            }
        } else {
#pragma unroll
            for (int ks = 0; ks < 8; ks += 2) {
                mma16816(c0, wf[ks], ob[ks].x, ob[ks].y);
                mma16816(c1, wf[ks + 1], ob[ks + 1].x, ob[ks + 1].y);
            }
        }
        if (t4 < 2) {
            stg_relaxed2(dst, flag(c0[0] + c1[0]), flag(c0[1] + c1[1]));
            stg_relaxed2(dst + NH * 32, flag(c0[2] + c1[2]), flag(c0[3] + c1[3]));
        }
    }
    PROF(9);
    const uint32_t red_st = (((warp * 4 + 2 * ((lane >> 3) & 1) + (lane >> 4)) * 8 + (lane & 7)) * 4);
    uint32_t x1w = 0;
    if (is_owner) {
        const uint32_t* const in = pin(g_p1 + (own * NH * 8 + tid) * 4);
        const uint32_t st = pin(sb + SC_E4 + red_st), ld = pin(sb + SC_E4 + (lane & 15) * 8);
        const int jo = own % 10;
        uint32_t* const dst = pin(g_x1 + ((lane >> 2) & 3) * 320 + (own / 10) * 40 + (jo < 8 ? (jo >> 2) * 16 + 4 * t4 + (jo & 3) : 24 + 2 * t4 + jo));
        uint32_t xw = 0;
        if (warp == 0) {
            int it = 0;
            while (__any_sync(0xffffffffu, ga_w == 0u || gb_w == 0u)) { ga_w = ldg_relaxed32(ga_p); gb_w = ldg_relaxed32(gb_p); if (++it > SPIN_LIMIT) __trap(); }
            ga_w = pin(~ga_w);
            gb_w = pin(~gb_w);
            xw = lds32(sb + OWN_X + (lane & 15) * 4);
        }
        uint4 v;
        for (int it = 0;; it++) {
            v = ldg_relaxed(in);
            if (__all_sync(0xffffffffu, v.x & v.y & v.z & v.w & 1u)) break;
            if (it > SPIN_LIMIT) __trap();
        }
        PROF(11);
        const float s0 = __uint_as_float(v.x) + __shfl_xor_sync(0xffffffffu, __uint_as_float(v.z), 8);
        const float s1 = __uint_as_float(v.y) + __shfl_xor_sync(0xffffffffu, __uint_as_float(v.w), 8);
        sts_f32(st, s0 + __shfl_xor_sync(0xffffffffu, s1, 16));
        if (warp == 0) {
            nbar_sync<NB_E4>();
            float2 a[8];
#pragma unroll
            for (int w = 0; w < 8; w++) a[w] = lds_f32x2(ld + w * 128);
            const uint32_t aw = pack_bf(((a[0].x + a[1].x) + (a[2].x + a[3].x)) + ((a[4].x + a[5].x) + (a[6].x + a[7].x)),
                                        ((a[0].y + a[1].y) + (a[2].y + a[3].y)) + ((a[4].y + a[5].y) + (a[6].y + a[7].y)));
            x1w = bf2_add(xw, bf2_mul(ga_w, aw));
            if (lane < 16) stg_relaxed(dst, x1w ^ 0x80008000u);
        } else {
            nbar_arrive<NB_E4>();
        }
    }
    PROF(12);
    if (is_f) {
        const int kap = 2 * (f & 1) + ((f >> 1) & 1);
        uint32_t f1[5][2][4], f2[5][2][4];
        {
            int it = 0;
            while (true) {
                bool miss = false;
#pragma unroll
                for (int j = 0; j < 10; j++) miss |= cs[j] == 0u;
                if (!__any_sync(0xffffffffu, miss)) break;
#pragma unroll
                for (int j = 0; j < 10; j++) cs[j] = ldg_relaxed32(mod_slot(g < 4 ? 4 : 3, 10 * warp + j, g & 3) + t4);
                if (++it > SPIN_LIMIT) __trap();
            }
#pragma unroll
            for (int j = 0; j < 10; j++) cs[j] = bf2_add(~cs[j], g < 4 ? 0x3f803f80u : 0u);
        }
        const uint32_t piv = lds32(sb + OFF_STAT + (g & 3) * 8);
        const uint32_t* const xin = pin(g_x1 + (g & 3) * 320 + warp * 40 + 4 * t4);
        const uint32_t* const xin2 = pin(g_x1 + (g & 3) * 320 + warp * 40 + 32 + 2 * t4);
        const uint32_t y_st = pin(sb + SC_Y + ((warp * 32 + g) * 4 + 2 * t4) * 4), y_ld = pin(sb + SC_Y + tid * 4);
        const uint32_t s_st = pin(sb + SC_ST + ((g & 3) * 8 + warp) * 8), s_ld = pin(sb + SC_ST + (tid & 3) * 64);
        const uint32_t h_st = pin(sb + SC_H1 + (tid & 3) * 64 + ((tid >> 3) & 3) * 16 + ((tid >> 5) & 3) * 4 + ((tid >> 2) & 1) * 2);
        const uint32_t h_ld = pin(sb + SC_H1 + ((g & 3) ^ kap) * 64 + t4 * 16);
        uint32_t* const dst = pin(g_p2 + ((10 * warp * NF + f) * 8 + g) * 4 + 2 * t4);
        uint32_t w2a[5];
#pragma unroll
        for (int i = 0; i < 5; i++) {
            const int cc = 2 * (warp * 5 + i) + (mi & 1);
            w2a[i] = pin(sb + X_W2 + (cc >> 3) * 4096 + (r8 + 8 * (mi >> 1)) * 128 + (((cc & 7) ^ r8) << 4));
        }
        float ab_a = 0.f, ab_b = 0.f;
        {
            const uint32_t wa = sb + X_W1 + (warp * 80 + r8 + 8 * (mi >> 1)) * 64 + (((mi & 1) ^ ((r8 >> 1) & 3)) << 4);
            mbar_wait(bar_w1, 0);
#pragma unroll
            for (int i = 0; i < 5; i++) { ldsm4t(f1[i][0], wa + i * 1024); ldsm4t(f1[i][1], (wa ^ 32) + i * 1024); }
            float c[2][4];
#pragma unroll
            for (int m = 0; m < 2; m++) c[m][0] = c[m][1] = c[m][2] = c[m][3] = 0.f;
#pragma unroll
            for (int i = 0; i < 5; i++) { mma16816(c[0], f1[i][0], cs[2 * i], cs[2 * i + 1]); mma16816(c[1], f1[i][1], cs[2 * i], cs[2 * i + 1]); }
#pragma unroll
            for (int m = 0; m < 2; m++) {
                sts_f32x2(sb + SC_AB + ((warp * 32 + m * 16 + g) * 8 + 2 * t4) * 4, c[m][0], c[m][1]);
                sts_f32x2(sb + SC_AB + ((warp * 32 + m * 16 + g + 8) * 8 + 2 * t4) * 4, c[m][2], c[m][3]);
            }
            if (warp < 4) {
                nbar_sync<NB_AB>();
                ab_b = lds_f32(sb + OWN_B1 + (tid >> 2) * 4);
#pragma unroll
                for (int w = 0; w < 8; w++) {
                    ab_a += lds_f32(sb + SC_AB + ((w * 32 + (tid >> 2)) * 8 + (tid & 3)) * 4);
                    ab_b += lds_f32(sb + SC_AB + ((w * 32 + (tid >> 2)) * 8 + 4 + (tid & 3)) * 4);
                }
            } else {
                nbar_arrive<NB_AB>();
            }
        }
        const bool have_w2 = __all_sync(0xffffffffu, mbar_test(bar_w2, 0));
        if (have_w2) {
#pragma unroll
            for (int i = 0; i < 5; i++) { ldsm4t(f2[i][0], w2a[i]); ldsm4t(f2[i][1], w2a[i] + 2048); }
        }
        PROF(10);
        uint32_t d[10];
        {
            uint4 va = make_uint4(1, 1, 1, 1), vb = va;
            uint2 vc = make_uint2(1, 1);
            for (int it = 0;; it++) {
                if (g < 4) { va = ldg_relaxed(xin); vb = ldg_relaxed(xin + 16); vc = ldg_relaxed64(xin2); }
                const uint32_t mn = min(min(min(min(va.x, va.y), va.z), min(min(va.w, vb.x), vb.y)), min(min(min(vb.z, vb.w), vc.x), vc.y));
                if (__all_sync(0xffffffffu, mn != 0u)) break;
                if (it > SPIN_LIMIT) __trap();
            }
            PROF(13);
            d[0] = va.x; d[1] = va.y; d[2] = va.z; d[3] = va.w; d[4] = vb.x; d[5] = vb.y; d[6] = vb.z; d[7] = vb.w; d[8] = vc.x; d[9] = vc.y;
        }
        {
            float y[2][4], st[4] = {0.f, 0.f, 0.f, 0.f};
#pragma unroll
            for (int m = 0; m < 2; m++) y[m][0] = y[m][1] = y[m][2] = y[m][3] = 0.f;
#pragma unroll
            for (int i = 0; i < 5; i++) {
                const uint32_t d0 = bf2_add(d[2 * i], piv), d1 = bf2_add(d[2 * i + 1], piv);
                const uint32_t a[4] = {d0, 0x3f803f80u, d1, 0x3f803f80u};
                mma16816(st, a, d0, d1);
                const uint32_t y0 = bf2_mul(d0, cs[2 * i]), y1 = bf2_mul(d1, cs[2 * i + 1]);
                mma16816(y[0], f1[i][0], y0, y1);
                mma16816(y[1], f1[i][1], y0, y1);
            }
            if (diag && g < 4) sts_f32x2(s_st, odd ? st[1] : st[0], odd ? st[3] : st[2]);
            if (t4 < 2) {
#pragma unroll
                for (int m = 0; m < 2; m++) { sts_f32x2(y_st + m * 256, y[m][0], y[m][1]); sts_f32x2(y_st + m * 256 + 128, y[m][2], y[m][3]); }
            }
        }
        if (warp < 4) {
            nbar_sync<NB_Y>();
            PROF(14);
            float4 q[4];
            float yy[8];
#pragma unroll
            for (int i = 0; i < 4; i++) q[i] = lds_f32x4(s_ld + i * 16);
#pragma unroll
            for (int w = 0; w < 8; w++) yy[w] = lds_f32(y_ld + w * 512);
            const float dm = (((q[0].y + q[0].w) + (q[1].y + q[1].w)) + ((q[2].y + q[2].w) + (q[3].y + q[3].w))) * (1.f / D);
            const float sq = ((q[0].x + q[0].z) + (q[1].x + q[1].z)) + ((q[2].x + q[2].z) + (q[3].x + q[3].z));
            const float r = rsqrt_fast(fmaxf(fmaf(-dm, dm, sq * (1.f / D)), 0.f) + 1e-5f);
            const float ys = ((yy[0] + yy[1]) + (yy[2] + yy[3])) + ((yy[4] + yy[5]) + (yy[6] + yy[7]));
            const float u = fmaf(r, fmaf(dm, ab_a, -ys), ab_b);
            const float e = ex2(u * fmaf(u * u, -0.044715f * 2.302208198144325f, -2.302208198144325f));
            sts16(h_st, pack_bf(u * rcp_fast(1.f + e), 0.f));
        } else {
            nbar_arrive<NB_Y>();
        }
        if (!have_w2) {
            mbar_wait(bar_w2, 0);
#pragma unroll
            for (int i = 0; i < 5; i++) { ldsm4t(f2[i][0], w2a[i]); ldsm4t(f2[i][1], w2a[i] + 2048); }
        }
        nbar_sync<NB_H1>();
        PROF(15);
        {
            const uint4 hb = lds128(h_ld);
            float c[5][4];
#pragma unroll
            for (int i = 0; i < 5; i++) { c[i][0] = c[i][1] = c[i][2] = c[i][3] = 0.f; mma16816(c[i], f2[i][0], hb.x, hb.y); }
#pragma unroll
            for (int i = 0; i < 5; i++) {
                mma16816(c[i], f2[i][1], hb.z, hb.w);
                if (t4 < 2) {
                    stg_relaxed2(dst + (2 * i) * (NF * 32), flag(c[i][0]), flag(c[i][1]));
                    stg_relaxed2(dst + (2 * i + 1) * (NF * 32), flag(c[i][2]), flag(c[i][3]));
                }
            }
        }
    }
    PROF(16);
    if (is_owner) {
        const uint32_t* const in = pin(g_p2 + own * (NF * 32) + tid * 4);
        const uint32_t st = pin(sb + SC_E6 + red_st), ld = pin(sb + SC_E6 + (lane & 15) * 8);
        uint32_t* const dst = pin((uint32_t*)(p.out + ((lane >> 2) & 3) * D + 8 * own) + t4);
        const uint32_t b2w = lds32(sb + OWN_B2 + (lane & 15) * 4);
        const bool two = tid < NF * 8 - 256;
        uint4 v, w = make_uint4(1, 1, 1, 1);
        for (int it = 0;; it++) {
            v = ldg_relaxed(in);
            if (two) w = ldg_relaxed(in + 1024);
            if (__all_sync(0xffffffffu, v.x & v.y & v.z & v.w & w.x & w.y & w.z & w.w & 1u)) break;
            if (it > SPIN_LIMIT) __trap();
        }
        PROF(17);
        const float s0 = (__uint_as_float(v.x) + __uint_as_float(w.x)) + __shfl_xor_sync(0xffffffffu, __uint_as_float(v.z) + __uint_as_float(w.z), 8);
        const float s1 = (__uint_as_float(v.y) + __uint_as_float(w.y)) + __shfl_xor_sync(0xffffffffu, __uint_as_float(v.w) + __uint_as_float(w.w), 8);
        sts_f32(st, s0 + __shfl_xor_sync(0xffffffffu, s1, 16));
        nbar_sync<NB_E6>();
        if (warp == 0) {
            float2 a[8];
#pragma unroll
            for (int i = 0; i < 8; i++) a[i] = lds_f32x2(ld + i * 128);
            const uint32_t aw = pack_bf(((a[0].x + a[1].x) + (a[2].x + a[3].x)) + ((a[4].x + a[5].x) + (a[6].x + a[7].x)),
                                        ((a[0].y + a[1].y) + (a[2].y + a[3].y)) + ((a[4].y + a[5].y) + (a[6].y + a[7].y)));
            if (lane < 16) *dst = bf2_add(x1w, bf2_mul(gb_w, bf2_add(aw, b2w)));
        }
        if (tid >= 32 && tid < 56) stg_zero4(mod_slot((tid - 32) >> 2, own, tid & 3));
    }
    if (tid == 96) stg_relaxed(g_clr + cta, 0u);
    PROF(18);
    PROF_DUMP;
}

typedef CUresult (*EncodeFn)(CUtensorMap*, CUtensorMapDataType, cuuint32_t, void*, const cuuint64_t*, const cuuint64_t*, const cuuint32_t*,
                             const cuuint32_t*, CUtensorMapInterleave, CUtensorMapSwizzle, CUtensorMapL2promotion, CUtensorMapFloatOOBfill);

static CUtensorMap make_map(EncodeFn enc, const void* ptr, int cols, int rows, int box_cols, int box_rows, CUtensorMapSwizzle sw) {
    CUtensorMap m;
    cuuint64_t dims[2] = {(cuuint64_t)cols, (cuuint64_t)rows};
    cuuint64_t strides[1] = {(cuuint64_t)cols * 2};
    cuuint32_t box[2] = {(cuuint32_t)box_cols, (cuuint32_t)box_rows};
    cuuint32_t es[2] = {1, 1};
    enc(&m, CU_TENSOR_MAP_DATA_TYPE_BFLOAT16, 2, const_cast<void*>(ptr), dims, strides, box, es, CU_TENSOR_MAP_INTERLEAVE_NONE, sw,
        CU_TENSOR_MAP_L2_PROMOTION_NONE, CU_TENSOR_MAP_FLOAT_OOB_FILL_NONE);
    return m;
}

}

extern "C" void kernel_launch(void* const* d_in, const int* in_sizes, int n_in, void* d_out, int out_size) {
    (void)in_sizes; (void)n_in; (void)out_size;
    static EncodeFn enc = nullptr;
    if (!enc) {
        void* fn = nullptr;
        cudaDriverEntryPointQueryResult qr;
        cudaGetDriverEntryPoint("cuTensorMapEncodeTiled", &fn, cudaEnableDefault, &qr);
        enc = (EncodeFn)fn;
        cudaFuncSetAttribute(fused_kernel, cudaFuncAttributeMaxDynamicSharedMemorySize, SMEM_BYTES);
    }
    Params p;
    p.x = (const __nv_bfloat16*)d_in[0];
    p.kc = (const __nv_bfloat16*)d_in[1];
    p.vc = (const __nv_bfloat16*)d_in[2];
    p.b1 = (const __nv_bfloat16*)d_in[7];
    p.b2 = (const __nv_bfloat16*)d_in[9];
    p.c = (const __nv_bfloat16*)d_in[10];
    p.out = (__nv_bfloat16*)d_out;
    CUtensorMap tm_wmod = make_map(enc, d_in[11], NMOD, D, 32, 160, CU_TENSOR_MAP_SWIZZLE_64B);
    CUtensorMap tm_wq = make_map(enc, d_in[3], NH * DH, D, 32, 160, CU_TENSOR_MAP_SWIZZLE_64B);
    CUtensorMap tm_wo = make_map(enc, d_in[4], D, NH * DH, 32, 128, CU_TENSOR_MAP_SWIZZLE_64B);
    CUtensorMap tm_w1 = make_map(enc, d_in[6], FF, D, 32, 160, CU_TENSOR_MAP_SWIZZLE_64B);
    CUtensorMap tm_w2 = make_map(enc, d_in[8], D, FF, 64, 32, CU_TENSOR_MAP_SWIZZLE_128B);
    CUtensorMap tm_v = make_map(enc, d_in[2], DH, NB * NH * SK, 64, TILE_KEYS, CU_TENSOR_MAP_SWIZZLE_128B);
    fused_kernel<<<NCTA, NTHREADS, SMEM_BYTES>>>(p, tm_wmod, tm_wq, tm_wo, tm_w1, tm_w2, tm_v);
}
```

```cpp
#include <cuda_runtime.h>
#include <cuda.h>
#include <cuda_bf16.h>
#include <stdint.h>

namespace {

constexpr int NB = 4, D = 640, NH = 32, DH = 128, SK = 8192, WIN = 2048, FF = 1728, NMOD = 6 * D;
constexpr int NCTA = 128;
constexpr int NOWN = 80;
constexpr int NF = 54;
constexpr int NTHREADS = 320;
constexpr int TILE_KEYS = 64;
constexpr int TILE_BYTES = TILE_KEYS * DH * 2;
constexpr int NITEM = 2 * WIN / TILE_KEYS;
constexpr int NS = 8;
constexpr int NMODC = 120;
constexpr int SPIN_LIMIT = 1 << 18;
#define INFLIGHT 3
#define PACE_A 8600
#define PACE_TAU 635
#define WQ_DELAY 800
#define WO_GATE 2
#define WF_GATE 4
#define WF_DELAY 0
#define W2_DELAY 0
#define WF_ALL 0
#define NPROBE 8
#define PROBE_END 10000
#define CLR_CHECK 28000
constexpr int SEG_J = 8;

constexpr int OFF_RING = 0;
constexpr int OFF_X = OFF_RING + NS * TILE_BYTES;
constexpr int X_WM = OFF_X;
constexpr int X_WQ = OFF_X + D * 64;
constexpr int X_WO = OFF_X;
constexpr int X_W1 = X_WO + 5 * DH * 64;
constexpr int X_END = X_W1 + D * 64;
constexpr int X_W2 = OFF_RING;
static_assert(X_WQ + D * 64 <= X_END, "prologue weights must fit");
constexpr int VEC_STRIDE = 1296;
constexpr int OFF_VA = X_END;
constexpr int OFF_VB = OFF_VA + 4 * VEC_STRIDE;
constexpr int OFF_RED = OFF_VB + 4 * VEC_STRIDE;
constexpr int OFF_ML = OFF_RED + 4096;
constexpr int O_STRIDE = 288;
constexpr int OFF_O = OFF_ML + 64;
constexpr int OFF_Q = OFF_O + 4 * O_STRIDE;
constexpr int OFF_OWN = OFF_Q + 256;
constexpr int OWN_X = OFF_OWN, OWN_B2 = OWN_X + 64, OWN_GA = OWN_B2 + 64, OWN_GB = OWN_GA + 64, OWN_B1 = OWN_GB + 64;
constexpr int OFF_STAT = OWN_B1 + 128;
constexpr int OFF_TAB1 = OFF_STAT + 32;
constexpr int OFF_TAB2 = OFF_TAB1 + NOWN * 4;
constexpr int OFF_SIDE = OFF_TAB2 + NOWN * 4;
constexpr int OFF_BAR = OFF_SIDE + 8;
constexpr int NBAR = 2 * NS + 18;
constexpr int SMEM_BYTES = OFF_BAR + NBAR * 8;
constexpr int SC_OP = OFF_RING + 4 * TILE_BYTES;
constexpr int SC_AB = SC_OP + 4096;
constexpr int SC_Y = SC_AB + 8192;
constexpr int SC_ST = SC_Y + 4096;
constexpr int SC_E4 = SC_ST + 256;
constexpr int SC_E6 = SC_E4 + 1024;
constexpr int SC_P = SC_E6 + 1024;
constexpr int SC_H1 = SC_P + 256;
static_assert(SMEM_BYTES <= 232448, "smem");
static_assert(OFF_BAR % 8 == 0 && OFF_X % 1024 == 0 && X_WQ % 512 == 0 && X_W1 % 512 == 0 && OFF_VA % 16 == 0 && OFF_RED % 16 == 0 && OFF_ML % 16 == 0 && OFF_O % 16 == 0 && OFF_Q % 16 == 0, "align");
constexpr int NB_O = 2  , NB_E4 = 10, NB_E6 = 11, NB_AB = 12, NB_Y = 13, NB_H1 = 14;

__device__ uint32_t g_mod[NMODC * 64];
__device__ uint32_t g_q[NCTA * 64];
__device__ uint32_t g_clr[NCTA];
constexpr int SL_P1 = 0;
constexpr int SL_P2 = SL_P1 + NOWN;
constexpr int SL_O = SL_P2 + 2 * NOWN;
constexpr int SL_X1 = SL_O + 8;
constexpr int SL_SIDE = SL_X1 + 3;
static_assert(SL_SIDE < 256, "one 2 MB page");
__device__ uint32_t g_slots[2 * 256 * 2048];
__device__ __forceinline__ uint32_t* slot(int i, int side) {
    const size_t base = ((size_t)g_slots + 0x1fffff) & ~(size_t)0x1fffff;
    return (uint32_t*)base + i * 2048 + (((__popc(i & 0x59) ^ side) & 1) << 10);
}
#define PROF_DECL
#define HPROF(i) do { } while (0)
#define PROF(i) do { } while (0)
#define PROF_DUMP do { } while (0)

__device__ __forceinline__ uint32_t smem_u32(const void* p) { return (uint32_t)__cvta_generic_to_shared(p); }
__device__ __forceinline__ void mbar_init(uint32_t bar, uint32_t cnt) { asm volatile("mbarrier.init.shared::cta.b64 [%0], %1;" ::"r"(bar), "r"(cnt) : "memory"); }
__device__ __forceinline__ void mbar_expect_tx(uint32_t bar, uint32_t bytes) { asm volatile("mbarrier.arrive.expect_tx.shared::cta.b64 _, [%0], %1;" ::"r"(bar), "r"(bytes) : "memory"); }
__device__ __forceinline__ void mbar_arrive(uint32_t bar) { asm volatile("mbarrier.arrive.shared::cta.b64 _, [%0];" ::"r"(bar) : "memory"); }
__device__ __forceinline__ void mbar_wait(uint32_t bar, uint32_t parity) {
    uint32_t ok;
    int it = 0;
    while (true) {
        asm volatile("{\n.reg .pred p;\nmbarrier.try_wait.parity.shared::cta.b64 p, [%1], %2;\nselp.u32 %0, 1, 0, p;\n}" : "=r"(ok) : "r"(bar), "r"(parity) : "memory");
        if (ok) break;
        if (++it > SPIN_LIMIT) __trap();
    }
}
__device__ __forceinline__ void bulk_load(uint32_t dst, const void* src, uint32_t bytes, uint32_t bar, uint64_t pol) {
    asm volatile("cp.async.bulk.shared::cluster.global.mbarrier::complete_tx::bytes.L2::cache_hint [%0], [%1], %2, [%3], %4;"
                 ::"r"(dst), "l"(src), "r"(bytes), "r"(bar), "l"(pol) : "memory");
}
__device__ __forceinline__ void bar_cons() { asm volatile("bar.sync 1, 256;" ::: "memory"); }
template <int ID> __device__ __forceinline__ void nbar_sync() { asm volatile("bar.sync %0, 256;" ::"n"(ID) : "memory"); }
template <int ID> __device__ __forceinline__ void nbar_arrive() { asm volatile("bar.arrive %0, 256;" ::"n"(ID) : "memory"); }
__device__ __forceinline__ bool mbar_test(uint32_t bar, uint32_t parity) {
    uint32_t ok;
    asm volatile("{\n.reg .pred p;\nmbarrier.test_wait.parity.shared::cta.b64 p, [%1], %2;\nselp.u32 %0, 1, 0, p;\n}" : "=r"(ok) : "r"(bar), "r"(parity) : "memory");
    return ok;
}
__device__ __forceinline__ uint32_t pin(uint32_t v) { asm volatile("" : "+r"(v)); return v; }
template <class T> __device__ __forceinline__ T* pin(T* v) { asm volatile("" : "+l"(v)); return v; }
__device__ __forceinline__ void ldsm4(uint32_t (&a)[4], uint32_t addr) {
    asm volatile("ldmatrix.sync.aligned.m8n8.x4.shared.b16 {%0,%1,%2,%3}, [%4];" : "=r"(a[0]), "=r"(a[1]), "=r"(a[2]), "=r"(a[3]) : "r"(addr) : "memory");
}
__device__ __forceinline__ void ldsm4t(uint32_t (&a)[4], uint32_t addr) {
    asm volatile("ldmatrix.sync.aligned.m8n8.x4.trans.shared.b16 {%0,%1,%2,%3}, [%4];" : "=r"(a[0]), "=r"(a[1]), "=r"(a[2]), "=r"(a[3]) : "r"(addr) : "memory");
}
__device__ __forceinline__ void mma16816(float (&c)[4], const uint32_t (&a)[4], uint32_t b0, uint32_t b1) {
    asm volatile("mma.sync.aligned.m16n8k16.row.col.f32.bf16.bf16.f32 {%0,%1,%2,%3}, {%4,%5,%6,%7}, {%8,%9}, {%0,%1,%2,%3};"
                 : "+f"(c[0]), "+f"(c[1]), "+f"(c[2]), "+f"(c[3]) : "r"(a[0]), "r"(a[1]), "r"(a[2]), "r"(a[3]), "r"(b0), "r"(b1));
}
__device__ __forceinline__ uint32_t lds32(uint32_t addr) { uint32_t v; asm volatile("ld.shared.u32 %0, [%1];" : "=r"(v) : "r"(addr) : "memory"); return v; }
__device__ __forceinline__ float lds_f32(uint32_t addr) { float v; asm volatile("ld.shared.f32 %0, [%1];" : "=f"(v) : "r"(addr) : "memory"); return v; }
__device__ __forceinline__ float2 lds_f32x2(uint32_t addr) { float2 v; asm volatile("ld.shared.v2.f32 {%0,%1}, [%2];" : "=f"(v.x), "=f"(v.y) : "r"(addr) : "memory"); return v; }
__device__ __forceinline__ float4 lds_f32x4(uint32_t addr) { float4 v; asm volatile("ld.shared.v4.f32 {%0,%1,%2,%3}, [%4];" : "=f"(v.x), "=f"(v.y), "=f"(v.z), "=f"(v.w) : "r"(addr) : "memory"); return v; }
__device__ __forceinline__ uint2 lds64(uint32_t addr) { uint2 v; asm volatile("ld.shared.v2.u32 {%0,%1}, [%2];" : "=r"(v.x), "=r"(v.y) : "r"(addr) : "memory"); return v; }
__device__ __forceinline__ uint4 lds128(uint32_t addr) { uint4 v; asm volatile("ld.shared.v4.u32 {%0,%1,%2,%3}, [%4];" : "=r"(v.x), "=r"(v.y), "=r"(v.z), "=r"(v.w) : "r"(addr) : "memory"); return v; }
__device__ __forceinline__ void sts16(uint32_t addr, uint32_t v) { asm volatile("st.shared.b16 [%0], %1;" ::"r"(addr), "h"((unsigned short)v) : "memory"); }
__device__ __forceinline__ void sts32(uint32_t addr, uint32_t v) { asm volatile("st.shared.u32 [%0], %1;" ::"r"(addr), "r"(v) : "memory"); }
__device__ __forceinline__ void sts_f32(uint32_t addr, float v) { asm volatile("st.shared.f32 [%0], %1;" ::"r"(addr), "f"(v) : "memory"); }
__device__ __forceinline__ void sts_f32x2(uint32_t addr, float a, float b) { asm volatile("st.shared.v2.f32 [%0], {%1,%2};" ::"r"(addr), "f"(a), "f"(b) : "memory"); }
__device__ __forceinline__ void sts128(uint32_t addr, uint4 v) { asm volatile("st.shared.v4.u32 [%0], {%1,%2,%3,%4};" ::"r"(addr), "r"(v.x), "r"(v.y), "r"(v.z), "r"(v.w) : "memory"); }
__device__ __forceinline__ uint4 ldg_relaxed(const uint32_t* p) {
    uint4 v;
    asm volatile("ld.relaxed.gpu.global.v4.u32 {%0,%1,%2,%3}, [%4];" : "=r"(v.x), "=r"(v.y), "=r"(v.z), "=r"(v.w) : "l"(p) : "memory");
    return v;
}
__device__ __forceinline__ void ldg_relaxed_if(bool on, uint4& v, const uint32_t* p) {
    asm volatile("{\n.reg .pred q;\nsetp.ne.u32 q, %5, 0;\n@q ld.relaxed.gpu.global.v4.u32 {%0,%1,%2,%3}, [%4];\n}"
                 : "+r"(v.x), "+r"(v.y), "+r"(v.z), "+r"(v.w) : "l"(p), "r"((uint32_t)on) : "memory");
}
__device__ __forceinline__ void stg_relaxed2_if(bool on, uint32_t* p, uint32_t a, uint32_t b) {
    asm volatile("{\n.reg .pred q;\nsetp.ne.u32 q, %3, 0;\n@q st.relaxed.gpu.global.v2.u32 [%0], {%1,%2};\n}" ::"l"(p), "r"(a), "r"(b), "r"((uint32_t)on) : "memory");
}
__device__ __forceinline__ uint32_t ldg_relaxed32(const uint32_t* p) { uint32_t v; asm volatile("ld.relaxed.gpu.global.u32 %0, [%1];" : "=r"(v) : "l"(p) : "memory"); return v; }
__device__ __forceinline__ void stg_relaxed(uint32_t* p, uint32_t v) { asm volatile("st.relaxed.gpu.global.u32 [%0], %1;" ::"l"(p), "r"(v) : "memory"); }
__device__ __forceinline__ void stg_relaxed2(uint32_t* p, uint32_t a, uint32_t b) { asm volatile("st.relaxed.gpu.global.v2.u32 [%0], {%1,%2};" ::"l"(p), "r"(a), "r"(b) : "memory"); }
__device__ __forceinline__ void stg_zero4(uint32_t* p) { asm volatile("st.relaxed.gpu.global.v4.u32 [%0], {%1,%1,%1,%1};" ::"l"(p), "r"(0u) : "memory"); }
__device__ __forceinline__ bool ready(const uint4& v) { return (v.x != 0u) & (v.y != 0u) & (v.z != 0u) & (v.w != 0u); }
__device__ __forceinline__ uint4 inv4(const uint4& v) { return make_uint4(~v.x, ~v.y, ~v.z, ~v.w); }
__device__ __forceinline__ uint32_t pack_bf(float lo, float hi) {
    uint32_t r;
    asm("cvt.rn.bf16x2.f32 %0, %1, %2;" : "=r"(r) : "f"(hi), "f"(lo));
    return r;
}
__device__ __forceinline__ float bfr(float x) { return __uint_as_float(pack_bf(0.f, x) & 0xffff0000u); }
__device__ __forceinline__ float bf_lo(uint32_t w) { return __uint_as_float(w << 16); }
__device__ __forceinline__ float bf_hi(uint32_t w) { return __uint_as_float(w & 0xffff0000u); }
__device__ __forceinline__ float bf2f(__nv_bfloat16 v) { return __bfloat162float(v); }
__device__ __forceinline__ float ex2(float x) { float y; asm("ex2.approx.ftz.f32 %0, %1;" : "=f"(y) : "f"(x)); return y; }
__device__ __forceinline__ float rcp_fast(float x) { float y; asm("rcp.approx.ftz.f32 %0, %1;" : "=f"(y) : "f"(x)); return y; }
__device__ __forceinline__ float rsqrt_fast(float x) { float y; asm("rsqrt.approx.ftz.f32 %0, %1;" : "=f"(y) : "f"(x)); return y; }
__device__ __forceinline__ float sqrt_fast(float x) { float y; asm("sqrt.approx.f32 %0, %1;" : "=f"(y) : "f"(x)); return y; }
__device__ __forceinline__ uint32_t bf2_add(uint32_t a, uint32_t b) { uint32_t r; asm("add.rn.bf16x2 %0, %1, %2;" : "=r"(r) : "r"(a), "r"(b)); return r; }
__device__ __forceinline__ uint32_t bf2_sub(uint32_t a, uint32_t b) { uint32_t r; asm("sub.rn.bf16x2 %0, %1, %2;" : "=r"(r) : "r"(a), "r"(b)); return r; }
__device__ __forceinline__ uint32_t bf2_mul(uint32_t a, uint32_t b) { uint32_t r; asm("mul.rn.bf16x2 %0, %1, %2;" : "=r"(r) : "r"(a), "r"(b)); return r; }
__device__ __forceinline__ uint32_t gtime32() { uint32_t c; asm volatile("mov.u32 %0, %%globaltimer_lo;" : "=r"(c)); return c; }
__device__ __forceinline__ uint32_t clock32() { uint32_t c; asm volatile("mov.u32 %0, %%clock;" : "=r"(c)); return c; }

__device__ __forceinline__ float warp_sum(float v) {
#pragma unroll
    for (int o = 16; o > 0; o >>= 1) v += __shfl_xor_sync(0xffffffffu, v, o);
    return v;
}

struct Params {
    const __nv_bfloat16 *x, *kc, *vc, *b1, *b2, *c;
    __nv_bfloat16* out;
};

__device__ __forceinline__ void tma2d(uint32_t dst, const CUtensorMap* tm, int x, int y, uint32_t bar) {
    asm volatile("cp.async.bulk.tensor.2d.shared::cluster.global.mbarrier::complete_tx::bytes [%0], [%1, {%2, %3}], [%4];"
                 ::"r"(dst), "l"(tm), "r"(x), "r"(y), "r"(bar) : "memory");
}

__device__ __forceinline__ void tma2d_hint(uint32_t dst, const CUtensorMap* tm, int x, int y, uint32_t bar, uint64_t pol) {
    asm volatile("cp.async.bulk.tensor.2d.shared::cluster.global.mbarrier::complete_tx::bytes.L2::cache_hint [%0], [%1, {%2, %3}], [%4], %5;"
                 ::"r"(dst), "l"(tm), "r"(x), "r"(y), "r"(bar), "l"(pol) : "memory");
}
__device__ __forceinline__ uint32_t flag(float v) { return __float_as_uint(v) | 1u; }
__device__ __forceinline__ uint32_t and3(uint32_t a, uint32_t b, uint32_t c) { uint32_t r; asm("lop3.b32 %0, %1, %2, %3, 0x80;" : "=r"(r) : "r"(a), "r"(b), "r"(c)); return r; }
__device__ __forceinline__ uint32_t* slot_ptr(uint32_t lo) {
    uint32_t* r;
    asm volatile("mov.b64 %0, {%1, %2};" : "=l"(r) : "r"(lo), "r"((uint32_t)((size_t)slot(0, 0) >> 32)));
    return r;
}

__device__ __forceinline__ void load_bfrag(uint32_t vec, int stride, int k0, int g, int t, uint32_t& b0, uint32_t& b1) {
    uint32_t a = vec + (g & 3) * stride + (k0 + 2 * t) * 2;
    b0 = lds32(a);
    b1 = lds32(a + 16);
}

__device__ __forceinline__ void ln_finish(float pivot, float sum, float sumsq, uint32_t& m2, float& rden) {
    float dm = sum * (1.f / D);
    float var = fmaxf(sumsq * (1.f / D) - dm * dm, 0.f);
    float mean = pivot + dm;
    m2 = pack_bf(mean, mean);
    rden = rcp_fast(bfr(sqrt_fast(bfr(bfr(var) + 1e-5f))));
}
__device__ __forceinline__ uint32_t ln_mod_pair(uint32_t xw, uint32_t cw, uint32_t sw, uint32_t m2, float rden) {
    uint32_t d = bf2_sub(xw, m2);
    uint32_t ln = pack_bf(bf_lo(d) * rden, bf_hi(d) * rden);
    return bf2_add(bf2_mul(ln, bf2_add(cw, 0x3f803f80u)), sw);
}
__device__ __forceinline__ uint4 ln_mod4(const uint4& x, const uint4& c, const uint4& s, uint32_t m2, float rden) {
    return make_uint4(ln_mod_pair(x.x, c.x, s.x, m2, rden), ln_mod_pair(x.y, c.y, s.y, m2, rden),
                      ln_mod_pair(x.z, c.z, s.z, m2, rden), ln_mod_pair(x.w, c.w, s.w, m2, rden));
}
__device__ __forceinline__ void acc_stats(const uint4& v, float pv, float& s, float& q) {
    const float a0 = bf_lo(v.x) - pv, a1 = bf_hi(v.x) - pv, a2 = bf_lo(v.y) - pv, a3 = bf_hi(v.y) - pv;
    const float a4 = bf_lo(v.z) - pv, a5 = bf_hi(v.z) - pv, a6 = bf_lo(v.w) - pv, a7 = bf_hi(v.w) - pv;
    s += ((a0 + a1) + (a2 + a3)) + ((a4 + a5) + (a6 + a7));
    q += (fmaf(a0, a0, a1 * a1) + fmaf(a2, a2, a3 * a3)) + (fmaf(a4, a4, a5 * a5) + fmaf(a6, a6, a7 * a7));
}
__device__ __forceinline__ uint32_t* mod_slot(int kind, int j, int b) { return g_mod + (kind * 20 + (j >> 2)) * 64 + b * 16 + (j & 3) * 4; }

template <int N>
__device__ __forceinline__ void poll_n(uint4 (&v)[N], const uint32_t* const* ptr, const bool* on) {
    bool pend[N];
#pragma unroll
    for (int i = 0; i < N; i++) pend[i] = on[i];
    int it = 0;
    while (true) {
#pragma unroll
        for (int i = 0; i < N; i++) if (pend[i]) v[i] = ldg_relaxed(ptr[i]);
        bool any = false;
#pragma unroll
        for (int i = 0; i < N; i++) { pend[i] = pend[i] && !ready(v[i]); any |= pend[i]; }
        if (!__any_sync(0xffffffffu, any)) break;
        if (++it > SPIN_LIMIT) __trap();
    }
#pragma unroll
    for (int i = 0; i < N; i++) v[i] = inv4(v[i]);
}
__device__ __forceinline__ uint4 poll1(const uint32_t* p, bool on) {
    uint4 v[1] = {make_uint4(0, 0, 0, 0)};
    const uint32_t* const ptr[1] = {p};
    const bool o[1] = {on};
    poll_n<1>(v, ptr, o);
    return v[0];
}

struct Roles { bool is_f, is_owner; int f, own; };
__device__ __forceinline__ Roles roles(int cta) {
    Roles r;
    r.f = (cta * 27) >> 6;
    r.is_f = (((cta + 1) * 27) >> 6) != r.f;
    r.is_owner = !r.is_f || r.f % 9 == 4;
    r.own = r.is_f ? 74 + r.f / 9 : cta - r.f;
    return r;
}

__global__ void __launch_bounds__(NTHREADS, 1)
fused_kernel(const Params p, const __grid_constant__ CUtensorMap tm_wmod, const __grid_constant__ CUtensorMap tm_wq,
             const __grid_constant__ CUtensorMap tm_wo, const __grid_constant__ CUtensorMap tm_w1, const __grid_constant__ CUtensorMap tm_w2,
             const __grid_constant__ CUtensorMap tm_v) {
    extern __shared__ __align__(1024) unsigned char smem[];
    const uint32_t sb = smem_u32(smem);
    const int cta = blockIdx.x;
    const int head = cta >> 2, bown = cta & 3;
    const uint32_t bar_full = sb + OFF_BAR, bar_empty = bar_full + NS * 8;
    const uint32_t bar_wm = bar_empty + NS * 8, bar_wq = bar_wm + 8, bar_xfree = bar_wq + 8, bar_wo = bar_xfree + 8  ;
    const uint32_t bar_w1 = bar_wo + 40  , bar_w2 = bar_w1 + 32, bar_help = bar_w2 + 8, bar_v = bar_help + 8  ;
    const int tid = threadIdx.x, warp = tid >> 5, lane = tid & 31;
    const Roles role = roles(cta);
    const bool is_f = role.is_f, is_owner = role.is_owner;
    const int f = role.f, own = role.own;
    const bool crit = (((cta + 1) * 5) >> 4) != ((cta * 5) >> 4);
    const int mr = cta - ((cta * 5) >> 4);
    const bool late = !crit && mr % 11 != 10;
    const int mc = crit ? (cta * 5) >> 4 : 40 + mr - mr / 11;

    const uint32_t t_start = gtime32();
    PROF_DECL
    PROF(0);
    uint4 xa = make_uint4(0, 0, 0, 0), xb = xa, ca0 = xa, ca1 = xa, xs[3] = {xa, xa, xa};
    uint32_t own0 = 0;
    __nv_bfloat16 own2 = __float2bfloat16(0.f);
    if (warp < 8) {
        xa = *(const uint4*)(p.x + (tid & 3) * D + (tid >> 2) * 8);
        ca0 = ((const uint4*)p.c)[tid];
        if (tid < 64) { xb = *(const uint4*)(p.x + (tid & 3) * D + (64 + (tid >> 2)) * 8); ca1 = ((const uint4*)p.c)[256 + tid]; }
        if (warp < 4) {
#pragma unroll
            for (int i = 0; i < 3; i++) if (lane + 32 * i < 80) xs[i] = ((const uint4*)p.x)[warp * 80 + lane + 32 * i];
        } else if (warp == 4) {
            if (is_owner) own0 = *(const uint32_t*)((lane < 16 ? p.x + (lane >> 2) * D : p.b2) + 8 * own + 2 * (lane & 3));
            if (is_f) own2 = p.b1[32 * f + lane];
        }
    }
    const int rot = (head & 1) * (NITEM / 4);
    const char* const kb = (const char*)(p.kc + ((size_t)(bown * NH + head) * SK + (SK - WIN)) * DH);
    const char* const vb = (const char*)(p.vc + ((size_t)(bown * NH + head) * SK + (SK - WIN)) * DH);
    const uint32_t bar_first = crit ? bar_wm : bar_wq;
    uint64_t pol = 0;
    if (threadIdx.x == 256) {
        mbar_init(bar_first, 1);
        mbar_init(bar_full, 1);
        asm volatile("fence.mbarrier_init.release.cluster;" ::: "memory");
        asm volatile("createpolicy.fractional.L2::evict_first.b64 %0, 1.0;" : "=l"(pol));
        const uint32_t dst = sb + (crit ? X_WM : X_WQ);
        const CUtensorMap* tm = crit ? &tm_wmod : &tm_wq;
        mbar_expect_tx(bar_first, D * 64);
        if (crit) {
#pragma unroll
            for (int r = 0; r < D; r += 160) tma2d(dst + r * 64, tm, 32 * mc, r, bar_first);
        }
        mbar_expect_tx(bar_full, TILE_BYTES);
        bulk_load(sb + OFF_RING, kb + (size_t)rot * TILE_BYTES, TILE_BYTES, bar_full, pol);
        if (!crit) {
            const uint32_t c0 = clock32();
            while (clock32() - c0 < WQ_DELAY) { }
#pragma unroll
            for (int r = 0; r < D; r += 160) tma2d(dst + r * 64, tm, 32 * cta, r, bar_first);
        }
    } else if (threadIdx.x == 0) {
#pragma unroll
        for (int s = 0; s < NS; s++) { if (s) mbar_init(bar_full + s * 8, 1); mbar_init(bar_empty + s * 8, 4); }
        mbar_init(crit ? bar_wq : bar_wm, 1);
        mbar_init(bar_xfree, 1);
#pragma unroll
        for (int i = 0; i < 5; i++) mbar_init(bar_wo + i * 8, 1);
        mbar_init(bar_w2, 1); mbar_init(bar_help, 1);
#pragma unroll
        for (int i = 0; i < 4; i++) { mbar_init(bar_v + i * 8, 1); mbar_init(bar_w1 + i * 8, 1); }
        asm volatile("fence.mbarrier_init.release.cluster;" ::: "memory");
    }
    __syncthreads();

    if (warp == 8) {
        if (lane == 0) {
#pragma unroll 1
            for (int t = 1; t <= NITEM; t++) {
                if (t == 1) mbar_wait(bar_full, 0);
                if (t == 2) {
                    mbar_wait(bar_first, 0);
                    if (crit) {
                        mbar_expect_tx(bar_wq, D * 64);
#pragma unroll 1
                        for (int r = 0; r < D; r += 160) tma2d(sb + X_WQ + r * 64, &tm_wq, 32 * cta, r, bar_wq);
                    }
                }
                if (t == 3) {
                    asm volatile("prefetch.tensormap [%0];" ::"l"(&tm_v) : "memory");
                    asm volatile("prefetch.tensormap [%0];" ::"l"(&tm_wo) : "memory");
                    asm volatile("prefetch.tensormap [%0];" ::"l"(&tm_w1) : "memory");
                    asm volatile("prefetch.tensormap [%0];" ::"l"(&tm_w2) : "memory");
                }
                if (t == NS && late) {
                    mbar_wait(bar_full + (NS - INFLIGHT) * 8, 0);
                    mbar_expect_tx(bar_wm, D * 64);
#pragma unroll 1
                    for (int r = 0; r < D; r += 160) tma2d(sb + X_WM + r * 64, &tm_wmod, 32 * mc, r, bar_wm);
                }
                if (t == NITEM) {
                    mbar_wait(bar_xfree, 0);
                    if (WO_GATE <= 2) { mbar_wait(bar_v + (2 - WO_GATE) * 16, 0); mbar_wait(bar_v + (2 - WO_GATE) * 16 + 8, 0); }
                    else mbar_wait(bar_full + ((NITEM - WO_GATE) & (NS - 1)) * 8, ((NITEM - WO_GATE) >> 3) & 1);
#pragma unroll 1
                    for (int i = 0; i < 5; i++) {
                        mbar_expect_tx(bar_wo + i * 8, DH * 64);
                        tma2d(sb + X_WO + i * (DH * 64), &tm_wo, bown * 160 + i * 32, head * DH, bar_wo + i * 8);
                    }
                    if (is_f) {
                        mbar_wait(bar_wo + WF_GATE * 8, 0);
                        { const uint32_t c0 = clock32(); while (clock32() - c0 < WF_DELAY) { } }
#pragma unroll 1
                        for (int i = 0; i < 4; i++) {
                            mbar_expect_tx(bar_w1 + i * 8, 160 * 64);
                            tma2d(sb + X_W1 + i * (160 * 64), &tm_w1, 32 * f, 160 * i, bar_w1 + i * 8);
                        }
#pragma unroll 1
                        for (int i = 0; i < 3; i++) mbar_wait(bar_empty + i * 8, ((NITEM >> 3) - 1) & 1);
                        { const uint32_t c0 = clock32(); while (clock32() - c0 < W2_DELAY) { } }
                        mbar_expect_tx(bar_w2, D * 64);
#pragma unroll 1
                        for (int i = 0; i < 10; i++) tma2d(sb + X_W2 + i * 4096, &tm_w2, 64 * i, 32 * f, bar_w2);
                    }
                    break;
                }
                const int s = t & (NS - 1);
                if (t >= NS) {
                    mbar_wait(bar_empty + s * 8, ((t >> 3) - 1) & 1);
                    while ((int)(gtime32() - t_start) < PACE_A + (t - NS) * PACE_TAU) { }
                } else if (t >= INFLIGHT) {
                    mbar_wait(bar_full + (t - INFLIGHT) * 8, 0);
                }
                if (t < NITEM - 2) {
                    const int pair = t == NITEM - 3 ? NITEM / 2 - 1 : t >> 1;
                    mbar_expect_tx(bar_full + s * 8, TILE_BYTES);
                    bulk_load(sb + OFF_RING + s * TILE_BYTES, ((t & 1) && t != NITEM - 3 ? vb : kb) + (size_t)((pair + rot) & (NITEM / 2 - 1)) * TILE_BYTES, TILE_BYTES, bar_full + s * 8, pol);
                } else {
                    const int row = (bown * NH + head) * SK + (SK - WIN) + ((t - NITEM / 2 + rot) & (NITEM / 2 - 1)) * TILE_KEYS;
#pragma unroll 1
                    for (int i = 0; i < 2; i++) {
                        const uint32_t bar = bar_v + (2 * (t - (NITEM - 2)) + i) * 8;
                        mbar_expect_tx(bar, TILE_BYTES / 2);
                        tma2d_hint(sb + OFF_RING + s * TILE_BYTES + i * (TILE_BYTES / 2), &tm_v, 64 * i, row, bar, pol);
                    }
                }
            }
        }
        return;
    }

    if (warp == 9) {
        int side = 0;
        if (lane == 0) {
            uint32_t best[2] = {~0u, ~0u};
#pragma unroll 1
            for (int i = 0; i < 2 * NPROBE && ((i & 1) || (int)(gtime32() - t_start) < PROBE_END); i++) {
                uint32_t t0 = clock32(), v, t1;
                asm volatile("atom.relaxed.gpu.global.exch.b32 %0, [%1], %2;" : "=r"(v) : "l"(slot(SL_SIDE, i & 1) + cta * 8), "r"(0u) : "memory");
                asm volatile("{\n.reg .pred p;\nsetp.ne.u32 p, %1, 0xffffffff;\nmov.u32 %0, 0;\n@p mov.u32 %0, %%clock;\n}" : "=r"(t1) : "r"(v) : "memory");
                if (i & 1) best[1] = min(best[1], t1 - t0); else best[0] = min(best[0], t1 - t0);
            }
            side = best[1] < best[0];
        }
        side = __shfl_sync(0xffffffffu, side, 0);
        HPROF(1);
        mbar_wait(bar_full + (NS - 1) * 8, 0);
        stg_zero4(slot(SL_O + (cta >> 4), lane >> 4) + (cta & 15) * 64 + (lane & 15) * 4);
        if (is_owner) {
#pragma unroll 1
            for (int i = lane; i < NH * 8; i += 32) stg_zero4(slot(SL_P1 + own, side) + i * 4);
#pragma unroll 1
            for (int i = lane; i < NF * 8; i += 32) stg_zero4(slot(SL_P2 + 2 * own + (i >> 8), side) + (i & 255) * 4);
            if (lane < 8) stg_zero4(slot(SL_X1 + own / 30, lane >> 2) + (own % 30) * 32 + (lane & 3) * 4);
        }
        __threadfence();
        __syncwarp();
        if (lane == 0) stg_relaxed(g_clr + cta, 1u + side);
        HPROF(0);
        HPROF(2);
        while ((int)(gtime32() - t_start) < CLR_CHECK) __nanosleep(1000);
        {
            int it = 0;
            uint4 v;
            while (v = ldg_relaxed(g_clr + lane * 4), !__all_sync(0xffffffffu, ready(v))) { __nanosleep(2000); if (++it > SPIN_LIMIT) __trap(); }
            const uint32_t w[4] = {v.x, v.y, v.z, v.w};
#pragma unroll
            for (int i = 0; i < 4; i++) {
                const Roles r = roles(4 * lane + i);
                if (r.is_owner) {
                    sts32(sb + OFF_TAB1 + r.own * 4, (uint32_t)(size_t)(slot(SL_P1 + r.own, w[i] - 1) + head * 32));
                    sts32(sb + OFF_TAB2 + r.own * 4, (uint32_t)(size_t)(slot(SL_P2 + 2 * r.own + (f >> 5), w[i] - 1) + (f & 31) * 32));
                }
            }
            if (lane == 0) sts32(sb + OFF_SIDE, side);
        }
        mbar_wait(bar_xfree, 0);
        if (is_owner) {
            const uint4 v = poll1(mod_slot(lane < 4 ? 2 : 5, own, lane & 3), lane < 8);
            if (lane < 8) sts128(sb + OWN_GA + lane * 16, v);
        }
        if (is_f) {
#pragma unroll 1
            for (int i = 0; i < 5; i++) {
                uint4 v[4];
                const int j = 16 * i + (lane >> 2);
                const uint32_t* const ptr[4] = {mod_slot(4, j, lane & 3), mod_slot(4, j + 8, lane & 3), mod_slot(3, j, lane & 3), mod_slot(3, j + 8, lane & 3)};
                const bool on[4] = {true, true, true, true};
                poll_n<4>(v, ptr, on);
                const uint32_t dst = sb + OFF_VA + (lane & 3) * VEC_STRIDE + j * 16;
#pragma unroll
                for (int k = 0; k < 2; k++) {
                    sts128(dst + k * 128, make_uint4(bf2_add(v[k].x, 0x3f803f80u), bf2_add(v[k].y, 0x3f803f80u), bf2_add(v[k].z, 0x3f803f80u), bf2_add(v[k].w, 0x3f803f80u)));
                    sts128(dst + (OFF_VB - OFF_VA) + k * 128, v[2 + k]);
                }
            }
        }
        __threadfence();
        __syncwarp();
        HPROF(3);
        if (lane == 0) mbar_arrive(bar_help);
        {
            const uint32_t* const src = pin(slot(SL_O + (cta >> 4), side) + (cta & 12) * 64 + lane * 4);
            const uint32_t dst = pin(sb + OFF_O + (lane >> 4) * O_STRIDE + (lane & 15) * 16);
            mbar_wait(bar_v + 16, 0);
            mbar_wait(bar_v + 24, 0);
            uint4 v[2];
            const uint32_t* const ptr[2] = {src, src + 128};
            const bool on[2] = {true, true};
            poll_n<2>(v, ptr, on);
            sts128(dst, v[0]);
            sts128(dst + 2 * O_STRIDE, v[1]);
#pragma unroll
            for (int w = 0; w < 8; w++) asm volatile("bar.arrive %0, 64;" ::"r"(NB_O + w) : "memory");
        }
        HPROF(4);
        return;
    }

    const int g = lane >> 2, t4 = lane & 3;
    const int mi = lane >> 3, r8 = lane & 7;

    {
        auto silu4 = [&](const uint4& cv) {
            uint32_t w4[4] = {cv.x, cv.y, cv.z, cv.w};
#pragma unroll
            for (int e = 0; e < 4; e++) {
                float c0 = bf_lo(w4[e]), c1 = bf_hi(w4[e]);
                w4[e] = pack_bf(c0 * rcp_fast(1.f + ex2(-1.4426950408889634f * c0)), c1 * rcp_fast(1.f + ex2(-1.4426950408889634f * c1)));
            }
            return make_uint4(w4[0], w4[1], w4[2], w4[3]);
        };
        if (crit || late) {
            uint4 v = silu4(ca0);
            sts128(sb + OFF_VA + (tid / 80) * VEC_STRIDE + (tid % 80) * 16, v);
            if (tid < 64) { v = silu4(ca1); sts128(sb + OFF_VA + 3 * VEC_STRIDE + (16 + tid) * 16, v); }
        }
        if (warp < 4) {
            float s = 0.f, q = 0.f;
            const float pv = __shfl_sync(0xffffffffu, bf_lo(xs[0].x), 0);
#pragma unroll
            for (int i = 0; i < 3; i++) if (i < 2 || lane < 16) acc_stats(xs[i], pv, s, q);
#pragma unroll
            for (int of = 16; of > 0; of >>= 1) { s += __shfl_xor_sync(0xffffffffu, s, of); q += __shfl_xor_sync(0xffffffffu, q, of); }
            uint32_t m2; float rden;
            ln_finish(pv, s, q, m2, rden);
            if (lane == 0) { sts32(sb + OFF_STAT + warp * 8, m2); sts_f32(sb + OFF_STAT + warp * 8 + 4, rden); }
        } else if (warp == 4) {
            sts32(sb + OWN_X + lane * 4, bf2_add(own0, 0u));
            sts_f32(sb + OWN_B1 + lane * 4, bf2f(own2));
        }
    }
    bar_cons();
    PROF(24);
    uint32_t qf[8][2];
    float o[8][4];
#pragma unroll
    for (int c = 0; c < 8; c++) { o[c][0] = o[c][1] = o[c][2] = o[c][3] = 0.f; }
    float m_run = -INFINITY, l_run = 0.f;
    const bool diag = (t4 == (g >> 1));
    const bool odd = g & 1;
    const uint32_t koff = (warp & 3) * 4096 + (r8 + 8 * (mi & 1)) * 256 + (mi >> 1) * 128 + (r8 << 4);
    const uint32_t voff = TILE_BYTES + (warp & 3) * 4096 + (r8 + 8 * (mi >> 1)) * 256 + (mi & 1) * 128 + (r8 << 4);
    const int src0 = (2 * t4) * 4 + t4, src1 = (2 * t4 + 1) * 4 + t4;
#pragma unroll 1
    for (int step = crit ? 0 : 1; step < 3; step++) {
        if (step < 2 || late) {
            if (step == 1) {
                if (!crit) mbar_wait(bar_wq, 0);
                const uint32_t m2 = lds32(sb + OFF_STAT + (tid & 3) * 8);
                const float rden = lds_f32(sb + OFF_STAT + (tid & 3) * 8 + 4);
                uint4 v[4] = {xa, xa, xa, xa};
                const uint32_t* const ptr[4] = {mod_slot(0, tid >> 2, tid & 3), mod_slot(1, tid >> 2, tid & 3),
                                                mod_slot(0, 64 + ((tid & 63) >> 2), tid & 3), mod_slot(1, 64 + ((tid & 63) >> 2), tid & 3)};
                const bool on[4] = {true, true, tid < 64, tid < 64};
                poll_n<4>(v, ptr, on);
                uint4 h0 = ln_mod4(xa, v[1], v[0], m2, rden);
                sts128(sb + OFF_VB + (tid & 3) * VEC_STRIDE + (tid >> 2) * 16, h0);
                if (tid < 64) {
                    h0 = ln_mod4(xb, v[3], v[2], m2, rden);
                    sts128(sb + OFF_VB + (tid & 3) * VEC_STRIDE + (64 + (tid >> 2)) * 16, h0);
                }
            }
            mbar_wait(step == 1 ? bar_wq : bar_wm, 0);
            bar_cons();
            const uint32_t strip = sb + (step == 1 ? X_WQ : X_WM), vec = sb + (step == 1 ? OFF_VB : OFF_VA);
            float acc[2][4];
#pragma unroll
            for (int m = 0; m < 2; m++) { acc[m][0] = acc[m][1] = acc[m][2] = acc[m][3] = 0.f; }
#pragma unroll
            for (int i = 0; i < 5; i++) {
                int k0 = (warp * 5 + i) * 16;
                uint32_t b0, b1;
                load_bfrag(vec, VEC_STRIDE, k0, g, t4, b0, b1);
                int krow = k0 + r8 + 8 * (mi >> 1);
#pragma unroll
                for (int m = 0; m < 2; m++) {
                    uint32_t a[4];
                    int ch = 2 * m + (mi & 1);
                    ldsm4t(a, strip + krow * 64 + ((ch ^ ((krow >> 1) & 3)) << 4));
                    mma16816(acc[m], a, b0, b1);
                }
            }
            if (t4 < 2) {
#pragma unroll
                for (int m = 0; m < 2; m++) {
                    sts_f32x2(sb + OFF_RED + ((warp * 32 + m * 16 + g) * 4 + 2 * t4) * 4, acc[m][0], acc[m][1]);
                    sts_f32x2(sb + OFF_RED + ((warp * 32 + m * 16 + g + 8) * 4 + 2 * t4) * 4, acc[m][2], acc[m][3]);
                }
            }
            bar_cons();
            if (tid < 128) {
                float v = 0.f;
#pragma unroll
                for (int w = 0; w < 8; w++) v += lds_f32(sb + OFF_RED + (w * 128 + tid) * 4);
                float vn = __shfl_down_sync(0xffffffffu, v, 4);
                uint32_t* dst = step == 1 ? g_q + ((cta & ~3) + (tid & 3)) * 64 + bown * 16 + (tid >> 3) : g_mod + mc * 64 + (tid & 3) * 16 + (tid >> 3);
                if (!((tid >> 2) & 1)) stg_relaxed(dst, ~pack_bf(v, vn));
            }
        }
        if (step == 0) continue;
        if (step == 1) {
            if (warp == 0) {
                uint4 v = poll1(g_q + cta * 64 + (lane & 15) * 4, lane < 16);
                if (lane < 16) {
                    sts128(sb + OFF_Q + lane * 16, v);
                    stg_zero4(g_q + cta * 64 + lane * 4);
                }
            }
            bar_cons();
            PROF(4);

#pragma unroll
            for (int c = 0; c < 8; c++) {
                qf[c][0] = lds32(sb + OFF_Q + (((c ^ g) * 4 + t4) << 2));
                qf[c][1] = lds32(sb + OFF_Q + 128 + (((c ^ g) * 4 + t4) << 2));
            }
        } else {
            bar_cons();
            if (tid == 0) mbar_arrive(bar_xfree);
        }
#pragma unroll 1
        for (int j = (step == 1 ? 0 : SEG_J) + (warp >> 2); j < (step == 1 ? SEG_J : NITEM / 2 - 2); j += 2) {
            const int s = (2 * j) & (NS - 1);
            const uint32_t par = (j >> 2) & 1;
            mbar_wait(bar_full + s * 8, par);
            const uint32_t base = sb + OFF_RING + s * TILE_BYTES;
            float sa[4] = {0.f, 0.f, 0.f, 0.f}, sb2[4] = {0.f, 0.f, 0.f, 0.f};
#pragma unroll
            for (int c = 0; c < 8; c += 2) {
                uint32_t a[4], a2[4];
                ldsm4(a, (base + koff) ^ (c << 4));
                ldsm4(a2, (base + koff) ^ ((c + 1) << 4));
                mma16816(sa, a, qf[c][0], qf[c][1]);
                mma16816(sb2, a2, qf[c + 1][0], qf[c + 1][1]);
            }
            const uint32_t sw = pack_bf(odd ? sa[1] + sb2[1] : sa[0] + sb2[0], odd ? sa[3] + sb2[3] : sa[2] + sb2[2]);
            const uint32_t sv = pack_bf(bf_lo(sw) * 0.08838834764831845f, bf_hi(sw) * 0.08838834764831845f);
            const float s0 = bf_lo(sv) * 1.4426950408889634f, s1 = bf_hi(sv) * 1.4426950408889634f;
            float m_new = fmaxf(m_run, fmaxf(s0, s1));
            const bool grow = __any_sync(0xffffffffu, (diag && (m_new > m_run)));
            if (lane == 0) mbar_arrive(bar_empty + s * 8);
            if (grow) {
                float al = ex2(m_run - m_new);
                float a0 = __shfl_sync(0xffffffffu, al, src0), a1 = __shfl_sync(0xffffffffu, al, src1);
#pragma unroll
                for (int c = 0; c < 8; c++) { o[c][0] *= a0; o[c][1] *= a1; o[c][2] *= a0; o[c][3] *= a1; }
                l_run *= al;
                m_run = m_new;
            }
            uint32_t pw = pack_bf(ex2(s0 - m_run), ex2(s1 - m_run));
            l_run += bf_lo(pw) + bf_hi(pw);
            uint32_t b0 = odd ? (pw << 16) : (pw & 0xffffu);
            uint32_t b1 = odd ? (pw & 0xffff0000u) : (pw >> 16);
            if (!diag) { b0 = 0u; b1 = 0u; }
            mbar_wait(bar_full + (s + 1) * 8, par);
#pragma unroll
            for (int c = 0; c < 8; c++) {
                uint32_t a[4];
                ldsm4t(a, (base + voff) ^ (c << 4));
                mma16816(o[c], a, b0, b1);
            }
            __syncwarp();
            if (lane == 0) mbar_arrive(bar_empty + (s + 1) * 8);
        }
    }
    PROF(5);
    float acc[4][4];
    uint32_t pa[8][2];
    float rinv;
    {
        const int s = 4 + (warp >> 2);
        mbar_wait(bar_full + s * 8, 1);
        const uint32_t base = sb + OFF_RING + s * TILE_BYTES;
        float sa[4] = {0.f, 0.f, 0.f, 0.f}, sb2[4] = {0.f, 0.f, 0.f, 0.f};
#pragma unroll
        for (int c = 0; c < 8; c += 2) {
            uint32_t a[4], a2[4];
            ldsm4(a, (base + koff) ^ (c << 4));
            ldsm4(a2, (base + koff) ^ ((c + 1) << 4));
            mma16816(sa, a, qf[c][0], qf[c][1]);
            mma16816(sb2, a2, qf[c + 1][0], qf[c + 1][1]);
        }
        const uint32_t sw = pack_bf(odd ? sa[1] + sb2[1] : sa[0] + sb2[0], odd ? sa[3] + sb2[3] : sa[2] + sb2[2]);
        const uint32_t sv = pack_bf(bf_lo(sw) * 0.08838834764831845f, bf_hi(sw) * 0.08838834764831845f);
        const float s0 = bf_lo(sv) * 1.4426950408889634f, s1 = bf_hi(sv) * 1.4426950408889634f;
        int mi_ = __float_as_int(diag ? fmaxf(m_run, fmaxf(s0, s1)) : -INFINITY);
        mi_ ^= (mi_ >> 31) & 0x7fffffff;
        mi_ = __reduce_max_sync(0xffffffffu, mi_);
        mi_ ^= (mi_ >> 31) & 0x7fffffff;
        if (lane == 0) sts32(sb + OFF_ML + warp * 4, mi_);
        bar_cons();
        const float4 m0 = lds_f32x4(sb + OFF_ML), m1 = lds_f32x4(sb + OFF_ML + 16);
        const float mx = fmaxf(fmaxf(fmaxf(m0.x, m0.y), fmaxf(m0.z, m0.w)), fmaxf(fmaxf(m1.x, m1.y), fmaxf(m1.z, m1.w)));
        const float scl = ex2(m_run - mx);
        const uint32_t pw = pack_bf(ex2(s0 - mx), ex2(s1 - mx));
        if (diag) { sts16(sb + SC_P + (warp * 16 + g) * 2, pw); sts16(sb + SC_P + (warp * 16 + g + 8) * 2, pw >> 16); }
        const float lw = warp_sum(diag ? fmaf(l_run, scl, bf_lo(pw) + bf_hi(pw)) : 0.f);
        const float a0 = __shfl_sync(0xffffffffu, scl, src0), a1 = __shfl_sync(0xffffffffu, scl, src1);
        float v[8], u[8];
#pragma unroll
        for (int c = 0; c < 8; c++) {
            v[c] = a0 * o[c][0] + a1 * o[c ^ 1][1];
            u[c] = a0 * o[c][2] + a1 * o[c ^ 1][3];
        }
#pragma unroll
        for (int c = 0; c < 8; c++) {
            if (!(c & 2)) {
                v[c] += __shfl_xor_sync(0xffffffffu, v[c ^ 2], 1);
                u[c] += __shfl_xor_sync(0xffffffffu, u[c ^ 2], 1);
            }
        }
#pragma unroll
        for (int c = 0; c < 2; c++) {
            v[c] += __shfl_xor_sync(0xffffffffu, v[c ^ 4], 2);
            u[c] += __shfl_xor_sync(0xffffffffu, u[c ^ 4], 2);
        }
        const uint32_t dst = sb + SC_OP + (warp * 128 + 16 * t4 + g) * 4;
        sts_f32(dst, v[0]); sts_f32(dst + 32, v[1]); sts_f32(dst + 256, u[0]); sts_f32(dst + 288, u[1]);
        if (lane == 0) sts_f32(sb + OFF_ML + 32 + warp * 4, lw);
        mbar_wait(bar_help, 0);
        bar_cons();
        const float4 l0 = lds_f32x4(sb + OFF_ML + 32), l1 = lds_f32x4(sb + OFF_ML + 48);
        rinv = rcp_fast(((l0.x + l0.y) + (l0.z + l0.w)) + ((l1.x + l1.y) + (l1.z + l1.w)));
#pragma unroll
        for (int i = 0; i < 4; i++) acc[i][0] = acc[i][1] = acc[i][2] = acc[i][3] = 0.f;
#pragma unroll
        for (int w = 0; w < 8; w++) {
            const float2 x0 = lds_f32x2(sb + SC_OP + (w * 128 + 16 * warp + 2 * t4) * 4), x1 = lds_f32x2(sb + SC_OP + (w * 128 + 16 * warp + 8 + 2 * t4) * 4);
            acc[2 * (w & 1)][0] += x0.x; acc[2 * (w & 1)][1] += x0.y;
            acc[2 * (w & 1) + 1][0] += x1.x; acc[2 * (w & 1) + 1][1] += x1.y;
        }
#pragma unroll
        for (int ks = 0; ks < 8; ks++) { pa[ks][0] = lds32(sb + SC_P + (8 * ks + t4) * 4); pa[ks][1] = lds32(sb + SC_P + (8 * ks + 4 + t4) * 4); }
    }
    PROF(20);
    const int mt = warp < 2 ? warp : warp + 2;
    {
        const uint32_t va = pin(sb + OFF_RING + 6 * TILE_BYTES + (warp >> 2) * (TILE_BYTES / 2) + (8 * (mi & 1) + r8) * 128 + (((2 * (warp & 3) + (mi >> 1)) ^ r8) << 4));
        const uint32_t vbar = pin(bar_v + (warp >> 2) * 8);
        uint32_t* const o_dst = pin(slot(SL_O + (cta >> 4), g) + (cta & 15) * 64 + warp * 8 + 2 * t4);
#pragma unroll
        for (int tl = 0; tl < 2; tl++) {
            mbar_wait(vbar + tl * 16, 0);
            uint32_t r[4][4];
#pragma unroll
            for (int ks = 0; ks < 4; ks++) ldsm4t(r[ks], va + tl * TILE_BYTES + ks * 2048);
#pragma unroll
            for (int ks = 0; ks < 4; ks++) {
                const uint32_t a[4] = {pa[4 * tl + ks][0], 0u, pa[4 * tl + ks][1], 0u};
                mma16816(acc[2 * (ks & 1)], a, r[ks][0], r[ks][1]);
                mma16816(acc[2 * (ks & 1) + 1], a, r[ks][2], r[ks][3]);
            }
        }
        stg_relaxed2_if(g < 2, o_dst, ~pack_bf((acc[0][0] + acc[2][0]) * rinv, (acc[0][1] + acc[2][1]) * rinv),
                        ~pack_bf((acc[1][0] + acc[3][0]) * rinv, (acc[1][1] + acc[3][1]) * rinv));
    }
    PROF(7);
    const int side = lds32(sb + OFF_SIDE);
    const uint32_t red_st = pin(sb + SC_E4 + ((warp * 4 + 2 * ((lane >> 3) & 1) + (lane >> 4)) * 8 + (lane & 7)) * 4);
    const uint32_t red_ld = pin(sb + SC_E4 + (lane & 15) * 8);
    const uint32_t* const in1 = pin(slot(SL_P1 + own, side) + tid * 4);
    const uint32_t* const in2a = pin(slot(SL_P2 + 2 * own, side) + tid * 4);
    const uint32_t* const in2b = pin(slot(SL_P2 + 2 * own + 1, side) + tid * 4);
    uint32_t* const x1_dst = pin(slot(SL_X1 + own / 30, lane >> 4) + (own % 30) * 32 + (lane & 15));
    const uint32_t xw = lds32(sb + OWN_X + (lane & 15) * 4), ga_w = lds32(sb + OWN_GA + (lane & 15) * 4);
    uint32_t cs[15];
    uint32_t* dst2[10];
    uint32_t w2a[5];
#pragma unroll
    for (int j = 0; j < 10; j++) cs[j] = lds32(sb + OFF_VA + g * VEC_STRIDE + warp * 160 + t4 * 4 + j * 16);
#pragma unroll
    for (int i = 0; i < 5; i++) {
        cs[10 + i] = lds32(sb + OFF_VA + (g >> 1) * VEC_STRIDE + warp * 160 + (g & 1) * 16 + t4 * 4 + i * 32);
        const uint2 t = lds64(sb + OFF_TAB2 + warp * 40 + i * 8);
        dst2[2 * i] = slot_ptr(t.x + g * 16 + t4 * 8);
        dst2[2 * i + 1] = slot_ptr(t.y + g * 16 + t4 * 8);
        const int cc = 2 * (warp * 5 + i) + (mi & 1);
        w2a[i] = pin(sb + X_W2 + (cc >> 3) * 4096 + (r8 + 8 * (mi >> 1)) * 128 + (((cc & 7) ^ r8) << 4));
    }
    const uint32_t piv = lds32(sb + OFF_STAT + (g >> 1) * 8);
    const uint32_t* const xin = pin(slot(SL_X1 + warp / 3, side) + ((warp % 3) * 10 + (g & 1)) * 32 + (g >> 1) * 4 + t4);
    const uint32_t w1a = pin(sb + X_W1 + (warp * 80 + r8 + 8 * (mi >> 1)) * 64 + (((mi & 1) ^ ((r8 >> 1) & 3)) << 4));
    const uint32_t w1bar = pin(bar_w1 + (warp >> 1) * 8);
    const uint32_t ab_st = pin(sb + SC_AB + warp * 1024 + lane * 8), ab_ld = pin(sb + SC_AB + (tid >> 2) * 32 + (tid & 3) * 4);
    const uint32_t y_st = pin(sb + SC_Y + (warp * 128 + lane) * 4), y_ld = pin(sb + SC_Y + tid * 4);
    const uint32_t s_st = pin(sb + SC_ST + (t4 * 8 + warp) * 8), s_ld = pin(sb + SC_ST + (tid & 3) * 64);
    const uint32_t h_st = pin(sb + SC_H1 + (tid & 3) * 64 + ((tid >> 3) & 3) * 16 + ((tid >> 5) & 3) * 4 + ((tid >> 2) & 1) * 2);
    const uint32_t h_ld = pin(sb + SC_H1 + ((g & 3) ^ (2 * (f & 1) + ((f >> 1) & 1))) * 64 + t4 * 16);
    float ab_a = 0.f, ab_b = lds_f32(sb + OWN_B1 + ((tid >> 2) & 31) * 4);
    {
        const int kap = 2 * (head & 1) + ((head >> 1) & 1);
        const uint32_t wa = pin(sb + X_WO + (mt >> 1) * (DH * 64) + (r8 + 8 * (mi >> 1)) * 64 + ((((mt & 1) * 2 + (mi & 1)) ^ ((r8 >> 1) & 3)) << 4));
        const uint32_t oa = pin(sb + OFF_O + ((g & 3) ^ kap) * O_STRIDE + t4 * 8);
        uint32_t* dst[4];
#pragma unroll
        for (int i = 0; i < 2; i++) {
            const uint2 t = lds64(sb + OFF_TAB1 + (bown * 20 + 2 * mt + (warp < 2 ? 4 * i : 0)) * 4);
            dst[2 * i] = slot_ptr(t.x + g * 16 + t4 * 8);
            dst[2 * i + 1] = slot_ptr(t.y + g * 16 + t4 * 8);
        }
        const uint32_t obar = pin(NB_O + warp);
        PROF(6);
        uint32_t wf[8][4], wg[8][4];
        mbar_wait(bar_wo + (mt >> 1) * 8, 0);
#pragma unroll
        for (int ks = 0; ks < 8; ks++) ldsm4t(wf[ks], wa + ks * 1024);
        if (warp < 2) {
            mbar_wait(bar_wo + 8, 0);
#pragma unroll
            for (int ks = 0; ks < 8; ks++) ldsm4t(wg[ks], wa + DH * 64 + ks * 1024);
        }
        asm volatile("bar.sync %0, 64;" ::"r"(obar) : "memory");
        PROF(8);
        uint2 ob[8];
#pragma unroll
        for (int ks = 0; ks < 8; ks++) ob[ks] = lds64(oa + ks * 32);
        float c0[4] = {0.f, 0.f, 0.f, 0.f}, c1[4] = {0.f, 0.f, 0.f, 0.f};
        if (warp < 2) {
            float c2[4] = {0.f, 0.f, 0.f, 0.f}, c3[4] = {0.f, 0.f, 0.f, 0.f};
#pragma unroll
            for (int ks = 0; ks < 8; ks += 2) {
                mma16816(c0, wf[ks], ob[ks].x, ob[ks].y);
                mma16816(c2, wg[ks], ob[ks].x, ob[ks].y);
                mma16816(c1, wf[ks + 1], ob[ks + 1].x, ob[ks + 1].y);
                mma16816(c3, wg[ks + 1], ob[ks + 1].x, ob[ks + 1].y);
            }
            stg_relaxed2_if(t4 < 2, dst[2], flag(c2[0] + c3[0]), flag(c2[1] + c3[1]));
            stg_relaxed2_if(t4 < 2, dst[3], flag(c2[2] + c3[2]), flag(c2[3] + c3[3]));
        } else {
#pragma unroll
            for (int ks = 0; ks < 8; ks += 2) {
                mma16816(c0, wf[ks], ob[ks].x, ob[ks].y);
                mma16816(c1, wf[ks + 1], ob[ks + 1].x, ob[ks + 1].y);
            }
        }
        stg_relaxed2_if(t4 < 2, dst[0], flag(c0[0] + c1[0]), flag(c0[1] + c1[1]));
        stg_relaxed2_if(t4 < 2, dst[1], flag(c0[2] + c1[2]), flag(c0[3] + c1[3]));
    }
    PROF(9);
    uint32_t x1w = 0;
    if (is_owner) {
        uint4 v;
        for (int it = 0;; it++) {
            v = ldg_relaxed(in1);
            if (__all_sync(0xffffffffu, and3(and3(v.x, v.y, v.z), v.w, 1u))) break;
            if (it > SPIN_LIMIT) __trap();
        }
        PROF(11);
        const float s0 = __uint_as_float(v.x) + __shfl_xor_sync(0xffffffffu, __uint_as_float(v.z), 8);
        const float s1 = __uint_as_float(v.y) + __shfl_xor_sync(0xffffffffu, __uint_as_float(v.w), 8);
        sts_f32(red_st, s0 + __shfl_xor_sync(0xffffffffu, s1, 16));
        if (warp == 0) {
            nbar_sync<NB_E4>();
            float2 a[8];
#pragma unroll
            for (int w = 0; w < 8; w++) a[w] = lds_f32x2(red_ld + w * 128);
            const uint32_t aw = pack_bf(((a[0].x + a[1].x) + (a[2].x + a[3].x)) + ((a[4].x + a[5].x) + (a[6].x + a[7].x)),
                                        ((a[0].y + a[1].y) + (a[2].y + a[3].y)) + ((a[4].y + a[5].y) + (a[6].y + a[7].y)));
            x1w = bf2_add(xw, bf2_mul(ga_w, aw));
            stg_relaxed(x1_dst, x1w ^ 0x80008000u);
        } else {
            nbar_arrive<NB_E4>();
        }
    }
    PROF(12);
    if (is_f) {
        uint32_t f1[5][2][4], f2[5][2][4];
        {
            mbar_wait(w1bar, 0);
#pragma unroll
            for (int i = 0; i < 5; i++) { ldsm4t(f1[i][0], w1a + i * 1024); ldsm4t(f1[i][1], (w1a ^ 32) + i * 1024); }
            float c[2][4];
#pragma unroll
            for (int m = 0; m < 2; m++) c[m][0] = c[m][1] = c[m][2] = c[m][3] = 0.f;
#pragma unroll
            for (int i = 0; i < 5; i++) { mma16816(c[0], f1[i][0], cs[2 * i], cs[2 * i + 1]); mma16816(c[1], f1[i][1], cs[2 * i], cs[2 * i + 1]); }
#pragma unroll
            for (int m = 0; m < 2; m++) { sts_f32x2(ab_st + m * 512, c[m][0], c[m][1]); sts_f32x2(ab_st + m * 512 + 256, c[m][2], c[m][3]); }
            if (warp < 4) {
                nbar_sync<NB_AB>();
#pragma unroll
                for (int w = 0; w < 8; w++) { ab_a += lds_f32(ab_ld + w * 1024); ab_b += lds_f32(ab_ld + w * 1024 + 16); }
            } else {
                nbar_arrive<NB_AB>();
            }
        }
        PROF(10);
#pragma unroll
        for (int i = 0; i < 5; i++) { cs[2 * i] = pin(odd ? 0u : cs[10 + i]); cs[2 * i + 1] = pin(odd ? cs[10 + i] : 0u); }
        uint32_t d[6];
        bool have_w2 = false;
#pragma unroll 1
        for (int it = 0;; it++) {
#pragma unroll
            for (int i = 0; i < 5; i++) d[i] = ldg_relaxed32(xin + i * 64);
            if (!have_w2 && __all_sync(0xffffffffu, mbar_test(bar_w2, 0))) {
                have_w2 = true;
#pragma unroll
                for (int i = 0; i < 5; i++) { ldsm4t(f2[i][0], w2a[i]); ldsm4t(f2[i][1], w2a[i] + 2048); }
            }
            if (__all_sync(0xffffffffu, __vimin3_u32(__vimin3_u32(d[0], d[1], d[2]), d[3], d[4]) != 0u)) break;
            if (it > SPIN_LIMIT) __trap();
        }
        PROF(13);
        {
            float y[2][4], st[4] = {0.f, 0.f, 0.f, 0.f};
#pragma unroll
            for (int m = 0; m < 2; m++) y[m][0] = y[m][1] = y[m][2] = y[m][3] = 0.f;
#pragma unroll
            for (int i = 0; i < 5; i++) d[i] = bf2_add(d[i], piv);
            d[5] = 0u;
#pragma unroll
            for (int i = 0; i < 5; i++) {
                if (i < 3) {
                    const uint32_t a[4] = {d[2 * i], 0x3f803f80u, d[2 * i + 1], 0x3f803f80u};
                    mma16816(st, a, d[2 * i], d[2 * i + 1]);
                }
                const uint32_t y0 = bf2_mul(d[i], cs[2 * i]), y1 = bf2_mul(d[i], cs[2 * i + 1]);
                mma16816(y[0], f1[i][0], y0, y1);
                mma16816(y[1], f1[i][1], y0, y1);
            }
            const float q = odd ? st[1] : st[0];
            const float q2 = q + __shfl_xor_sync(0xffffffffu, q, 4);
            if (diag && !odd) sts_f32x2(s_st, q2, st[2] + st[3]);
#pragma unroll
            for (int m = 0; m < 2; m++) { sts_f32(y_st + m * 256, y[m][0] + y[m][1]); sts_f32(y_st + m * 256 + 128, y[m][2] + y[m][3]); }
        }
        if (warp < 4) {
            nbar_sync<NB_Y>();
            PROF(14);
            float4 q[4];
            float yy[8];
#pragma unroll
            for (int i = 0; i < 4; i++) q[i] = lds_f32x4(s_ld + i * 16);
#pragma unroll
            for (int w = 0; w < 8; w++) yy[w] = lds_f32(y_ld + w * 512);
            const float dm = (((q[0].y + q[0].w) + (q[1].y + q[1].w)) + ((q[2].y + q[2].w) + (q[3].y + q[3].w))) * (1.f / D);
            const float sq = ((q[0].x + q[0].z) + (q[1].x + q[1].z)) + ((q[2].x + q[2].z) + (q[3].x + q[3].z));
            const float r = rsqrt_fast(fmaxf(fmaf(-dm, dm, sq * (1.f / D)), 0.f) + 1e-5f);
            const float ys = ((yy[0] + yy[1]) + (yy[2] + yy[3])) + ((yy[4] + yy[5]) + (yy[6] + yy[7]));
            const float u = fmaf(r, fmaf(dm, ab_a, -ys), ab_b);
            const float e = ex2(u * fmaf(u * u, -0.044715f * 2.302208198144325f, -2.302208198144325f));
            sts16(h_st, pack_bf(u * rcp_fast(1.f + e), 0.f));
        } else {
            nbar_arrive<NB_Y>();
        }
        if (!have_w2) {
            mbar_wait(bar_w2, 0);
#pragma unroll
            for (int i = 0; i < 5; i++) { ldsm4t(f2[i][0], w2a[i]); ldsm4t(f2[i][1], w2a[i] + 2048); }
        }
        nbar_sync<NB_H1>();
        PROF(15);
        {
            const uint4 hb = lds128(h_ld);
            float c[5][4];
#pragma unroll
            for (int i = 0; i < 7; i++) {
                if (i < 5) { c[i][0] = c[i][1] = c[i][2] = c[i][3] = 0.f; mma16816(c[i], f2[i][0], hb.x, hb.y); }
                if (i > 0 && i < 6) mma16816(c[i - 1], f2[i - 1][1], hb.z, hb.w);
                if (i > 1) {
                    stg_relaxed2_if(t4 < 2, dst2[2 * i - 4], flag(c[i - 2][0]), flag(c[i - 2][1]));
                    stg_relaxed2_if(t4 < 2, dst2[2 * i - 3], flag(c[i - 2][2]), flag(c[i - 2][3]));
                }
            }
        }
    }
    PROF(16);
    if (is_owner) {
        uint32_t* const dst = pin((uint32_t*)(p.out + ((lane >> 2) & 3) * D + 8 * own) + t4);
        const uint32_t b2w = lds32(sb + OWN_B2 + (lane & 15) * 4), gb_w = lds32(sb + OWN_GB + (lane & 15) * 4);
        const bool two = tid < NF * 8 - 256;
        uint4 v, w = make_uint4(1, 1, 1, 1);
        for (int it = 0;; it++) {
            ldg_relaxed_if(two, w, in2b);
            v = ldg_relaxed(in2a);
            if (__all_sync(0xffffffffu, and3(and3(v.x, v.y, v.z), and3(v.w, w.x, w.y), and3(w.z, w.w, 1u)))) break;
            if (it > SPIN_LIMIT) __trap();
        }
        PROF(17);
        const float s0 = (__uint_as_float(v.x) + __uint_as_float(w.x)) + __shfl_xor_sync(0xffffffffu, __uint_as_float(v.z) + __uint_as_float(w.z), 8);
        const float s1 = (__uint_as_float(v.y) + __uint_as_float(w.y)) + __shfl_xor_sync(0xffffffffu, __uint_as_float(v.w) + __uint_as_float(w.w), 8);
        sts_f32(red_st + (SC_E6 - SC_E4), s0 + __shfl_xor_sync(0xffffffffu, s1, 16));
        nbar_sync<NB_E6>();
        if (warp == 0) {
            float2 a[8];
#pragma unroll
            for (int i = 0; i < 8; i++) a[i] = lds_f32x2(red_ld + (SC_E6 - SC_E4) + i * 128);
            const uint32_t aw = pack_bf(((a[0].x + a[1].x) + (a[2].x + a[3].x)) + ((a[4].x + a[5].x) + (a[6].x + a[7].x)),
                                        ((a[0].y + a[1].y) + (a[2].y + a[3].y)) + ((a[4].y + a[5].y) + (a[6].y + a[7].y)));
            const uint32_t r = bf2_add(x1w, bf2_mul(gb_w, bf2_add(aw, b2w)));
            if (lane < 16) asm volatile("st.global.u32 [%0], %1;" ::"l"(dst), "r"(r) : "memory");
        }
        if (tid >= 32 && tid < 56) stg_zero4(mod_slot((tid - 32) >> 2, own, tid & 3));
    }
    if (tid == 96) stg_relaxed(g_clr + cta, 0u);
    PROF(18);
    PROF_DUMP;
}

typedef CUresult (*EncodeFn)(CUtensorMap*, CUtensorMapDataType, cuuint32_t, void*, const cuuint64_t*, const cuuint64_t*, const cuuint32_t*,
                             const cuuint32_t*, CUtensorMapInterleave, CUtensorMapSwizzle, CUtensorMapL2promotion, CUtensorMapFloatOOBfill);

static CUtensorMap make_map(EncodeFn enc, const void* ptr, int cols, int rows, int box_cols, int box_rows, CUtensorMapSwizzle sw) {
    CUtensorMap m;
    cuuint64_t dims[2] = {(cuuint64_t)cols, (cuuint64_t)rows};
    cuuint64_t strides[1] = {(cuuint64_t)cols * 2};
    cuuint32_t box[2] = {(cuuint32_t)box_cols, (cuuint32_t)box_rows};
    cuuint32_t es[2] = {1, 1};
    enc(&m, CU_TENSOR_MAP_DATA_TYPE_BFLOAT16, 2, const_cast<void*>(ptr), dims, strides, box, es, CU_TENSOR_MAP_INTERLEAVE_NONE, sw,
        CU_TENSOR_MAP_L2_PROMOTION_NONE, CU_TENSOR_MAP_FLOAT_OOB_FILL_NONE);
    return m;
}

}

extern "C" void kernel_launch(void* const* d_in, const int* in_sizes, int n_in, void* d_out, int out_size) {
    (void)in_sizes; (void)n_in; (void)out_size;
    static EncodeFn enc = nullptr;
    if (!enc) {
        void* fn = nullptr;
        cudaDriverEntryPointQueryResult qr;
        cudaGetDriverEntryPoint("cuTensorMapEncodeTiled", &fn, cudaEnableDefault, &qr);
        enc = (EncodeFn)fn;
        cudaFuncSetAttribute(fused_kernel, cudaFuncAttributeMaxDynamicSharedMemorySize, SMEM_BYTES);
    }
    Params p;
    p.x = (const __nv_bfloat16*)d_in[0];
    p.kc = (const __nv_bfloat16*)d_in[1];
    p.vc = (const __nv_bfloat16*)d_in[2];
    p.b1 = (const __nv_bfloat16*)d_in[7];
    p.b2 = (const __nv_bfloat16*)d_in[9];
    p.c = (const __nv_bfloat16*)d_in[10];
    p.out = (__nv_bfloat16*)d_out;
    CUtensorMap tm_wmod = make_map(enc, d_in[11], NMOD, D, 32, 160, CU_TENSOR_MAP_SWIZZLE_64B);
    CUtensorMap tm_wq = make_map(enc, d_in[3], NH * DH, D, 32, 160, CU_TENSOR_MAP_SWIZZLE_64B);
    CUtensorMap tm_wo = make_map(enc, d_in[4], D, NH * DH, 32, 128, CU_TENSOR_MAP_SWIZZLE_64B);
    CUtensorMap tm_w1 = make_map(enc, d_in[6], FF, D, 32, 160, CU_TENSOR_MAP_SWIZZLE_64B);
    CUtensorMap tm_w2 = make_map(enc, d_in[8], D, FF, 64, 32, CU_TENSOR_MAP_SWIZZLE_128B);
    CUtensorMap tm_v = make_map(enc, d_in[2], DH, NB * NH * SK, 64, TILE_KEYS, CU_TENSOR_MAP_SWIZZLE_128B);
    fused_kernel<<<NCTA, NTHREADS, SMEM_BYTES>>>(p, tm_wmod, tm_wq, tm_wo, tm_w1, tm_w2, tm_v);
}
```

```cpp
#include <cuda_runtime.h>
#include <cuda.h>
#include <cuda_bf16.h>
#include <stdint.h>

namespace {

constexpr int NB = 4, D = 640, NH = 32, DH = 128, SK = 8192, WIN = 2048, FF = 1728, NMOD = 6 * D;
constexpr int NCTA = 128;
constexpr int NOWN = 80;
constexpr int NF = 54;
constexpr int NTHREADS = 320;
constexpr int TILE_KEYS = 64;
constexpr int TILE_BYTES = TILE_KEYS * DH * 2;
constexpr int NITEM = 2 * WIN / TILE_KEYS;
constexpr int NS = 8;
constexpr int NMODC = 120;
constexpr int SPIN_LIMIT = 1 << 18;
#define INFLIGHT 3
#define PACE_A 8600
#define PACE_TAU 635
#define WQ_DELAY 800
#define WO_GATE 2
#define WF_GATE 2
#define WF_DELAY 0
#define W2_DELAY 0
#define WF_ALL 0
#define NPROBE 8
#define PROBE_END 10000
#define NREF 6
#define WO_S 0
#define W1_S 0
#define W2_S 0
#define CLR_CHECK 28000
constexpr int SEG_J = 8;

constexpr int OFF_RING = 0;
constexpr int OFF_X = OFF_RING + NS * TILE_BYTES;
constexpr int X_WM = OFF_X;
constexpr int X_WQ = OFF_X + D * 64;
constexpr int X_WO = OFF_X;
constexpr int X_W1 = X_WO + 5 * DH * 64;
constexpr int X_END = X_W1 + D * 64;
constexpr int X_W2 = OFF_RING;
static_assert(X_WQ + D * 64 <= X_END, "prologue weights must fit");
constexpr int VEC_STRIDE = 1296;
constexpr int OFF_VA = X_END;
constexpr int OFF_VB = OFF_VA + 4 * VEC_STRIDE;
constexpr int OFF_RED = OFF_VB + 4 * VEC_STRIDE;
constexpr int OFF_ML = OFF_RED + 4096;
constexpr int O_STRIDE = 288;
constexpr int OFF_O = OFF_ML + 64;
constexpr int OFF_Q = OFF_O + 4 * O_STRIDE;
constexpr int OFF_OWN = OFF_Q + 256;
constexpr int OWN_X = OFF_OWN, OWN_B2 = OWN_X + 64, OWN_GA = OWN_B2 + 64, OWN_GB = OWN_GA + 64, OWN_B1 = OWN_GB + 64;
constexpr int OFF_STAT = OWN_B1 + 128;
constexpr int OFF_TAB1 = OFF_STAT + 32;
constexpr int OFF_TAB2 = OFF_TAB1 + NOWN * 4;
constexpr int OFF_SIDE = OFF_TAB2 + NOWN * 4;
constexpr int OFF_BAR = OFF_SIDE + 8;
constexpr int NBAR = 2 * NS + 19;
constexpr int SMEM_BYTES = OFF_BAR + NBAR * 8;
constexpr int SC_OP = OFF_RING + 4 * TILE_BYTES;
constexpr int SC_AB = SC_OP + 4096;
constexpr int SC_Y = SC_AB + 8192;
constexpr int SC_ST = SC_Y + 4096;
constexpr int SC_E4 = SC_ST + 256;
constexpr int SC_E6 = SC_E4 + 1024;
constexpr int SC_P = SC_E6 + 1024;
constexpr int SC_H1 = SC_P + 256;
static_assert(SMEM_BYTES <= 232448, "smem");
static_assert(OFF_BAR % 8 == 0 && OFF_X % 1024 == 0 && X_WQ % 512 == 0 && X_W1 % 512 == 0 && OFF_VA % 16 == 0 && OFF_RED % 16 == 0 && OFF_ML % 16 == 0 && OFF_O % 16 == 0 && OFF_Q % 16 == 0, "align");
constexpr int NB_O = 2  , NB_E4 = 10, NB_E6 = 11, NB_AB = 12, NB_Y = 13, NB_H1 = 14;

__device__ uint32_t g_mod[NMODC * 64];
__device__ uint32_t g_q[NCTA * 64];
__device__ uint32_t g_clr[NCTA];
constexpr int SL_P1 = 0;
constexpr int SL_P2 = SL_P1 + NOWN;
constexpr int SL_O = SL_P2 + 2 * NOWN;
constexpr int SL_X1 = SL_O + 8;
constexpr int SL_SIDE = SL_X1 + 3;
static_assert(SL_SIDE < 256, "one 2 MB page");
__device__ uint32_t g_slots[2 * 256 * 2048];
__device__ __forceinline__ uint32_t* slot(int i, int side) {
    const size_t base = ((size_t)g_slots + 0x1fffff) & ~(size_t)0x1fffff;
    return (uint32_t*)base + i * 2048 + (((__popc(i & 0x59) ^ side) & 1) << 10);
}
#define PROF_DECL
#define HPROF(i) do { } while (0)
#define PROF(i) do { } while (0)
#define PROF_DUMP do { } while (0)

__device__ __forceinline__ uint32_t smem_u32(const void* p) { return (uint32_t)__cvta_generic_to_shared(p); }
__device__ __forceinline__ void mbar_init(uint32_t bar, uint32_t cnt) { asm volatile("mbarrier.init.shared::cta.b64 [%0], %1;" ::"r"(bar), "r"(cnt) : "memory"); }
__device__ __forceinline__ void mbar_expect_tx(uint32_t bar, uint32_t bytes) { asm volatile("mbarrier.arrive.expect_tx.shared::cta.b64 _, [%0], %1;" ::"r"(bar), "r"(bytes) : "memory"); }
__device__ __forceinline__ void mbar_arrive(uint32_t bar) { asm volatile("mbarrier.arrive.shared::cta.b64 _, [%0];" ::"r"(bar) : "memory"); }
__device__ __forceinline__ void mbar_wait(uint32_t bar, uint32_t parity) {
    uint32_t ok;
    int it = 0;
    while (true) {
        asm volatile("{\n.reg .pred p;\nmbarrier.try_wait.parity.shared::cta.b64 p, [%1], %2;\nselp.u32 %0, 1, 0, p;\n}" : "=r"(ok) : "r"(bar), "r"(parity) : "memory");
        if (ok) break;
        if (++it > SPIN_LIMIT) __trap();
    }
}
__device__ __forceinline__ void bulk_load(uint32_t dst, const void* src, uint32_t bytes, uint32_t bar, uint64_t pol) {
    asm volatile("cp.async.bulk.shared::cluster.global.mbarrier::complete_tx::bytes.L2::cache_hint [%0], [%1], %2, [%3], %4;"
                 ::"r"(dst), "l"(src), "r"(bytes), "r"(bar), "l"(pol) : "memory");
}
__device__ __forceinline__ void bar_cons() { asm volatile("bar.sync 1, 256;" ::: "memory"); }
template <int ID, int N> __device__ __forceinline__ void nbar_sync() { asm volatile("bar.sync %0, %1;" ::"n"(ID), "n"(N) : "memory"); }
template <int ID, int N> __device__ __forceinline__ void nbar_arrive() { asm volatile("bar.arrive %0, %1;" ::"n"(ID), "n"(N) : "memory"); }
__device__ __forceinline__ uint32_t pin(uint32_t v) { asm volatile("" : "+r"(v)); return v; }
template <class T> __device__ __forceinline__ T* pin(T* v) { asm volatile("" : "+l"(v)); return v; }
__device__ __forceinline__ void ldsm4(uint32_t (&a)[4], uint32_t addr) {
    asm volatile("ldmatrix.sync.aligned.m8n8.x4.shared.b16 {%0,%1,%2,%3}, [%4];" : "=r"(a[0]), "=r"(a[1]), "=r"(a[2]), "=r"(a[3]) : "r"(addr) : "memory");
}
__device__ __forceinline__ void ldsm4t(uint32_t (&a)[4], uint32_t addr) {
    asm volatile("ldmatrix.sync.aligned.m8n8.x4.trans.shared.b16 {%0,%1,%2,%3}, [%4];" : "=r"(a[0]), "=r"(a[1]), "=r"(a[2]), "=r"(a[3]) : "r"(addr) : "memory");
}
__device__ __forceinline__ void mma16816(float (&c)[4], const uint32_t (&a)[4], uint32_t b0, uint32_t b1) {
    asm volatile("mma.sync.aligned.m16n8k16.row.col.f32.bf16.bf16.f32 {%0,%1,%2,%3}, {%4,%5,%6,%7}, {%8,%9}, {%0,%1,%2,%3};"
                 : "+f"(c[0]), "+f"(c[1]), "+f"(c[2]), "+f"(c[3]) : "r"(a[0]), "r"(a[1]), "r"(a[2]), "r"(a[3]), "r"(b0), "r"(b1));
}
__device__ __forceinline__ uint32_t lds32(uint32_t addr) { uint32_t v; asm volatile("ld.shared.u32 %0, [%1];" : "=r"(v) : "r"(addr) : "memory"); return v; }
__device__ __forceinline__ float lds_f32(uint32_t addr) { float v; asm volatile("ld.shared.f32 %0, [%1];" : "=f"(v) : "r"(addr) : "memory"); return v; }
__device__ __forceinline__ float2 lds_f32x2(uint32_t addr) { float2 v; asm volatile("ld.shared.v2.f32 {%0,%1}, [%2];" : "=f"(v.x), "=f"(v.y) : "r"(addr) : "memory"); return v; }
__device__ __forceinline__ float4 lds_f32x4(uint32_t addr) { float4 v; asm volatile("ld.shared.v4.f32 {%0,%1,%2,%3}, [%4];" : "=f"(v.x), "=f"(v.y), "=f"(v.z), "=f"(v.w) : "r"(addr) : "memory"); return v; }
__device__ __forceinline__ uint2 lds64(uint32_t addr) { uint2 v; asm volatile("ld.shared.v2.u32 {%0,%1}, [%2];" : "=r"(v.x), "=r"(v.y) : "r"(addr) : "memory"); return v; }
__device__ __forceinline__ uint4 lds128(uint32_t addr) { uint4 v; asm volatile("ld.shared.v4.u32 {%0,%1,%2,%3}, [%4];" : "=r"(v.x), "=r"(v.y), "=r"(v.z), "=r"(v.w) : "r"(addr) : "memory"); return v; }
__device__ __forceinline__ void sts16(uint32_t addr, uint32_t v) { asm volatile("st.shared.b16 [%0], %1;" ::"r"(addr), "h"((unsigned short)v) : "memory"); }
__device__ __forceinline__ void sts32(uint32_t addr, uint32_t v) { asm volatile("st.shared.u32 [%0], %1;" ::"r"(addr), "r"(v) : "memory"); }
__device__ __forceinline__ void sts_f32(uint32_t addr, float v) { asm volatile("st.shared.f32 [%0], %1;" ::"r"(addr), "f"(v) : "memory"); }
__device__ __forceinline__ void sts_f32x2(uint32_t addr, float a, float b) { asm volatile("st.shared.v2.f32 [%0], {%1,%2};" ::"r"(addr), "f"(a), "f"(b) : "memory"); }
__device__ __forceinline__ void sts128(uint32_t addr, uint4 v) { asm volatile("st.shared.v4.u32 [%0], {%1,%2,%3,%4};" ::"r"(addr), "r"(v.x), "r"(v.y), "r"(v.z), "r"(v.w) : "memory"); }
__device__ __forceinline__ uint4 ldg_relaxed(const uint32_t* p) {
    uint4 v;
    asm volatile("ld.relaxed.gpu.global.v4.u32 {%0,%1,%2,%3}, [%4];" : "=r"(v.x), "=r"(v.y), "=r"(v.z), "=r"(v.w) : "l"(p) : "memory");
    return v;
}
__device__ __forceinline__ void ldg_relaxed_if(bool on, uint4& v, const uint32_t* p) {
    asm volatile("{\n.reg .pred q;\nsetp.ne.u32 q, %5, 0;\n@q ld.relaxed.gpu.global.v4.u32 {%0,%1,%2,%3}, [%4];\n}"
                 : "+r"(v.x), "+r"(v.y), "+r"(v.z), "+r"(v.w) : "l"(p), "r"((uint32_t)on) : "memory");
}
__device__ __forceinline__ void stg_relaxed2_if(bool on, uint32_t* p, uint32_t a, uint32_t b) {
    asm volatile("{\n.reg .pred q;\nsetp.ne.u32 q, %3, 0;\n@q st.relaxed.gpu.global.v2.u32 [%0], {%1,%2};\n}" ::"l"(p), "r"(a), "r"(b), "r"((uint32_t)on) : "memory");
}
__device__ __forceinline__ uint32_t ldg_relaxed32(const uint32_t* p) { uint32_t v; asm volatile("ld.relaxed.gpu.global.u32 %0, [%1];" : "=r"(v) : "l"(p) : "memory"); return v; }
__device__ __forceinline__ void stg_relaxed(uint32_t* p, uint32_t v) { asm volatile("st.relaxed.gpu.global.u32 [%0], %1;" ::"l"(p), "r"(v) : "memory"); }
__device__ __forceinline__ void stg_relaxed2(uint32_t* p, uint32_t a, uint32_t b) { asm volatile("st.relaxed.gpu.global.v2.u32 [%0], {%1,%2};" ::"l"(p), "r"(a), "r"(b) : "memory"); }
__device__ __forceinline__ void stg_zero4(uint32_t* p) { asm volatile("st.relaxed.gpu.global.v4.u32 [%0], {%1,%1,%1,%1};" ::"l"(p), "r"(0u) : "memory"); }
__device__ __forceinline__ bool ready(const uint4& v) { return (v.x != 0u) & (v.y != 0u) & (v.z != 0u) & (v.w != 0u); }
__device__ __forceinline__ uint4 inv4(const uint4& v) { return make_uint4(~v.x, ~v.y, ~v.z, ~v.w); }
__device__ __forceinline__ uint32_t pack_bf(float lo, float hi) {
    uint32_t r;
    asm("cvt.rn.bf16x2.f32 %0, %1, %2;" : "=r"(r) : "f"(hi), "f"(lo));
    return r;
}
__device__ __forceinline__ float bfr(float x) { return __uint_as_float(pack_bf(0.f, x) & 0xffff0000u); }
__device__ __forceinline__ float bf_lo(uint32_t w) { return __uint_as_float(w << 16); }
__device__ __forceinline__ float bf_hi(uint32_t w) { return __uint_as_float(w & 0xffff0000u); }
__device__ __forceinline__ float bf2f(__nv_bfloat16 v) { return __bfloat162float(v); }
__device__ __forceinline__ float ex2(float x) { float y; asm("ex2.approx.ftz.f32 %0, %1;" : "=f"(y) : "f"(x)); return y; }
__device__ __forceinline__ float rcp_fast(float x) { float y; asm("rcp.approx.ftz.f32 %0, %1;" : "=f"(y) : "f"(x)); return y; }
__device__ __forceinline__ float rsqrt_fast(float x) { float y; asm("rsqrt.approx.ftz.f32 %0, %1;" : "=f"(y) : "f"(x)); return y; }
__device__ __forceinline__ float sqrt_fast(float x) { float y; asm("sqrt.approx.f32 %0, %1;" : "=f"(y) : "f"(x)); return y; }
__device__ __forceinline__ uint32_t bf2_add(uint32_t a, uint32_t b) { uint32_t r; asm("add.rn.bf16x2 %0, %1, %2;" : "=r"(r) : "r"(a), "r"(b)); return r; }
__device__ __forceinline__ uint32_t bf2_sub(uint32_t a, uint32_t b) { uint32_t r; asm("sub.rn.bf16x2 %0, %1, %2;" : "=r"(r) : "r"(a), "r"(b)); return r; }
__device__ __forceinline__ uint32_t bf2_mul(uint32_t a, uint32_t b) { uint32_t r; asm("mul.rn.bf16x2 %0, %1, %2;" : "=r"(r) : "r"(a), "r"(b)); return r; }
__device__ __forceinline__ uint32_t gtime32() { uint32_t c; asm volatile("mov.u32 %0, %%globaltimer_lo;" : "=r"(c)); return c; }
__device__ __forceinline__ uint32_t clock32() { uint32_t c; asm volatile("mov.u32 %0, %%clock;" : "=r"(c)); return c; }

__device__ __forceinline__ float warp_sum(float v) {
#pragma unroll
    for (int o = 16; o > 0; o >>= 1) v += __shfl_xor_sync(0xffffffffu, v, o);
    return v;
}

struct Params {
    const __nv_bfloat16 *x, *kc, *vc, *b1, *b2, *c;
    __nv_bfloat16* out;
};

__device__ __forceinline__ void tma2d(uint32_t dst, const CUtensorMap* tm, int x, int y, uint32_t bar) {
    asm volatile("cp.async.bulk.tensor.2d.shared::cluster.global.mbarrier::complete_tx::bytes [%0], [%1, {%2, %3}], [%4];"
                 ::"r"(dst), "l"(tm), "r"(x), "r"(y), "r"(bar) : "memory");
}

__device__ __forceinline__ void tma2d_hint(uint32_t dst, const CUtensorMap* tm, int x, int y, uint32_t bar, uint64_t pol) {
    asm volatile("cp.async.bulk.tensor.2d.shared::cluster.global.mbarrier::complete_tx::bytes.L2::cache_hint [%0], [%1, {%2, %3}], [%4], %5;"
                 ::"r"(dst), "l"(tm), "r"(x), "r"(y), "r"(bar), "l"(pol) : "memory");
}
__device__ __forceinline__ uint32_t flag(float v) { return __float_as_uint(v) | 1u; }
__device__ __forceinline__ uint32_t and3(uint32_t a, uint32_t b, uint32_t c) { uint32_t r; asm("lop3.b32 %0, %1, %2, %3, 0x80;" : "=r"(r) : "r"(a), "r"(b), "r"(c)); return r; }
__device__ __forceinline__ uint32_t* slot_ptr(uint32_t lo) {
    uint32_t* r;
    asm volatile("mov.b64 %0, {%1, %2};" : "=l"(r) : "r"(lo), "r"((uint32_t)((size_t)slot(0, 0) >> 32)));
    return r;
}

__device__ __forceinline__ void load_bfrag(uint32_t vec, int stride, int k0, int g, int t, uint32_t& b0, uint32_t& b1) {
    uint32_t a = vec + (g & 3) * stride + (k0 + 2 * t) * 2;
    b0 = lds32(a);
    b1 = lds32(a + 16);
}

__device__ __forceinline__ void ln_finish(float pivot, float sum, float sumsq, uint32_t& m2, float& rden) {
    float dm = sum * (1.f / D);
    float var = fmaxf(sumsq * (1.f / D) - dm * dm, 0.f);
    float mean = pivot + dm;
    m2 = pack_bf(mean, mean);
    rden = rcp_fast(bfr(sqrt_fast(bfr(bfr(var) + 1e-5f))));
}
__device__ __forceinline__ uint32_t ln_mod_pair(uint32_t xw, uint32_t cw, uint32_t sw, uint32_t m2, float rden) {
    uint32_t d = bf2_sub(xw, m2);
    uint32_t ln = pack_bf(bf_lo(d) * rden, bf_hi(d) * rden);
    return bf2_add(bf2_mul(ln, bf2_add(cw, 0x3f803f80u)), sw);
}
__device__ __forceinline__ uint4 ln_mod4(const uint4& x, const uint4& c, const uint4& s, uint32_t m2, float rden) {
    return make_uint4(ln_mod_pair(x.x, c.x, s.x, m2, rden), ln_mod_pair(x.y, c.y, s.y, m2, rden),
                      ln_mod_pair(x.z, c.z, s.z, m2, rden), ln_mod_pair(x.w, c.w, s.w, m2, rden));
}
__device__ __forceinline__ void acc_stats(const uint4& v, float pv, float& s, float& q) {
    const float a0 = bf_lo(v.x) - pv, a1 = bf_hi(v.x) - pv, a2 = bf_lo(v.y) - pv, a3 = bf_hi(v.y) - pv;
    const float a4 = bf_lo(v.z) - pv, a5 = bf_hi(v.z) - pv, a6 = bf_lo(v.w) - pv, a7 = bf_hi(v.w) - pv;
    s += ((a0 + a1) + (a2 + a3)) + ((a4 + a5) + (a6 + a7));
    q += (fmaf(a0, a0, a1 * a1) + fmaf(a2, a2, a3 * a3)) + (fmaf(a4, a4, a5 * a5) + fmaf(a6, a6, a7 * a7));
}
__device__ __forceinline__ uint32_t* mod_slot(int kind, int j, int b) { return g_mod + (kind * 20 + (j >> 2)) * 64 + b * 16 + (j & 3) * 4; }

template <int N>
__device__ __forceinline__ void poll_n(uint4 (&v)[N], const uint32_t* const* ptr, const bool* on) {
    bool pend[N];
#pragma unroll
    for (int i = 0; i < N; i++) pend[i] = on[i];
    int it = 0;
    while (true) {
#pragma unroll
        for (int i = 0; i < N; i++) if (pend[i]) v[i] = ldg_relaxed(ptr[i]);
        bool any = false;
#pragma unroll
        for (int i = 0; i < N; i++) { pend[i] = pend[i] && !ready(v[i]); any |= pend[i]; }
        if (!__any_sync(0xffffffffu, any)) break;
        if (++it > SPIN_LIMIT) __trap();
    }
#pragma unroll
    for (int i = 0; i < N; i++) v[i] = inv4(v[i]);
}
__device__ __forceinline__ uint4 poll1(const uint32_t* p, bool on) {
    uint4 v[1] = {make_uint4(0, 0, 0, 0)};
    const uint32_t* const ptr[1] = {p};
    const bool o[1] = {on};
    poll_n<1>(v, ptr, o);
    return v[0];
}

__device__ __forceinline__ void gelu_stage(uint32_t sb, int m, int lane) {
    const int g = lane >> 2, b = lane & 3;
    const uint32_t y_ld = pin(sb + SC_Y + m * 256 + lane * 8), s_ld = pin(sb + SC_ST + b * 64);
    const uint32_t h_st = pin(sb + SC_H1 + b * 64 + (g >> 1) * 16 + m * 8 + (g & 1) * 2);
    float a0 = 0.f, b0 = lds_f32(sb + OWN_B1 + (16 * m + g) * 4), a1 = 0.f, b1 = lds_f32(sb + OWN_B1 + (16 * m + g + 8) * 4);
    nbar_sync<NB_AB, 320>();
#pragma unroll
    for (int w = 0; w < 8; w++) {
        const float4 t = lds_f32x4(sb + SC_AB + w * 1024 + m * 512 + lane * 16);
        a0 += t.x; b0 += t.y; a1 += t.z; b1 += t.w;
    }
    nbar_sync<NB_Y, 320>();
    float4 q[4];
    float2 y[8];
#pragma unroll
    for (int i = 0; i < 4; i++) q[i] = lds_f32x4(s_ld + i * 16);
#pragma unroll
    for (int w = 0; w < 8; w++) y[w] = lds_f32x2(y_ld + w * 512);
    const float dm = (((q[0].y + q[0].w) + (q[1].y + q[1].w)) + ((q[2].y + q[2].w) + (q[3].y + q[3].w))) * (1.f / D);
    const float sq = ((q[0].x + q[0].z) + (q[1].x + q[1].z)) + ((q[2].x + q[2].z) + (q[3].x + q[3].z));
    const float r = rsqrt_fast(fmaxf(fmaf(-dm, dm, sq * (1.f / D)), 0.f) + 1e-5f);
    const float y0 = ((y[0].x + y[1].x) + (y[2].x + y[3].x)) + ((y[4].x + y[5].x) + (y[6].x + y[7].x));
    const float y1 = ((y[0].y + y[1].y) + (y[2].y + y[3].y)) + ((y[4].y + y[5].y) + (y[6].y + y[7].y));
    const float u0 = fmaf(r, fmaf(dm, a0, -y0), b0), u1 = fmaf(r, fmaf(dm, a1, -y1), b1);
    const float e0 = ex2(u0 * fmaf(u0 * u0, -0.044715f * 2.302208198144325f, -2.302208198144325f));
    const float e1 = ex2(u1 * fmaf(u1 * u1, -0.044715f * 2.302208198144325f, -2.302208198144325f));
    sts16(h_st, pack_bf(u0 * rcp_fast(1.f + e0), 0.f));
    sts16(h_st + 4, pack_bf(u1 * rcp_fast(1.f + e1), 0.f));
    nbar_arrive<NB_H1, 320>();
}

struct Roles { bool is_f, is_owner; int f, own; };
__device__ __forceinline__ Roles roles(int cta) {
    Roles r;
    r.f = (cta * 27) >> 6;
    r.is_f = (((cta + 1) * 27) >> 6) != r.f;
    r.is_owner = !r.is_f || r.f % 9 == 4;
    r.own = r.is_f ? 74 + r.f / 9 : cta - r.f;
    return r;
}

__global__ void __launch_bounds__(NTHREADS, 1)
fused_kernel(const Params p, const __grid_constant__ CUtensorMap tm_wmod, const __grid_constant__ CUtensorMap tm_wq,
             const __grid_constant__ CUtensorMap tm_wo, const __grid_constant__ CUtensorMap tm_w1, const __grid_constant__ CUtensorMap tm_w2,
             const __grid_constant__ CUtensorMap tm_v) {
    extern __shared__ __align__(1024) unsigned char smem[];
    const uint32_t sb = smem_u32(smem);
    const int cta = blockIdx.x;
    const int head = cta >> 2, bown = cta & 3;
    const uint32_t bar_full = sb + OFF_BAR, bar_empty = bar_full + NS * 8;
    const uint32_t bar_wm = bar_empty + NS * 8, bar_wq = bar_wm + 8, bar_xfree = bar_wq + 8, bar_wo = bar_xfree + 8  ;
    const uint32_t bar_w1 = bar_wo + 40  , bar_w2 = bar_w1 + 32, bar_help = bar_w2 + 8, bar_v = bar_help + 8  , bar_ref = bar_v + 32;
    const int tid = threadIdx.x, warp = tid >> 5, lane = tid & 31;
    const Roles role = roles(cta);
    const bool is_f = role.is_f, is_owner = role.is_owner;
    const int f = role.f, own = role.own;
    const bool crit = (((cta + 1) * 5) >> 4) != ((cta * 5) >> 4);
    const int mr = cta - ((cta * 5) >> 4);
    const bool late = !crit && mr % 11 != 10;
    const int mc = crit ? (cta * 5) >> 4 : 40 + mr - mr / 11;

    const uint32_t t_start = gtime32();
    PROF_DECL
    PROF(0);
    uint4 xa = make_uint4(0, 0, 0, 0), xb = xa, ca0 = xa, ca1 = xa, xs[3] = {xa, xa, xa};
    uint32_t own0 = 0;
    __nv_bfloat16 own2 = __float2bfloat16(0.f);
    if (warp < 8) {
        xa = *(const uint4*)(p.x + (tid & 3) * D + (tid >> 2) * 8);
        ca0 = ((const uint4*)p.c)[tid];
        if (tid < 64) { xb = *(const uint4*)(p.x + (tid & 3) * D + (64 + (tid >> 2)) * 8); ca1 = ((const uint4*)p.c)[256 + tid]; }
        if (warp < 4) {
#pragma unroll
            for (int i = 0; i < 3; i++) if (lane + 32 * i < 80) xs[i] = ((const uint4*)p.x)[warp * 80 + lane + 32 * i];
        } else if (warp == 4) {
            if (is_owner) own0 = *(const uint32_t*)((lane < 16 ? p.x + (lane >> 2) * D : p.b2) + 8 * own + 2 * (lane & 3));
            if (is_f) own2 = p.b1[32 * f + lane];
        }
    }
    const int rot = (head & 1) * (NITEM / 4);
    const char* const kb = (const char*)(p.kc + ((size_t)(bown * NH + head) * SK + (SK - WIN)) * DH);
    const char* const vb = (const char*)(p.vc + ((size_t)(bown * NH + head) * SK + (SK - WIN)) * DH);
    const uint32_t bar_first = crit ? bar_wm : bar_wq;
    uint64_t pol = 0;
    if (threadIdx.x == 256) {
        mbar_init(bar_first, 1);
        mbar_init(bar_full, 1);
        asm volatile("fence.mbarrier_init.release.cluster;" ::: "memory");
        asm volatile("createpolicy.fractional.L2::evict_first.b64 %0, 1.0;" : "=l"(pol));
        const uint32_t dst = sb + (crit ? X_WM : X_WQ);
        const CUtensorMap* tm = crit ? &tm_wmod : &tm_wq;
        mbar_expect_tx(bar_first, D * 64);
        if (crit) {
#pragma unroll
            for (int r = 0; r < D; r += 160) tma2d(dst + r * 64, tm, 32 * mc, r, bar_first);
        }
        mbar_expect_tx(bar_full, TILE_BYTES);
        bulk_load(sb + OFF_RING, kb + (size_t)rot * TILE_BYTES, TILE_BYTES, bar_full, pol);
        if (!crit) {
            const uint32_t c0 = clock32();
            while (clock32() - c0 < WQ_DELAY) { }
#pragma unroll
            for (int r = 0; r < D; r += 160) tma2d(dst + r * 64, tm, 32 * cta, r, bar_first);
        }
    } else if (threadIdx.x == 0) {
#pragma unroll
        for (int s = 0; s < NS; s++) { if (s) mbar_init(bar_full + s * 8, 1); mbar_init(bar_empty + s * 8, 4); }
        mbar_init(crit ? bar_wq : bar_wm, 1);
        mbar_init(bar_xfree, 1);
#pragma unroll
        for (int i = 0; i < 5; i++) mbar_init(bar_wo + i * 8, 1);
        mbar_init(bar_w2, 1); mbar_init(bar_help, 1); mbar_init(bar_ref, 1);
#pragma unroll
        for (int i = 0; i < 4; i++) { mbar_init(bar_v + i * 8, 1); mbar_init(bar_w1 + i * 8, 1); }
        asm volatile("fence.mbarrier_init.release.cluster;" ::: "memory");
    }
    __syncthreads();

    if (warp == 8) {
        if (lane == 0) {
#pragma unroll 1
            for (int t = 1; t <= NITEM; t++) {
                if (t == 1) mbar_wait(bar_full, 0);
                if (t == 2) {
                    mbar_wait(bar_first, 0);
                    if (crit) {
                        mbar_expect_tx(bar_wq, D * 64);
#pragma unroll 1
                        for (int r = 0; r < D; r += 160) tma2d(sb + X_WQ + r * 64, &tm_wq, 32 * cta, r, bar_wq);
                    }
                }
                if (t == 3) {
                    asm volatile("prefetch.tensormap [%0];" ::"l"(&tm_v) : "memory");
                    asm volatile("prefetch.tensormap [%0];" ::"l"(&tm_wo) : "memory");
                    asm volatile("prefetch.tensormap [%0];" ::"l"(&tm_w1) : "memory");
                    asm volatile("prefetch.tensormap [%0];" ::"l"(&tm_w2) : "memory");
                }
                if (t == NS && late) {
                    mbar_wait(bar_full + (NS - INFLIGHT) * 8, 0);
                    mbar_expect_tx(bar_wm, D * 64);
#pragma unroll 1
                    for (int r = 0; r < D; r += 160) tma2d(sb + X_WM + r * 64, &tm_wmod, 32 * mc, r, bar_wm);
                }
                if (t == NITEM) {
                    mbar_wait(bar_xfree, 0);
                    if (WO_GATE <= 2) { mbar_wait(bar_v + (2 - WO_GATE) * 16, 0); mbar_wait(bar_v + (2 - WO_GATE) * 16 + 8, 0); }
                    else mbar_wait(bar_full + ((NITEM - WO_GATE) & (NS - 1)) * 8, ((NITEM - WO_GATE) >> 3) & 1);
#pragma unroll 1
                    for (int i = 0; i < 5; i++) {
                        mbar_expect_tx(bar_wo + i * 8, DH * 64);
                        tma2d(sb + X_WO + i * (DH * 64), &tm_wo, bown * 160 + i * 32, head * DH, bar_wo + i * 8);
                    }
                    if (is_f) {
                        mbar_wait(bar_wo + WF_GATE * 8, 0);
                        { const uint32_t c0 = clock32(); while (clock32() - c0 < WF_DELAY) { } }
#pragma unroll 1
                        for (int i = 0; i < 4; i++) {
                            mbar_expect_tx(bar_w1 + i * 8, 160 * 64);
                            tma2d(sb + X_W1 + i * (160 * 64), &tm_w1, 32 * f, 160 * i, bar_w1 + i * 8);
                        }
#pragma unroll 1
                        for (int i = 0; i < 3; i++) mbar_wait(bar_empty + i * 8, ((NITEM >> 3) - 1) & 1);
                        { const uint32_t c0 = clock32(); while (clock32() - c0 < W2_DELAY) { } }
                        mbar_expect_tx(bar_w2, D * 64);
#pragma unroll 1
                        for (int i = 0; i < 10; i++) tma2d(sb + X_W2 + i * 4096, &tm_w2, 64 * i, 32 * f, bar_w2);
                    }
                    break;
                }
                const int s = t & (NS - 1);
                if (t >= NS) {
                    mbar_wait(bar_empty + s * 8, ((t >> 3) - 1) & 1);
                    while ((int)(gtime32() - t_start) < PACE_A + (t - NS) * PACE_TAU) { }
                } else if (t >= INFLIGHT) {
                    mbar_wait(bar_full + (t - INFLIGHT) * 8, 0);
                }
                if (t < NITEM - 2) {
                    const int pair = t == NITEM - 3 ? NITEM / 2 - 1 : t >> 1;
                    mbar_expect_tx(bar_full + s * 8, TILE_BYTES);
                    bulk_load(sb + OFF_RING + s * TILE_BYTES, ((t & 1) && t != NITEM - 3 ? vb : kb) + (size_t)((pair + rot) & (NITEM / 2 - 1)) * TILE_BYTES, TILE_BYTES, bar_full + s * 8, pol);
                } else {
                    const int row = (bown * NH + head) * SK + (SK - WIN) + ((t - NITEM / 2 + rot) & (NITEM / 2 - 1)) * TILE_KEYS;
#pragma unroll 1
                    for (int i = 0; i < 2; i++) {
                        const uint32_t bar = bar_v + (2 * (t - (NITEM - 2)) + i) * 8;
                        mbar_expect_tx(bar, TILE_BYTES / 2);
                        tma2d_hint(sb + OFF_RING + s * TILE_BYTES + i * (TILE_BYTES / 2), &tm_v, 64 * i, row, bar, pol);
                    }
                }
            }
        }
        __syncwarp();
    }

    if (warp == 9) {
        int side = 0;
        if (lane == 0) {
            uint32_t best[2] = {~0u, ~0u};
#pragma unroll 1
            for (int i = 0; i < 2 * NPROBE && ((i & 1) || (int)(gtime32() - t_start) < PROBE_END); i++) {
                uint32_t t0 = clock32(), v, t1;
                asm volatile("atom.relaxed.gpu.global.exch.b32 %0, [%1], %2;" : "=r"(v) : "l"(slot(SL_SIDE, i & 1) + cta * 8), "r"(0u) : "memory");
                asm volatile("{\n.reg .pred p;\nsetp.ne.u32 p, %1, 0xffffffff;\nmov.u32 %0, 0;\n@p mov.u32 %0, %%clock;\n}" : "=r"(t1) : "r"(v) : "memory");
                if (i & 1) best[1] = min(best[1], t1 - t0); else best[0] = min(best[0], t1 - t0);
            }
            side = best[1] < best[0];
        }
        side = __shfl_sync(0xffffffffu, side, 0);
        HPROF(1);
        mbar_wait(bar_full + (NS - 1) * 8, 0);
        stg_zero4(slot(SL_O + (cta >> 4), lane >> 4) + (cta & 15) * 64 + (lane & 15) * 4);
        if (is_owner) {
#pragma unroll 1
            for (int i = lane; i < NH * 8; i += 32) stg_zero4(slot(SL_P1 + own, side) + i * 4);
#pragma unroll 1
            for (int i = lane; i < NF * 8; i += 32) stg_zero4(slot(SL_P2 + 2 * own + (i >> 8), side) + (i & 255) * 4);
            if (lane < 8) stg_zero4(slot(SL_X1 + own / 30, lane >> 2) + (own % 30) * 32 + (lane & 3) * 4);
        }
        __threadfence();
        __syncwarp();
        if (lane == 0) stg_relaxed(g_clr + cta, 1u + side);
        HPROF(0);
        HPROF(2);
        while ((int)(gtime32() - t_start) < CLR_CHECK) __nanosleep(1000);
        mbar_wait(bar_xfree, 0);
        {
            uint4 v = make_uint4(1, 1, 1, 1), gv = v, mv[20];
#pragma unroll
            for (int i = 0; i < 20; i++) mv[i] = v;
#pragma unroll 1
            for (int it = 0;; it++) {
                v = ldg_relaxed(g_clr + lane * 4);
                ldg_relaxed_if(is_owner && lane < 8, gv, mod_slot(lane < 4 ? 2 : 5, own, lane & 3));
#pragma unroll
                for (int i = 0; i < 20; i++) ldg_relaxed_if(is_f, mv[i], mod_slot(3, 8 * i + (lane >> 2), lane & 3));
                bool ok = ready(v) && ready(gv);
#pragma unroll
                for (int i = 0; i < 20; i++) ok = ok && ready(mv[i]);
                if (__all_sync(0xffffffffu, ok)) break;
                if (it > SPIN_LIMIT) __trap();
                __nanosleep(2000);
            }
            const uint32_t w[4] = {v.x, v.y, v.z, v.w};
#pragma unroll
            for (int i = 0; i < 4; i++) {
                const Roles r = roles(4 * lane + i);
                if (r.is_owner) {
                    sts32(sb + OFF_TAB1 + r.own * 4, (uint32_t)(size_t)(slot(SL_P1 + r.own, w[i] - 1) + head * 32));
                    sts32(sb + OFF_TAB2 + r.own * 4, (uint32_t)(size_t)(slot(SL_P2 + 2 * r.own + (f >> 5), w[i] - 1) + (f & 31) * 32));
                }
            }
            if (lane == 0) sts32(sb + OFF_SIDE, side);
            if (lane < 8) sts128(sb + OWN_GA + lane * 16, inv4(gv));
            const uint32_t dst = sb + OFF_VA + (lane & 3) * VEC_STRIDE + (lane >> 2) * 16;
#pragma unroll
            for (int i = 0; i < 10; i++) {
                const uint4 c = inv4(mv[10 + i]);
                sts128(dst + i * 128, make_uint4(bf2_add(c.x, 0x3f803f80u), bf2_add(c.y, 0x3f803f80u), bf2_add(c.z, 0x3f803f80u), bf2_add(c.w, 0x3f803f80u)));
                sts128(dst + (OFF_VB - OFF_VA) + i * 128, inv4(mv[i]));
            }
        }
        asm volatile("fence.acq_rel.gpu;" ::: "memory");
        __syncwarp();
        HPROF(3);
        if (lane == 0) mbar_arrive(bar_help);
        {
            const uint32_t* const src = pin(slot(SL_O + (cta >> 4), side) + (cta & 12) * 64 + lane * 4);
            const uint32_t dst = pin(sb + OFF_O + (lane >> 4) * O_STRIDE + (lane & 15) * 16);
            mbar_wait(bar_v + 16, 0);
            mbar_wait(bar_v + 24, 0);
            uint4 v[2];
            const uint32_t* const ptr[2] = {src, src + 128};
            const bool on[2] = {true, true};
            poll_n<2>(v, ptr, on);
            sts128(dst, v[0]);
            sts128(dst + 2 * O_STRIDE, v[1]);
#pragma unroll
            for (int w = 0; w < 8; w++) asm volatile("bar.arrive %0, 64;" ::"r"(NB_O + w) : "memory");
        }
        HPROF(4);
    }
    if (warp >= 8) {
        if (is_f) gelu_stage(sb, warp - 8, lane);
        return;
    }

    const int g = lane >> 2, t4 = lane & 3;
    const int mi = lane >> 3, r8 = lane & 7;

    {
        auto silu4 = [&](const uint4& cv) {
            uint32_t w4[4] = {cv.x, cv.y, cv.z, cv.w};
#pragma unroll
            for (int e = 0; e < 4; e++) {
                float c0 = bf_lo(w4[e]), c1 = bf_hi(w4[e]);
                w4[e] = pack_bf(c0 * rcp_fast(1.f + ex2(-1.4426950408889634f * c0)), c1 * rcp_fast(1.f + ex2(-1.4426950408889634f * c1)));
            }
            return make_uint4(w4[0], w4[1], w4[2], w4[3]);
        };
        if (crit || late) {
            uint4 v = silu4(ca0);
            sts128(sb + OFF_VA + (tid / 80) * VEC_STRIDE + (tid % 80) * 16, v);
            if (tid < 64) { v = silu4(ca1); sts128(sb + OFF_VA + 3 * VEC_STRIDE + (16 + tid) * 16, v); }
        }
        if (warp < 4) {
            float s = 0.f, q = 0.f;
            const float pv = __shfl_sync(0xffffffffu, bf_lo(xs[0].x), 0);
#pragma unroll
            for (int i = 0; i < 3; i++) if (i < 2 || lane < 16) acc_stats(xs[i], pv, s, q);
#pragma unroll
            for (int of = 16; of > 0; of >>= 1) { s += __shfl_xor_sync(0xffffffffu, s, of); q += __shfl_xor_sync(0xffffffffu, q, of); }
            uint32_t m2; float rden;
            ln_finish(pv, s, q, m2, rden);
            if (lane == 0) { sts32(sb + OFF_STAT + warp * 8, m2); sts_f32(sb + OFF_STAT + warp * 8 + 4, rden); }
        } else if (warp == 4) {
            sts32(sb + OWN_X + lane * 4, bf2_add(own0, 0u));
            sts_f32(sb + OWN_B1 + lane * 4, bf2f(own2));
        }
    }
    bar_cons();
    PROF(24);
    uint32_t qf[8][2];
    float o[8][4];
#pragma unroll
    for (int c = 0; c < 8; c++) { o[c][0] = o[c][1] = o[c][2] = o[c][3] = 0.f; }
    float m_run = -INFINITY, l_run = 0.f;
    const bool diag = (t4 == (g >> 1));
    const bool odd = g & 1;
    const uint32_t koff = (warp & 3) * 4096 + (r8 + 8 * (mi & 1)) * 256 + (mi >> 1) * 128 + (r8 << 4);
    const uint32_t voff = TILE_BYTES + (warp & 3) * 4096 + (r8 + 8 * (mi >> 1)) * 256 + (mi & 1) * 128 + (r8 << 4);
    const int src0 = (2 * t4) * 4 + t4, src1 = (2 * t4 + 1) * 4 + t4;
#pragma unroll 1
    for (int step = crit ? 0 : 1; step < 3; step++) {
        if (step < 2 || late) {
            if (step == 1) {
                if (!crit) mbar_wait(bar_wq, 0);
                const uint32_t m2 = lds32(sb + OFF_STAT + (tid & 3) * 8);
                const float rden = lds_f32(sb + OFF_STAT + (tid & 3) * 8 + 4);
                uint4 v[4] = {xa, xa, xa, xa};
                const uint32_t* const ptr[4] = {mod_slot(0, tid >> 2, tid & 3), mod_slot(1, tid >> 2, tid & 3),
                                                mod_slot(0, 64 + ((tid & 63) >> 2), tid & 3), mod_slot(1, 64 + ((tid & 63) >> 2), tid & 3)};
                const bool on[4] = {true, true, tid < 64, tid < 64};
                poll_n<4>(v, ptr, on);
                uint4 h0 = ln_mod4(xa, v[1], v[0], m2, rden);
                sts128(sb + OFF_VB + (tid & 3) * VEC_STRIDE + (tid >> 2) * 16, h0);
                if (tid < 64) {
                    h0 = ln_mod4(xb, v[3], v[2], m2, rden);
                    sts128(sb + OFF_VB + (tid & 3) * VEC_STRIDE + (64 + (tid >> 2)) * 16, h0);
                }
            }
            mbar_wait(step == 1 ? bar_wq : bar_wm, 0);
            bar_cons();
            const uint32_t strip = sb + (step == 1 ? X_WQ : X_WM), vec = sb + (step == 1 ? OFF_VB : OFF_VA);
            float acc[2][4];
#pragma unroll
            for (int m = 0; m < 2; m++) { acc[m][0] = acc[m][1] = acc[m][2] = acc[m][3] = 0.f; }
#pragma unroll
            for (int i = 0; i < 5; i++) {
                int k0 = (warp * 5 + i) * 16;
                uint32_t b0, b1;
                load_bfrag(vec, VEC_STRIDE, k0, g, t4, b0, b1);
                int krow = k0 + r8 + 8 * (mi >> 1);
#pragma unroll
                for (int m = 0; m < 2; m++) {
                    uint32_t a[4];
                    int ch = 2 * m + (mi & 1);
                    ldsm4t(a, strip + krow * 64 + ((ch ^ ((krow >> 1) & 3)) << 4));
                    mma16816(acc[m], a, b0, b1);
                }
            }
            if (t4 < 2) {
#pragma unroll
                for (int m = 0; m < 2; m++) {
                    sts_f32x2(sb + OFF_RED + ((warp * 32 + m * 16 + g) * 4 + 2 * t4) * 4, acc[m][0], acc[m][1]);
                    sts_f32x2(sb + OFF_RED + ((warp * 32 + m * 16 + g + 8) * 4 + 2 * t4) * 4, acc[m][2], acc[m][3]);
                }
            }
            bar_cons();
            if (tid < 128) {
                float v = 0.f;
#pragma unroll
                for (int w = 0; w < 8; w++) v += lds_f32(sb + OFF_RED + (w * 128 + tid) * 4);
                float vn = __shfl_down_sync(0xffffffffu, v, 4);
                uint32_t* dst = step == 1 ? g_q + ((cta & ~3) + (tid & 3)) * 64 + bown * 16 + (tid >> 3) : g_mod + mc * 64 + (tid & 3) * 16 + (tid >> 3);
                if (!((tid >> 2) & 1)) stg_relaxed(dst, ~pack_bf(v, vn));
            }
        }
        if (step == 0) continue;
        if (step == 1) {
            if (warp == 0) {
                uint4 v = poll1(g_q + cta * 64 + (lane & 15) * 4, lane < 16);
                if (lane < 16) {
                    sts128(sb + OFF_Q + lane * 16, v);
                    stg_zero4(g_q + cta * 64 + lane * 4);
                }
            }
            bar_cons();
            PROF(4);

#pragma unroll
            for (int c = 0; c < 8; c++) {
                qf[c][0] = lds32(sb + OFF_Q + (((c ^ g) * 4 + t4) << 2));
                qf[c][1] = lds32(sb + OFF_Q + 128 + (((c ^ g) * 4 + t4) << 2));
            }
        } else {
            bar_cons();
            if (tid == 0) mbar_arrive(bar_xfree);
        }
#pragma unroll 1
        for (int j = (step == 1 ? 0 : SEG_J) + (warp >> 2); j < (step == 1 ? SEG_J : NITEM / 2 - 2); j += 2) {
            const int s = (2 * j) & (NS - 1);
            const uint32_t par = (j >> 2) & 1;
            mbar_wait(bar_full + s * 8, par);
            const uint32_t base = sb + OFF_RING + s * TILE_BYTES;
            float sa[4] = {0.f, 0.f, 0.f, 0.f}, sb2[4] = {0.f, 0.f, 0.f, 0.f};
#pragma unroll
            for (int c = 0; c < 8; c += 2) {
                uint32_t a[4], a2[4];
                ldsm4(a, (base + koff) ^ (c << 4));
                ldsm4(a2, (base + koff) ^ ((c + 1) << 4));
                mma16816(sa, a, qf[c][0], qf[c][1]);
                mma16816(sb2, a2, qf[c + 1][0], qf[c + 1][1]);
            }
            const uint32_t sw = pack_bf(odd ? sa[1] + sb2[1] : sa[0] + sb2[0], odd ? sa[3] + sb2[3] : sa[2] + sb2[2]);
            const uint32_t sv = pack_bf(bf_lo(sw) * 0.08838834764831845f, bf_hi(sw) * 0.08838834764831845f);
            const float s0 = bf_lo(sv) * 1.4426950408889634f, s1 = bf_hi(sv) * 1.4426950408889634f;
            float m_new = fmaxf(m_run, fmaxf(s0, s1));
            const bool grow = __any_sync(0xffffffffu, (diag && (m_new > m_run)));
            if (lane == 0) mbar_arrive(bar_empty + s * 8);
            if (grow) {
                float al = ex2(m_run - m_new);
                float a0 = __shfl_sync(0xffffffffu, al, src0), a1 = __shfl_sync(0xffffffffu, al, src1);
#pragma unroll
                for (int c = 0; c < 8; c++) { o[c][0] *= a0; o[c][1] *= a1; o[c][2] *= a0; o[c][3] *= a1; }
                l_run *= al;
                m_run = m_new;
            }
            uint32_t pw = pack_bf(ex2(s0 - m_run), ex2(s1 - m_run));
            l_run += bf_lo(pw) + bf_hi(pw);
            uint32_t b0 = odd ? (pw << 16) : (pw & 0xffffu);
            uint32_t b1 = odd ? (pw & 0xffff0000u) : (pw >> 16);
            if (!diag) { b0 = 0u; b1 = 0u; }
            mbar_wait(bar_full + (s + 1) * 8, par);
#pragma unroll
            for (int c = 0; c < 8; c++) {
                uint32_t a[4];
                ldsm4t(a, (base + voff) ^ (c << 4));
                mma16816(o[c], a, b0, b1);
            }
            __syncwarp();
            if (lane == 0) mbar_arrive(bar_empty + (s + 1) * 8);
        }
    }
    PROF(5);
    float acc[4][4];
    uint32_t pa[8][2];
    float rinv;
    {
        const int s = 4 + (warp >> 2);
        mbar_wait(bar_full + s * 8, 1);
        const uint32_t base = sb + OFF_RING + s * TILE_BYTES;
        float sa[4] = {0.f, 0.f, 0.f, 0.f}, sb2[4] = {0.f, 0.f, 0.f, 0.f};
#pragma unroll
        for (int c = 0; c < 8; c += 2) {
            uint32_t a[4], a2[4];
            ldsm4(a, (base + koff) ^ (c << 4));
            ldsm4(a2, (base + koff) ^ ((c + 1) << 4));
            mma16816(sa, a, qf[c][0], qf[c][1]);
            mma16816(sb2, a2, qf[c + 1][0], qf[c + 1][1]);
        }
        const uint32_t sw = pack_bf(odd ? sa[1] + sb2[1] : sa[0] + sb2[0], odd ? sa[3] + sb2[3] : sa[2] + sb2[2]);
        const uint32_t sv = pack_bf(bf_lo(sw) * 0.08838834764831845f, bf_hi(sw) * 0.08838834764831845f);
        const float s0 = bf_lo(sv) * 1.4426950408889634f, s1 = bf_hi(sv) * 1.4426950408889634f;
        int mi_ = __float_as_int(diag ? fmaxf(m_run, fmaxf(s0, s1)) : -INFINITY);
        mi_ ^= (mi_ >> 31) & 0x7fffffff;
        mi_ = __reduce_max_sync(0xffffffffu, mi_);
        mi_ ^= (mi_ >> 31) & 0x7fffffff;
        if (lane == 0) sts32(sb + OFF_ML + warp * 4, mi_);
        bar_cons();
        const float4 m0 = lds_f32x4(sb + OFF_ML), m1 = lds_f32x4(sb + OFF_ML + 16);
        const float mx = fmaxf(fmaxf(fmaxf(m0.x, m0.y), fmaxf(m0.z, m0.w)), fmaxf(fmaxf(m1.x, m1.y), fmaxf(m1.z, m1.w)));
        const float scl = ex2(m_run - mx);
        const uint32_t pw = pack_bf(ex2(s0 - mx), ex2(s1 - mx));
        if (diag) { sts16(sb + SC_P + (warp * 16 + g) * 2, pw); sts16(sb + SC_P + (warp * 16 + g + 8) * 2, pw >> 16); }
        const float lw = warp_sum(diag ? fmaf(l_run, scl, bf_lo(pw) + bf_hi(pw)) : 0.f);
        const float a0 = __shfl_sync(0xffffffffu, scl, src0), a1 = __shfl_sync(0xffffffffu, scl, src1);
        float v[8], u[8];
#pragma unroll
        for (int c = 0; c < 8; c++) {
            v[c] = a0 * o[c][0] + a1 * o[c ^ 1][1];
            u[c] = a0 * o[c][2] + a1 * o[c ^ 1][3];
        }
#pragma unroll
        for (int c = 0; c < 8; c++) {
            if (!(c & 2)) {
                v[c] += __shfl_xor_sync(0xffffffffu, v[c ^ 2], 1);
                u[c] += __shfl_xor_sync(0xffffffffu, u[c ^ 2], 1);
            }
        }
#pragma unroll
        for (int c = 0; c < 2; c++) {
            v[c] += __shfl_xor_sync(0xffffffffu, v[c ^ 4], 2);
            u[c] += __shfl_xor_sync(0xffffffffu, u[c ^ 4], 2);
        }
        const uint32_t dst = sb + SC_OP + (warp * 128 + 16 * t4 + g) * 4;
        sts_f32(dst, v[0]); sts_f32(dst + 32, v[1]); sts_f32(dst + 256, u[0]); sts_f32(dst + 288, u[1]);
        if (lane == 0) sts_f32(sb + OFF_ML + 32 + warp * 4, lw);
        mbar_wait(bar_help, 0);
        bar_cons();
        const float4 l0 = lds_f32x4(sb + OFF_ML + 32), l1 = lds_f32x4(sb + OFF_ML + 48);
        rinv = rcp_fast(((l0.x + l0.y) + (l0.z + l0.w)) + ((l1.x + l1.y) + (l1.z + l1.w)));
#pragma unroll
        for (int i = 0; i < 4; i++) acc[i][0] = acc[i][1] = acc[i][2] = acc[i][3] = 0.f;
#pragma unroll
        for (int w = 0; w < 8; w++) {
            const float2 x0 = lds_f32x2(sb + SC_OP + (w * 128 + 16 * warp + 2 * t4) * 4), x1 = lds_f32x2(sb + SC_OP + (w * 128 + 16 * warp + 8 + 2 * t4) * 4);
            acc[2 * (w & 1)][0] += x0.x; acc[2 * (w & 1)][1] += x0.y;
            acc[2 * (w & 1) + 1][0] += x1.x; acc[2 * (w & 1) + 1][1] += x1.y;
        }
#pragma unroll
        for (int ks = 0; ks < 8; ks++) { pa[ks][0] = lds32(sb + SC_P + (8 * ks + t4) * 4); pa[ks][1] = lds32(sb + SC_P + (8 * ks + 4 + t4) * 4); }
    }
    PROF(20);
    const int mt = warp < 2 ? warp : warp + 2;
    {
        const uint32_t va = pin(sb + OFF_RING + 6 * TILE_BYTES + (warp >> 2) * (TILE_BYTES / 2) + (8 * (mi & 1) + r8) * 128 + (((2 * (warp & 3) + (mi >> 1)) ^ r8) << 4));
        const uint32_t vbar = pin(bar_v + (warp >> 2) * 8);
        uint32_t* const o_dst = pin(slot(SL_O + (cta >> 4), g) + (cta & 15) * 64 + warp * 8 + 2 * t4);
#pragma unroll
        for (int tl = 0; tl < 2; tl++) {
            mbar_wait(vbar + tl * 16, 0);
            uint32_t r[4][4];
#pragma unroll
            for (int ks = 0; ks < 4; ks++) ldsm4t(r[ks], va + tl * TILE_BYTES + ks * 2048);
#pragma unroll
            for (int ks = 0; ks < 4; ks++) {
                const uint32_t a[4] = {pa[4 * tl + ks][0], 0u, pa[4 * tl + ks][1], 0u};
                mma16816(acc[2 * (ks & 1)], a, r[ks][0], r[ks][1]);
                mma16816(acc[2 * (ks & 1) + 1], a, r[ks][2], r[ks][3]);
            }
        }
        stg_relaxed2_if(g < 2, o_dst, ~pack_bf((acc[0][0] + acc[2][0]) * rinv, (acc[0][1] + acc[2][1]) * rinv),
                        ~pack_bf((acc[1][0] + acc[3][0]) * rinv, (acc[1][1] + acc[3][1]) * rinv));
    }
    PROF(7);
    const int side = lds32(sb + OFF_SIDE);
    const uint32_t red_st = pin(sb + SC_E4 + ((warp * 4 + 2 * ((lane >> 3) & 1) + (lane >> 4)) * 8 + (lane & 7)) * 4);
    const uint32_t red_ld = pin(sb + SC_E4 + (lane & 15) * 8);
    const uint32_t* const in1 = pin(slot(SL_P1 + own, side) + tid * 4);
    const uint32_t* const in2a = pin(slot(SL_P2 + 2 * own, side) + tid * 4);
    const uint32_t* const in2b = pin(slot(SL_P2 + 2 * own + 1, side) + tid * 4);
    uint32_t* const x1_dst = pin(slot(SL_X1 + own / 30, lane >> 4) + (own % 30) * 32 + (lane & 15));
    const uint32_t xw = lds32(sb + OWN_X + (lane & 15) * 4), ga_w = lds32(sb + OWN_GA + (lane & 15) * 4);
    uint32_t cs[15];
    uint32_t* dst2[10];
    uint32_t w2a[5];
#pragma unroll
    for (int j = 0; j < 10; j++) cs[j] = lds32(sb + OFF_VA + ((g & 1) * 4 + (g >> 1)) * VEC_STRIDE + warp * 160 + t4 * 4 + j * 16);
#pragma unroll
    for (int i = 0; i < 5; i++) {
        cs[10 + i] = lds32(sb + OFF_VA + (g >> 1) * VEC_STRIDE + warp * 160 + (g & 1) * 16 + t4 * 4 + i * 32);
        const uint2 t = lds64(sb + OFF_TAB2 + warp * 40 + i * 8);
        dst2[2 * i] = slot_ptr(t.x + g * 16 + t4 * 8);
        dst2[2 * i + 1] = slot_ptr(t.y + g * 16 + t4 * 8);
        const int cc = 2 * (warp * 5 + i) + (mi & 1);
        w2a[i] = pin(sb + X_W2 + (cc >> 3) * 4096 + (r8 + 8 * (mi >> 1)) * 128 + (((cc & 7) ^ r8) << 4));
    }
    const uint32_t piv = lds32(sb + OFF_STAT + (g >> 1) * 8);
    const uint32_t* const xin = pin(slot(SL_X1 + warp / 3, side) + ((warp % 3) * 10 + (g & 1)) * 32 + (g >> 1) * 4 + t4);
    const uint32_t w1a = pin(sb + X_W1 + (warp * 80 + r8 + 8 * (mi >> 1)) * 64 + (((mi & 1) ^ ((r8 >> 1) & 3)) << 4));
    const uint32_t w1bar = pin(bar_w1 + (warp >> 1) * 8);
    const uint32_t ab_st = pin(sb + SC_AB + warp * 1024 + lane * 16), y_st = pin(sb + SC_Y + warp * 512 + lane * 8), s_st = pin(sb + SC_ST + (t4 * 8 + warp) * 8);
    const uint32_t h_ld = pin(sb + SC_H1 + ((g & 3) ^ (2 * (f & 1) + ((f >> 1) & 1))) * 64 + t4 * 16);
    {
        const int kap = 2 * (head & 1) + ((head >> 1) & 1);
        const uint32_t wa = pin(sb + X_WO + (mt >> 1) * (DH * 64) + (r8 + 8 * (mi >> 1)) * 64 + ((((mt & 1) * 2 + (mi & 1)) ^ ((r8 >> 1) & 3)) << 4));
        const uint32_t oa = pin(sb + OFF_O + ((g & 3) ^ kap) * O_STRIDE + t4 * 8);
        uint32_t* dst[4];
#pragma unroll
        for (int i = 0; i < 2; i++) {
            const uint2 t = lds64(sb + OFF_TAB1 + (bown * 20 + 2 * mt + (warp < 2 ? 4 * i : 0)) * 4);
            dst[2 * i] = slot_ptr(t.x + g * 16 + t4 * 8);
            dst[2 * i + 1] = slot_ptr(t.y + g * 16 + t4 * 8);
        }
        const uint32_t obar = pin(NB_O + warp);
        PROF(6);
        uint32_t wf[8][4], wg[8][4];
        mbar_wait(bar_wo + (mt >> 1) * 8, 0);
#pragma unroll
        for (int ks = 0; ks < 8; ks++) ldsm4t(wf[ks], wa + ks * 1024);
        if (warp < 2) {
            mbar_wait(bar_wo + 8, 0);
#pragma unroll
            for (int ks = 0; ks < 8; ks++) ldsm4t(wg[ks], wa + DH * 64 + ks * 1024);
        }
        asm volatile("bar.sync %0, 64;" ::"r"(obar) : "memory");
        PROF(8);
        uint2 ob[8];
#pragma unroll
        for (int ks = 0; ks < 8; ks++) ob[ks] = lds64(oa + ks * 32);
        float c0[4] = {0.f, 0.f, 0.f, 0.f}, c1[4] = {0.f, 0.f, 0.f, 0.f};
        if (warp < 2) {
            float c2[4] = {0.f, 0.f, 0.f, 0.f}, c3[4] = {0.f, 0.f, 0.f, 0.f};
#pragma unroll
            for (int ks = 0; ks < 8; ks += 2) {
                mma16816(c0, wf[ks], ob[ks].x, ob[ks].y);
                mma16816(c2, wg[ks], ob[ks].x, ob[ks].y);
                mma16816(c1, wf[ks + 1], ob[ks + 1].x, ob[ks + 1].y);
                mma16816(c3, wg[ks + 1], ob[ks + 1].x, ob[ks + 1].y);
            }
            stg_relaxed2_if(t4 < 2, dst[2], flag(c2[0] + c3[0]), flag(c2[1] + c3[1]));
            stg_relaxed2_if(t4 < 2, dst[3], flag(c2[2] + c3[2]), flag(c2[3] + c3[3]));
        } else {
#pragma unroll
            for (int ks = 0; ks < 8; ks += 2) {
                mma16816(c0, wf[ks], ob[ks].x, ob[ks].y);
                mma16816(c1, wf[ks + 1], ob[ks + 1].x, ob[ks + 1].y);
            }
        }
        stg_relaxed2_if(t4 < 2, dst[0], flag(c0[0] + c1[0]), flag(c0[1] + c1[1]));
        stg_relaxed2_if(t4 < 2, dst[1], flag(c0[2] + c1[2]), flag(c0[3] + c1[3]));
    }
    PROF(9);
    uint32_t x1w = 0;
    if (is_owner) {
        uint4 v;
        for (int it = 0;; it++) {
            v = ldg_relaxed(in1);
            if (__all_sync(0xffffffffu, and3(and3(v.x, v.y, v.z), v.w, 1u))) break;
            if (it > SPIN_LIMIT) __trap();
        }
        PROF(11);
        const float s0 = __uint_as_float(v.x) + __shfl_xor_sync(0xffffffffu, __uint_as_float(v.z), 8);
        const float s1 = __uint_as_float(v.y) + __shfl_xor_sync(0xffffffffu, __uint_as_float(v.w), 8);
        sts_f32(red_st, s0 + __shfl_xor_sync(0xffffffffu, s1, 16));
        if (warp == 0) {
            nbar_sync<NB_E4, 256>();
            float2 a[8];
#pragma unroll
            for (int w = 0; w < 8; w++) a[w] = lds_f32x2(red_ld + w * 128);
            const uint32_t aw = pack_bf(((a[0].x + a[1].x) + (a[2].x + a[3].x)) + ((a[4].x + a[5].x) + (a[6].x + a[7].x)),
                                        ((a[0].y + a[1].y) + (a[2].y + a[3].y)) + ((a[4].y + a[5].y) + (a[6].y + a[7].y)));
            x1w = bf2_add(xw, bf2_mul(ga_w, aw));
            stg_relaxed(x1_dst, x1w ^ 0x80008000u);
        } else {
            nbar_arrive<NB_E4, 256>();
        }
    }
    PROF(12);
    if (is_f) {
        uint32_t f1[5][2][4], f2[5][2][4];
        uint32_t d[6];
        auto load_x1 = [&] {
#pragma unroll
            for (int i = 0; i < 5; i++) d[i] = ldg_relaxed32(xin + i * 64);
        };
        auto have_x1 = [&] { return __all_sync(0xffffffffu, __vimin3_u32(__vimin3_u32(d[0], d[1], d[2]), d[3], d[4]) != 0u); };
        mbar_wait(w1bar, 0);
        load_x1();
        {
#pragma unroll
            for (int i = 0; i < 5; i++) { ldsm4t(f1[i][0], w1a + i * 1024); ldsm4t(f1[i][1], (w1a ^ 32) + i * 1024); }
            float c[2][4];
#pragma unroll
            for (int m = 0; m < 2; m++) c[m][0] = c[m][1] = c[m][2] = c[m][3] = 0.f;
#pragma unroll
            for (int i = 0; i < 5; i++) { mma16816(c[0], f1[i][0], cs[2 * i], cs[2 * i + 1]); mma16816(c[1], f1[i][1], cs[2 * i], cs[2 * i + 1]); }
#pragma unroll
            for (int i = 0; i < 5; i++) { cs[2 * i] = pin(odd ? 0u : cs[10 + i]); cs[2 * i + 1] = pin(odd ? cs[10 + i] : 0u); }
#pragma unroll
            for (int m = 0; m < 2; m++) sts128(ab_st + m * 512, make_uint4(__float_as_uint(c[m][0]), __float_as_uint(c[m][1]), __float_as_uint(c[m][2]), __float_as_uint(c[m][3])));
            nbar_arrive<NB_AB, 320>();
            d[0] |= __float_as_uint(c[1][3]) & (side >> 1);
        }
        PROF(10);
#pragma unroll 1
        for (int it = 0; !have_x1(); it++) {
            load_x1();
            if (it > SPIN_LIMIT) __trap();
        }
        PROF(13);
        {
            float y[2][4], st[4] = {0.f, 0.f, 0.f, 0.f};
#pragma unroll
            for (int m = 0; m < 2; m++) y[m][0] = y[m][1] = y[m][2] = y[m][3] = 0.f;
#pragma unroll
            for (int i = 0; i < 5; i++) d[i] = bf2_add(d[i], piv);
            d[5] = 0u;
#pragma unroll
            for (int i = 0; i < 5; i++) {
                if (i < 3) {
                    const uint32_t a[4] = {d[2 * i], 0x3f803f80u, d[2 * i + 1], 0x3f803f80u};
                    mma16816(st, a, d[2 * i], d[2 * i + 1]);
                }
                const uint32_t y0 = bf2_mul(d[i], cs[2 * i]), y1 = bf2_mul(d[i], cs[2 * i + 1]);
                mma16816(y[0], f1[i][0], y0, y1);
                mma16816(y[1], f1[i][1], y0, y1);
            }
            const float q = odd ? st[1] : st[0];
            const float q2 = q + __shfl_xor_sync(0xffffffffu, q, 4);
            if (diag && !odd) sts_f32x2(s_st, q2, st[2] + st[3]);
#pragma unroll
            for (int m = 0; m < 2; m++) sts_f32x2(y_st + m * 256, y[m][0] + y[m][1], y[m][2] + y[m][3]);
        }
        nbar_arrive<NB_Y, 320>();
        PROF(14);
        mbar_wait(bar_w2, 0);
#pragma unroll
        for (int i = 0; i < 5; i++) { ldsm4t(f2[i][0], w2a[i]); ldsm4t(f2[i][1], w2a[i] + 2048); }
        nbar_sync<NB_H1, 320>();
        PROF(15);
        {
            const uint4 hb = lds128(h_ld);
            float c[5][4];
#pragma unroll
            for (int i = 0; i < 7; i++) {
                if (i < 5) { c[i][0] = c[i][1] = c[i][2] = c[i][3] = 0.f; mma16816(c[i], f2[i][0], hb.x, hb.y); }
                if (i > 0 && i < 6) mma16816(c[i - 1], f2[i - 1][1], hb.z, hb.w);
                if (i > 1) {
                    stg_relaxed2_if(t4 < 2, dst2[2 * i - 4], flag(c[i - 2][0]), flag(c[i - 2][1]));
                    stg_relaxed2_if(t4 < 2, dst2[2 * i - 3], flag(c[i - 2][2]), flag(c[i - 2][3]));
                }
            }
        }
    }
    PROF(16);
    if (is_owner) {
        uint32_t* const dst = pin((uint32_t*)(p.out + ((lane >> 2) & 3) * D + 8 * own) + t4);
        const uint32_t b2w = lds32(sb + OWN_B2 + (lane & 15) * 4), gb_w = lds32(sb + OWN_GB + (lane & 15) * 4);
        const bool two = tid < NF * 8 - 256;
        uint4 v, w = make_uint4(1, 1, 1, 1);
        for (int it = 0;; it++) {
            ldg_relaxed_if(two, w, in2b);
            v = ldg_relaxed(in2a);
            if (__all_sync(0xffffffffu, and3(and3(v.x, v.y, v.z), and3(v.w, w.x, w.y), and3(w.z, w.w, 1u)))) break;
            if (it > SPIN_LIMIT) __trap();
        }
        PROF(17);
        const float s0 = (__uint_as_float(v.x) + __uint_as_float(w.x)) + __shfl_xor_sync(0xffffffffu, __uint_as_float(v.z) + __uint_as_float(w.z), 8);
        const float s1 = (__uint_as_float(v.y) + __uint_as_float(w.y)) + __shfl_xor_sync(0xffffffffu, __uint_as_float(v.w) + __uint_as_float(w.w), 8);
        sts_f32(red_st + (SC_E6 - SC_E4), s0 + __shfl_xor_sync(0xffffffffu, s1, 16));
        nbar_sync<NB_E6, 256>();
        if (warp == 0) {
            float2 a[8];
#pragma unroll
            for (int i = 0; i < 8; i++) a[i] = lds_f32x2(red_ld + (SC_E6 - SC_E4) + i * 128);
            const uint32_t aw = pack_bf(((a[0].x + a[1].x) + (a[2].x + a[3].x)) + ((a[4].x + a[5].x) + (a[6].x + a[7].x)),
                                        ((a[0].y + a[1].y) + (a[2].y + a[3].y)) + ((a[4].y + a[5].y) + (a[6].y + a[7].y)));
            const uint32_t r = bf2_add(x1w, bf2_mul(gb_w, bf2_add(aw, b2w)));
            if (lane < 16) asm volatile("st.global.u32 [%0], %1;" ::"l"(dst), "r"(r) : "memory");
        }
        if (tid >= 32 && tid < 56) stg_zero4(mod_slot((tid - 32) >> 2, own, tid & 3));
    }
    if (tid == 96) stg_relaxed(g_clr + cta, 0u);
    PROF(18);
    PROF_DUMP;
}

typedef CUresult (*EncodeFn)(CUtensorMap*, CUtensorMapDataType, cuuint32_t, void*, const cuuint64_t*, const cuuint64_t*, const cuuint32_t*,
                             const cuuint32_t*, CUtensorMapInterleave, CUtensorMapSwizzle, CUtensorMapL2promotion, CUtensorMapFloatOOBfill);

static CUtensorMap make_map(EncodeFn enc, const void* ptr, int cols, int rows, int box_cols, int box_rows, CUtensorMapSwizzle sw) {
    CUtensorMap m;
    cuuint64_t dims[2] = {(cuuint64_t)cols, (cuuint64_t)rows};
    cuuint64_t strides[1] = {(cuuint64_t)cols * 2};
    cuuint32_t box[2] = {(cuuint32_t)box_cols, (cuuint32_t)box_rows};
    cuuint32_t es[2] = {1, 1};
    enc(&m, CU_TENSOR_MAP_DATA_TYPE_BFLOAT16, 2, const_cast<void*>(ptr), dims, strides, box, es, CU_TENSOR_MAP_INTERLEAVE_NONE, sw,
        CU_TENSOR_MAP_L2_PROMOTION_NONE, CU_TENSOR_MAP_FLOAT_OOB_FILL_NONE);
    return m;
}

}

extern "C" void kernel_launch(void* const* d_in, const int* in_sizes, int n_in, void* d_out, int out_size) {
    (void)in_sizes; (void)n_in; (void)out_size;
    static EncodeFn enc = nullptr;
    if (!enc) {
        void* fn = nullptr;
        cudaDriverEntryPointQueryResult qr;
        cudaGetDriverEntryPoint("cuTensorMapEncodeTiled", &fn, cudaEnableDefault, &qr);
        enc = (EncodeFn)fn;
        cudaFuncSetAttribute(fused_kernel, cudaFuncAttributeMaxDynamicSharedMemorySize, SMEM_BYTES);
    }
    Params p;
    p.x = (const __nv_bfloat16*)d_in[0];
    p.kc = (const __nv_bfloat16*)d_in[1];
    p.vc = (const __nv_bfloat16*)d_in[2];
    p.b1 = (const __nv_bfloat16*)d_in[7];
    p.b2 = (const __nv_bfloat16*)d_in[9];
    p.c = (const __nv_bfloat16*)d_in[10];
    p.out = (__nv_bfloat16*)d_out;
    CUtensorMap tm_wmod = make_map(enc, d_in[11], NMOD, D, 32, 160, CU_TENSOR_MAP_SWIZZLE_64B);
    CUtensorMap tm_wq = make_map(enc, d_in[3], NH * DH, D, 32, 160, CU_TENSOR_MAP_SWIZZLE_64B);
    CUtensorMap tm_wo = make_map(enc, d_in[4], D, NH * DH, 32, 128, CU_TENSOR_MAP_SWIZZLE_64B);
    CUtensorMap tm_w1 = make_map(enc, d_in[6], FF, D, 32, 160, CU_TENSOR_MAP_SWIZZLE_64B);
    CUtensorMap tm_w2 = make_map(enc, d_in[8], D, FF, 64, 32, CU_TENSOR_MAP_SWIZZLE_128B);
    CUtensorMap tm_v = make_map(enc, d_in[2], DH, NB * NH * SK, 64, TILE_KEYS, CU_TENSOR_MAP_SWIZZLE_128B);
    fused_kernel<<<NCTA, NTHREADS, SMEM_BYTES>>>(p, tm_wmod, tm_wq, tm_wo, tm_w1, tm_w2, tm_v);
}
```

```cpp
#include <cuda_runtime.h>
#include <cuda.h>
#include <cuda_bf16.h>
#include <stdint.h>

namespace {

constexpr int NB = 4, D = 640, NH = 32, DH = 128, SK = 8192, WIN = 2048, FF = 1728, NMOD = 6 * D;
constexpr int NCTA = 128;
constexpr int NOWN = 80;
constexpr int NF = 54;
constexpr int NTHREADS = 320;
constexpr int TILE_KEYS = 64;
constexpr int TILE_BYTES = TILE_KEYS * DH * 2;
constexpr int NITEM = 2 * WIN / TILE_KEYS;
constexpr int NS = 8;
constexpr int NMODC = 120;
constexpr int SPIN_LIMIT = 1 << 18;
#define INFLIGHT 3
#define PACE_A 8600
#define PACE_TAU 635
#define WQ_DELAY 800
#define WO_GATE 2
#define WF_GATE 2
#define WF_DELAY 0
#define W2_DELAY 0
#define WF_ALL 0
#define NPROBE 8
#define PROBE_END 10000
#define PH_GAIN 8
#define LAT_FROM 99
#define LAT_END 0
#define PH_FIRST 12
#define PH_LAG 5
#define WO_S 0
#define W1_S 0
#define W2_S 0
#define WQ2_AT 1
#define PF_END 16
#define CLR_CHECK 28000
constexpr int SEG_J = 8;

constexpr int OFF_RING = 0;
constexpr int OFF_X = OFF_RING + NS * TILE_BYTES;
constexpr int X_WM = OFF_X;
constexpr int X_WQ = OFF_X + D * 64;
constexpr int X_WO = OFF_X;
constexpr int X_W1 = X_WO + 5 * DH * 64;
constexpr int X_END = X_W1 + D * 64;
constexpr int X_W2 = OFF_RING;
static_assert(X_WQ + D * 64 <= X_END, "prologue weights must fit");
constexpr int VEC_STRIDE = 1296;
constexpr int OFF_VA = X_END;
constexpr int OFF_VB = OFF_VA + 4 * VEC_STRIDE;
constexpr int OFF_RED = OFF_VB + 4 * VEC_STRIDE;
constexpr int OFF_ML = OFF_RED + 4096;
constexpr int O_STRIDE = 288;
constexpr int OFF_O = OFF_ML + 64;
constexpr int OFF_Q = OFF_O + 4 * O_STRIDE;
constexpr int OFF_OWN = OFF_Q + 256;
constexpr int OWN_X = OFF_OWN, OWN_B2 = OWN_X + 64, OWN_GA = OWN_B2 + 64, OWN_GB = OWN_GA + 64, OWN_B1 = OWN_GB + 64;
constexpr int OFF_STAT = OWN_B1 + 128;
constexpr int OFF_TAB1 = OFF_STAT + 32;
constexpr int OFF_TAB2 = OFF_TAB1 + NOWN * 4;
constexpr int OFF_SIDE = OFF_TAB2 + NOWN * 4;
constexpr int OFF_BAR = OFF_SIDE + 8;
constexpr int NBAR = 2 * NS + 27;
constexpr int SMEM_BYTES = OFF_BAR + NBAR * 8;
constexpr int SC_OP = OFF_RING + 4 * TILE_BYTES;
constexpr int SC_AB = SC_OP + 4096;
constexpr int SC_Y = SC_AB + 8192;
constexpr int SC_ST = SC_Y + 4096;
constexpr int SC_E4 = SC_ST + 256;
constexpr int SC_E6 = SC_E4 + 1024;
constexpr int SC_P = SC_E6 + 1024;
constexpr int SC_H1 = SC_P + 256;
static_assert(SMEM_BYTES <= 232448, "smem");
static_assert(OFF_BAR % 8 == 0 && OFF_X % 1024 == 0 && X_WQ % 512 == 0 && X_W1 % 512 == 0 && OFF_VA % 16 == 0 && OFF_RED % 16 == 0 && OFF_ML % 16 == 0 && OFF_O % 16 == 0 && OFF_Q % 16 == 0, "align");
constexpr int NB_O = 2  , NB_E4 = 10, NB_E6 = 11, NB_AB = 12, NB_Y = 13;

__device__ uint32_t g_mod[NMODC * 64];
__device__ uint32_t g_q[NCTA * 64];
__device__ uint32_t g_clr[NCTA];
__device__ uint32_t g_phase[16 * 32];
constexpr int SL_P1 = 0;
constexpr int SL_P2 = SL_P1 + NOWN;
constexpr int SL_O = SL_P2 + 2 * NOWN;
constexpr int SL_X1 = SL_O + 8;
constexpr int SL_SIDE = SL_X1 + 3;
static_assert(SL_SIDE < 256, "one 2 MB page");
__device__ uint32_t g_slots[2 * 256 * 2048];
__device__ __forceinline__ uint32_t* slot(int i, int side) {
    const size_t base = ((size_t)g_slots + 0x1fffff) & ~(size_t)0x1fffff;
    return (uint32_t*)base + i * 2048 + (((__popc(i & 0x59) ^ side) & 1) << 10);
}
#define PROF_DECL
#define HPROF(i) do { } while (0)
#define PROF(i) do { } while (0)
#define PROF_DUMP do { } while (0)

__device__ __forceinline__ uint32_t smem_u32(const void* p) { return (uint32_t)__cvta_generic_to_shared(p); }
__device__ __forceinline__ void mbar_init(uint32_t bar, uint32_t cnt) { asm volatile("mbarrier.init.shared::cta.b64 [%0], %1;" ::"r"(bar), "r"(cnt) : "memory"); }
__device__ __forceinline__ void mbar_expect_tx(uint32_t bar, uint32_t bytes) { asm volatile("mbarrier.arrive.expect_tx.shared::cta.b64 _, [%0], %1;" ::"r"(bar), "r"(bytes) : "memory"); }
__device__ __forceinline__ void mbar_arrive(uint32_t bar) { asm volatile("mbarrier.arrive.shared::cta.b64 _, [%0];" ::"r"(bar) : "memory"); }
__device__ __forceinline__ void mbar_wait(uint32_t bar, uint32_t parity) {
    uint32_t ok;
    int it = 0;
    while (true) {
        asm volatile("{\n.reg .pred p;\nmbarrier.try_wait.parity.shared::cta.b64 p, [%1], %2;\nselp.u32 %0, 1, 0, p;\n}" : "=r"(ok) : "r"(bar), "r"(parity) : "memory");
        if (ok) break;
        if (++it > SPIN_LIMIT) __trap();
    }
}
__device__ __forceinline__ void bulk_load(uint32_t dst, const void* src, uint32_t bytes, uint32_t bar, uint64_t pol) {
    asm volatile("cp.async.bulk.shared::cluster.global.mbarrier::complete_tx::bytes.L2::cache_hint [%0], [%1], %2, [%3], %4;"
                 ::"r"(dst), "l"(src), "r"(bytes), "r"(bar), "l"(pol) : "memory");
}
__device__ __forceinline__ void bar_cons() { asm volatile("bar.sync 1, 256;" ::: "memory"); }
template <int ID, int N> __device__ __forceinline__ void nbar_sync() { asm volatile("bar.sync %0, %1;" ::"n"(ID), "n"(N) : "memory"); }
template <int ID, int N> __device__ __forceinline__ void nbar_arrive() { asm volatile("bar.arrive %0, %1;" ::"n"(ID), "n"(N) : "memory"); }
__device__ __forceinline__ bool mbar_test(uint32_t bar, uint32_t parity) {
    uint32_t ok;
    asm volatile("{\n.reg .pred p;\nmbarrier.test_wait.parity.shared::cta.b64 p, [%1], %2;\nselp.u32 %0, 1, 0, p;\n}" : "=r"(ok) : "r"(bar), "r"(parity) : "memory");
    return ok;
}
__device__ __forceinline__ uint32_t pin(uint32_t v) { asm volatile("" : "+r"(v)); return v; }
template <class T> __device__ __forceinline__ T* pin(T* v) { asm volatile("" : "+l"(v)); return v; }
__device__ __forceinline__ void ldsm4(uint32_t (&a)[4], uint32_t addr) {
    asm volatile("ldmatrix.sync.aligned.m8n8.x4.shared.b16 {%0,%1,%2,%3}, [%4];" : "=r"(a[0]), "=r"(a[1]), "=r"(a[2]), "=r"(a[3]) : "r"(addr) : "memory");
}
__device__ __forceinline__ void ldsm4t(uint32_t (&a)[4], uint32_t addr) {
    asm volatile("ldmatrix.sync.aligned.m8n8.x4.trans.shared.b16 {%0,%1,%2,%3}, [%4];" : "=r"(a[0]), "=r"(a[1]), "=r"(a[2]), "=r"(a[3]) : "r"(addr) : "memory");
}
__device__ __forceinline__ void mma16816(float (&c)[4], const uint32_t (&a)[4], uint32_t b0, uint32_t b1) {
    asm volatile("mma.sync.aligned.m16n8k16.row.col.f32.bf16.bf16.f32 {%0,%1,%2,%3}, {%4,%5,%6,%7}, {%8,%9}, {%0,%1,%2,%3};"
                 : "+f"(c[0]), "+f"(c[1]), "+f"(c[2]), "+f"(c[3]) : "r"(a[0]), "r"(a[1]), "r"(a[2]), "r"(a[3]), "r"(b0), "r"(b1));
}
__device__ __forceinline__ uint32_t lds32(uint32_t addr) { uint32_t v; asm volatile("ld.shared.u32 %0, [%1];" : "=r"(v) : "r"(addr) : "memory"); return v; }
__device__ __forceinline__ float lds_f32(uint32_t addr) { float v; asm volatile("ld.shared.f32 %0, [%1];" : "=f"(v) : "r"(addr) : "memory"); return v; }
__device__ __forceinline__ float2 lds_f32x2(uint32_t addr) { float2 v; asm volatile("ld.shared.v2.f32 {%0,%1}, [%2];" : "=f"(v.x), "=f"(v.y) : "r"(addr) : "memory"); return v; }
__device__ __forceinline__ float4 lds_f32x4(uint32_t addr) { float4 v; asm volatile("ld.shared.v4.f32 {%0,%1,%2,%3}, [%4];" : "=f"(v.x), "=f"(v.y), "=f"(v.z), "=f"(v.w) : "r"(addr) : "memory"); return v; }
__device__ __forceinline__ uint2 lds64(uint32_t addr) { uint2 v; asm volatile("ld.shared.v2.u32 {%0,%1}, [%2];" : "=r"(v.x), "=r"(v.y) : "r"(addr) : "memory"); return v; }
__device__ __forceinline__ uint4 lds128(uint32_t addr) { uint4 v; asm volatile("ld.shared.v4.u32 {%0,%1,%2,%3}, [%4];" : "=r"(v.x), "=r"(v.y), "=r"(v.z), "=r"(v.w) : "r"(addr) : "memory"); return v; }
__device__ __forceinline__ void sts16(uint32_t addr, uint32_t v) { asm volatile("st.shared.b16 [%0], %1;" ::"r"(addr), "h"((unsigned short)v) : "memory"); }
__device__ __forceinline__ void sts32(uint32_t addr, uint32_t v) { asm volatile("st.shared.u32 [%0], %1;" ::"r"(addr), "r"(v) : "memory"); }
__device__ __forceinline__ void sts_f32(uint32_t addr, float v) { asm volatile("st.shared.f32 [%0], %1;" ::"r"(addr), "f"(v) : "memory"); }
__device__ __forceinline__ void sts_f32x2(uint32_t addr, float a, float b) { asm volatile("st.shared.v2.f32 [%0], {%1,%2};" ::"r"(addr), "f"(a), "f"(b) : "memory"); }
__device__ __forceinline__ void sts128(uint32_t addr, uint4 v) { asm volatile("st.shared.v4.u32 [%0], {%1,%2,%3,%4};" ::"r"(addr), "r"(v.x), "r"(v.y), "r"(v.z), "r"(v.w) : "memory"); }
__device__ __forceinline__ uint4 ldg_relaxed(const uint32_t* p) {
    uint4 v;
    asm volatile("ld.relaxed.gpu.global.v4.u32 {%0,%1,%2,%3}, [%4];" : "=r"(v.x), "=r"(v.y), "=r"(v.z), "=r"(v.w) : "l"(p) : "memory");
    return v;
}
__device__ __forceinline__ void ldg_relaxed_if(bool on, uint4& v, const uint32_t* p) {
    asm volatile("{\n.reg .pred q;\nsetp.ne.u32 q, %5, 0;\n@q ld.relaxed.gpu.global.v4.u32 {%0,%1,%2,%3}, [%4];\n}"
                 : "+r"(v.x), "+r"(v.y), "+r"(v.z), "+r"(v.w) : "l"(p), "r"((uint32_t)on) : "memory");
}
__device__ __forceinline__ void stg_relaxed2_if(bool on, uint32_t* p, uint32_t a, uint32_t b) {
    asm volatile("{\n.reg .pred q;\nsetp.ne.u32 q, %3, 0;\n@q st.relaxed.gpu.global.v2.u32 [%0], {%1,%2};\n}" ::"l"(p), "r"(a), "r"(b), "r"((uint32_t)on) : "memory");
}
__device__ __forceinline__ uint32_t ldg_relaxed32(const uint32_t* p) { uint32_t v; asm volatile("ld.relaxed.gpu.global.u32 %0, [%1];" : "=r"(v) : "l"(p) : "memory"); return v; }
__device__ __forceinline__ void stg_relaxed(uint32_t* p, uint32_t v) { asm volatile("st.relaxed.gpu.global.u32 [%0], %1;" ::"l"(p), "r"(v) : "memory"); }
__device__ __forceinline__ void stg_relaxed2(uint32_t* p, uint32_t a, uint32_t b) { asm volatile("st.relaxed.gpu.global.v2.u32 [%0], {%1,%2};" ::"l"(p), "r"(a), "r"(b) : "memory"); }
__device__ __forceinline__ void stg_zero4(uint32_t* p) { asm volatile("st.relaxed.gpu.global.v4.u32 [%0], {%1,%1,%1,%1};" ::"l"(p), "r"(0u) : "memory"); }
__device__ __forceinline__ bool ready(const uint4& v) { return (v.x != 0u) & (v.y != 0u) & (v.z != 0u) & (v.w != 0u); }
__device__ __forceinline__ uint4 inv4(const uint4& v) { return make_uint4(~v.x, ~v.y, ~v.z, ~v.w); }
__device__ __forceinline__ uint32_t pack_bf(float lo, float hi) {
    uint32_t r;
    asm("cvt.rn.bf16x2.f32 %0, %1, %2;" : "=r"(r) : "f"(hi), "f"(lo));
    return r;
}
__device__ __forceinline__ float bfr(float x) { return __uint_as_float(pack_bf(0.f, x) & 0xffff0000u); }
__device__ __forceinline__ float bf_lo(uint32_t w) { return __uint_as_float(w << 16); }
__device__ __forceinline__ float bf_hi(uint32_t w) { return __uint_as_float(w & 0xffff0000u); }
__device__ __forceinline__ float bf2f(__nv_bfloat16 v) { return __bfloat162float(v); }
__device__ __forceinline__ float ex2(float x) { float y; asm("ex2.approx.ftz.f32 %0, %1;" : "=f"(y) : "f"(x)); return y; }
__device__ __forceinline__ float rcp_fast(float x) { float y; asm("rcp.approx.ftz.f32 %0, %1;" : "=f"(y) : "f"(x)); return y; }
__device__ __forceinline__ float rsqrt_fast(float x) { float y; asm("rsqrt.approx.ftz.f32 %0, %1;" : "=f"(y) : "f"(x)); return y; }
__device__ __forceinline__ float sqrt_fast(float x) { float y; asm("sqrt.approx.f32 %0, %1;" : "=f"(y) : "f"(x)); return y; }
__device__ __forceinline__ uint32_t bf2_add(uint32_t a, uint32_t b) { uint32_t r; asm("add.rn.bf16x2 %0, %1, %2;" : "=r"(r) : "r"(a), "r"(b)); return r; }
__device__ __forceinline__ uint32_t bf2_sub(uint32_t a, uint32_t b) { uint32_t r; asm("sub.rn.bf16x2 %0, %1, %2;" : "=r"(r) : "r"(a), "r"(b)); return r; }
__device__ __forceinline__ uint32_t bf2_mul(uint32_t a, uint32_t b) { uint32_t r; asm("mul.rn.bf16x2 %0, %1, %2;" : "=r"(r) : "r"(a), "r"(b)); return r; }
__device__ __forceinline__ uint32_t gtime32() { uint32_t c; asm volatile("mov.u32 %0, %%globaltimer_lo;" : "=r"(c)); return c; }
__device__ __forceinline__ uint32_t clock32() { uint32_t c; asm volatile("mov.u32 %0, %%clock;" : "=r"(c)); return c; }

__device__ __forceinline__ float warp_sum(float v) {
#pragma unroll
    for (int o = 16; o > 0; o >>= 1) v += __shfl_xor_sync(0xffffffffu, v, o);
    return v;
}

struct Params {
    const __nv_bfloat16 *x, *kc, *vc, *b1, *b2, *c;
    __nv_bfloat16* out;
};

__device__ __forceinline__ void tma2d(uint32_t dst, const CUtensorMap* tm, int x, int y, uint32_t bar) {
    asm volatile("cp.async.bulk.tensor.2d.shared::cluster.global.mbarrier::complete_tx::bytes [%0], [%1, {%2, %3}], [%4];"
                 ::"r"(dst), "l"(tm), "r"(x), "r"(y), "r"(bar) : "memory");
}

__device__ __forceinline__ void tma2d_hint(uint32_t dst, const CUtensorMap* tm, int x, int y, uint32_t bar, uint64_t pol) {
    asm volatile("cp.async.bulk.tensor.2d.shared::cluster.global.mbarrier::complete_tx::bytes.L2::cache_hint [%0], [%1, {%2, %3}], [%4], %5;"
                 ::"r"(dst), "l"(tm), "r"(x), "r"(y), "r"(bar), "l"(pol) : "memory");
}
__device__ __forceinline__ uint32_t flag(float v) { return __float_as_uint(v) | 1u; }
__device__ __forceinline__ uint32_t and3(uint32_t a, uint32_t b, uint32_t c) { uint32_t r; asm("lop3.b32 %0, %1, %2, %3, 0x80;" : "=r"(r) : "r"(a), "r"(b), "r"(c)); return r; }
__device__ __forceinline__ uint32_t* slot_ptr(uint32_t lo) {
    uint32_t* r;
    asm volatile("mov.b64 %0, {%1, %2};" : "=l"(r) : "r"(lo), "r"((uint32_t)((size_t)slot(0, 0) >> 32)));
    return r;
}

__device__ __forceinline__ void load_bfrag(uint32_t vec, int stride, int k0, int g, int t, uint32_t& b0, uint32_t& b1) {
    uint32_t a = vec + (g & 3) * stride + (k0 + 2 * t) * 2;
    b0 = lds32(a);
    b1 = lds32(a + 16);
}

__device__ __forceinline__ void ln_finish(float pivot, float sum, float sumsq, uint32_t& m2, float& rden) {
    float dm = sum * (1.f / D);
    float var = fmaxf(sumsq * (1.f / D) - dm * dm, 0.f);
    float mean = pivot + dm;
    m2 = pack_bf(mean, mean);
    rden = rcp_fast(bfr(sqrt_fast(bfr(bfr(var) + 1e-5f))));
}
__device__ __forceinline__ uint32_t ln_mod_pair(uint32_t xw, uint32_t cw, uint32_t sw, uint32_t m2, float rden) {
    uint32_t d = bf2_sub(xw, m2);
    uint32_t ln = pack_bf(bf_lo(d) * rden, bf_hi(d) * rden);
    return bf2_add(bf2_mul(ln, bf2_add(cw, 0x3f803f80u)), sw);
}
__device__ __forceinline__ uint4 ln_mod4(const uint4& x, const uint4& c, const uint4& s, uint32_t m2, float rden) {
    return make_uint4(ln_mod_pair(x.x, c.x, s.x, m2, rden), ln_mod_pair(x.y, c.y, s.y, m2, rden),
                      ln_mod_pair(x.z, c.z, s.z, m2, rden), ln_mod_pair(x.w, c.w, s.w, m2, rden));
}
__device__ __forceinline__ void acc_stats(const uint4& v, float pv, float& s, float& q) {
    const float a0 = bf_lo(v.x) - pv, a1 = bf_hi(v.x) - pv, a2 = bf_lo(v.y) - pv, a3 = bf_hi(v.y) - pv;
    const float a4 = bf_lo(v.z) - pv, a5 = bf_hi(v.z) - pv, a6 = bf_lo(v.w) - pv, a7 = bf_hi(v.w) - pv;
    s += ((a0 + a1) + (a2 + a3)) + ((a4 + a5) + (a6 + a7));
    q += (fmaf(a0, a0, a1 * a1) + fmaf(a2, a2, a3 * a3)) + (fmaf(a4, a4, a5 * a5) + fmaf(a6, a6, a7 * a7));
}
__device__ __forceinline__ uint32_t* mod_slot(int kind, int j, int b) { return g_mod + (kind * 20 + (j >> 2)) * 64 + b * 16 + (j & 3) * 4; }

template <int N>
__device__ __forceinline__ void poll_n(uint4 (&v)[N], const uint32_t* const* ptr, const bool* on) {
    bool pend[N];
#pragma unroll
    for (int i = 0; i < N; i++) pend[i] = on[i];
    int it = 0;
    while (true) {
#pragma unroll
        for (int i = 0; i < N; i++) if (pend[i]) v[i] = ldg_relaxed(ptr[i]);
        bool any = false;
#pragma unroll
        for (int i = 0; i < N; i++) { pend[i] = pend[i] && !ready(v[i]); any |= pend[i]; }
        if (!__any_sync(0xffffffffu, any)) break;
        if (++it > SPIN_LIMIT) __trap();
    }
#pragma unroll
    for (int i = 0; i < N; i++) v[i] = inv4(v[i]);
}
__device__ __forceinline__ uint4 poll1(const uint32_t* p, bool on) {
    uint4 v[1] = {make_uint4(0, 0, 0, 0)};
    const uint32_t* const ptr[1] = {p};
    const bool o[1] = {on};
    poll_n<1>(v, ptr, o);
    return v[0];
}

__device__ __forceinline__ void gelu_stage(uint32_t sb, int m, int lane) {
    const int g = lane >> 2, b = lane & 3;
    const uint32_t y_ld = pin(sb + SC_Y + m * 256 + lane * 8), s_ld = pin(sb + SC_ST + b * 64);
    const uint32_t h_st = pin(sb + SC_H1 + b * 64 + (g >> 1) * 16 + m * 8 + (g & 1) * 2);
    float a0 = 0.f, b0 = lds_f32(sb + OWN_B1 + (16 * m + g) * 4), a1 = 0.f, b1 = lds_f32(sb + OWN_B1 + (16 * m + g + 8) * 4);
    nbar_sync<NB_AB, 320>();
#pragma unroll
    for (int w = 0; w < 8; w++) {
        const float4 t = lds_f32x4(sb + SC_AB + w * 1024 + m * 512 + lane * 16);
        a0 += t.x; b0 += t.y; a1 += t.z; b1 += t.w;
    }
    nbar_sync<NB_Y, 320>();
    float4 q[4];
    float2 y[8];
#pragma unroll
    for (int i = 0; i < 4; i++) q[i] = lds_f32x4(s_ld + i * 16);
#pragma unroll
    for (int w = 0; w < 8; w++) y[w] = lds_f32x2(y_ld + w * 512);
    const float dm = (((q[0].y + q[0].w) + (q[1].y + q[1].w)) + ((q[2].y + q[2].w) + (q[3].y + q[3].w))) * (1.f / D);
    const float sq = ((q[0].x + q[0].z) + (q[1].x + q[1].z)) + ((q[2].x + q[2].z) + (q[3].x + q[3].z));
    const float r = rsqrt_fast(fmaxf(fmaf(-dm, dm, sq * (1.f / D)), 0.f) + 1e-5f);
    const float y0 = ((y[0].x + y[1].x) + (y[2].x + y[3].x)) + ((y[4].x + y[5].x) + (y[6].x + y[7].x));
    const float y1 = ((y[0].y + y[1].y) + (y[2].y + y[3].y)) + ((y[4].y + y[5].y) + (y[6].y + y[7].y));
    const float u0 = fmaf(r, fmaf(dm, a0, -y0), b0), u1 = fmaf(r, fmaf(dm, a1, -y1), b1);
    const float e0 = ex2(u0 * fmaf(u0 * u0, -0.044715f * 2.302208198144325f, -2.302208198144325f));
    const float e1 = ex2(u1 * fmaf(u1 * u1, -0.044715f * 2.302208198144325f, -2.302208198144325f));
    sts16(h_st, pack_bf(u0 * rcp_fast(1.f + e0), 0.f));
    sts16(h_st + 4, pack_bf(u1 * rcp_fast(1.f + e1), 0.f));
#pragma unroll
    for (int w = 0; w < 8; w++) asm volatile("bar.arrive %0, 96;" ::"r"(NB_O + w) : "memory");
}

struct Roles { bool is_f, is_owner; int f, own; };
__device__ __forceinline__ Roles roles(int cta) {
    Roles r;
    r.f = (cta * 27) >> 6;
    r.is_f = (((cta + 1) * 27) >> 6) != r.f;
    r.is_owner = !r.is_f || r.f % 9 == 4;
    r.own = r.is_f ? 74 + r.f / 9 : cta - r.f;
    return r;
}

__global__ void __launch_bounds__(NTHREADS, 1)
fused_kernel(const Params p, const __grid_constant__ CUtensorMap tm_wmod, const __grid_constant__ CUtensorMap tm_wq,
             const __grid_constant__ CUtensorMap tm_wo, const __grid_constant__ CUtensorMap tm_w1, const __grid_constant__ CUtensorMap tm_w2,
             const __grid_constant__ CUtensorMap tm_v) {
    extern __shared__ __align__(1024) unsigned char smem[];
    const uint32_t sb = smem_u32(smem);
    const int cta = blockIdx.x;
    const int head = cta >> 2, bown = cta & 3;
    const uint32_t bar_full = sb + OFF_BAR, bar_empty = bar_full + NS * 8;
    const uint32_t bar_wm = bar_empty + NS * 8, bar_wq = bar_wm + 8, bar_xfree = bar_wq + 8, bar_wo = bar_xfree + 8  ;
    const uint32_t bar_w1 = bar_wo + 40  , bar_w2 = bar_w1 + 32  , bar_help = bar_w2 + 80, bar_v = bar_help + 8  ;
    const int tid = threadIdx.x, warp = tid >> 5, lane = tid & 31;
    const Roles role = roles(cta);
    const bool is_f = role.is_f, is_owner = role.is_owner;
    const int f = role.f, own = role.own;
    const bool crit = (((cta + 1) * 5) >> 4) != ((cta * 5) >> 4);
    const int mr = cta - ((cta * 5) >> 4);
    const bool late = !crit && mr % 11 != 10;
    const int mc = crit ? (cta * 5) >> 4 : 40 + mr - mr / 11;

    const uint32_t t_start = gtime32();
    PROF_DECL
    PROF(0);
    uint4 xa = make_uint4(0, 0, 0, 0), xb = xa, ca0 = xa, ca1 = xa, xs[3] = {xa, xa, xa};
    uint32_t own0 = 0;
    __nv_bfloat16 own2 = __float2bfloat16(0.f);
    if (warp < 8) {
        xa = *(const uint4*)(p.x + (tid & 3) * D + (tid >> 2) * 8);
        ca0 = ((const uint4*)p.c)[tid];
        if (tid < 64) { xb = *(const uint4*)(p.x + (tid & 3) * D + (64 + (tid >> 2)) * 8); ca1 = ((const uint4*)p.c)[256 + tid]; }
        if (warp < 4) {
#pragma unroll
            for (int i = 0; i < 3; i++) if (lane + 32 * i < 80) xs[i] = ((const uint4*)p.x)[warp * 80 + lane + 32 * i];
        } else if (warp == 4) {
            if (is_owner) own0 = *(const uint32_t*)((lane < 16 ? p.x + (lane >> 2) * D : p.b2) + 8 * own + 2 * (lane & 3));
            if (is_f) own2 = p.b1[32 * f + lane];
        }
    }
    const int rot = (head & 1) * (NITEM / 4);
    const char* const kb = (const char*)(p.kc + ((size_t)(bown * NH + head) * SK + (SK - WIN)) * DH);
    const char* const vb = (const char*)(p.vc + ((size_t)(bown * NH + head) * SK + (SK - WIN)) * DH);
    const uint32_t bar_first = crit ? bar_wm : bar_wq;
    uint64_t pol = 0;
    if (threadIdx.x == 256) {
        mbar_init(bar_first, 1);
        mbar_init(bar_full, 1);
        asm volatile("fence.mbarrier_init.release.cluster;" ::: "memory");
        asm volatile("createpolicy.fractional.L2::evict_first.b64 %0, 1.0;" : "=l"(pol));
        const uint32_t dst = sb + (crit ? X_WM : X_WQ);
        const CUtensorMap* tm = crit ? &tm_wmod : &tm_wq;
        mbar_expect_tx(bar_first, D * 64);
        if (crit) {
#pragma unroll
            for (int r = 0; r < D; r += 160) tma2d(dst + r * 64, tm, 32 * mc, r, bar_first);
        }
        mbar_expect_tx(bar_full, TILE_BYTES);
        bulk_load(sb + OFF_RING, kb + (size_t)rot * TILE_BYTES, TILE_BYTES, bar_full, pol);
        if (!crit) {
            const uint32_t c0 = clock32();
            while (clock32() - c0 < WQ_DELAY) { }
#pragma unroll
            for (int r = 0; r < D; r += 160) tma2d(dst + r * 64, tm, 32 * cta, r, bar_first);
        }
    } else if (threadIdx.x == 0) {
#pragma unroll
        for (int s = 0; s < NS; s++) { if (s) mbar_init(bar_full + s * 8, 1); mbar_init(bar_empty + s * 8, 4); }
        mbar_init(crit ? bar_wq : bar_wm, 1);
        mbar_init(bar_xfree, 1);
#pragma unroll
        for (int i = 0; i < 5; i++) { mbar_init(bar_wo + i * 8, 1); mbar_init(bar_w2 + i * 16, 1); mbar_init(bar_w2 + i * 16 + 8, 1); }
        mbar_init(bar_help, 1);
#pragma unroll
        for (int i = 0; i < 4; i++) { mbar_init(bar_v + i * 8, 1); mbar_init(bar_w1 + i * 8, 1); }
        asm volatile("fence.mbarrier_init.release.cluster;" ::: "memory");
    }
    __syncthreads();

    if (warp == 8) {
        if (lane == 0) {
            int sched = PACE_A - NS * PACE_TAU;
#pragma unroll 1
            for (int t = 1; t <= NITEM; t++) {
                if (t == 1) mbar_wait(bar_full, 0);
                if (t == 2) {
                    mbar_wait(bar_first, 0);
                    if (crit) {
                        mbar_expect_tx(bar_wq, D * 64);
#pragma unroll 1
                        for (int r = 0; r < D; r += 160) tma2d(sb + X_WQ + r * 64, &tm_wq, 32 * cta, r, bar_wq);
                    }
                }
                if (t == 3) {
                    asm volatile("prefetch.tensormap [%0];" ::"l"(&tm_v) : "memory");
                    asm volatile("prefetch.tensormap [%0];" ::"l"(&tm_wo) : "memory");
                    asm volatile("prefetch.tensormap [%0];" ::"l"(&tm_w1) : "memory");
                    asm volatile("prefetch.tensormap [%0];" ::"l"(&tm_w2) : "memory");
                }
                if (t == NS && late) {
                    mbar_wait(bar_full + (NS - INFLIGHT) * 8, 0);
                    mbar_expect_tx(bar_wm, D * 64);
#pragma unroll 1
                    for (int r = 0; r < D; r += 160) tma2d(sb + X_WM + r * 64, &tm_wmod, 32 * mc, r, bar_wm);
                }
                if (t == NITEM) {
                    mbar_wait(bar_xfree, 0);
                    if (WO_GATE <= 2) { mbar_wait(bar_v + (2 - WO_GATE) * 16, 0); mbar_wait(bar_v + (2 - WO_GATE) * 16 + 8, 0); }
                    else mbar_wait(bar_full + ((NITEM - WO_GATE) & (NS - 1)) * 8, ((NITEM - WO_GATE) >> 3) & 1);
#pragma unroll 1
                    for (int i = 0; i < 5; i++) {
                        mbar_expect_tx(bar_wo + i * 8, DH * 64);
                        tma2d(sb + X_WO + i * (DH * 64), &tm_wo, bown * 160 + i * 32, head * DH, bar_wo + i * 8);
                    }
                    if (is_f) {
                        mbar_wait(bar_wo + WF_GATE * 8, 0);
                        { const uint32_t c0 = clock32(); while (clock32() - c0 < WF_DELAY) { } }
#pragma unroll 1
                        for (int i = 0; i < 4; i++) {
                            mbar_expect_tx(bar_w1 + i * 8, 160 * 64);
                            tma2d(sb + X_W1 + i * (160 * 64), &tm_w1, 32 * f, 160 * i, bar_w1 + i * 8);
                        }
#pragma unroll 1
                        for (int i = 0; i < 3; i++) mbar_wait(bar_empty + i * 8, ((NITEM >> 3) - 1) & 1);
                        { const uint32_t c0 = clock32(); while (clock32() - c0 < W2_DELAY) { } }
#pragma unroll 1
                        for (int i = 0; i < 10; i++) {
                            mbar_expect_tx(bar_w2 + i * 8, 4096);
                            tma2d(sb + X_W2 + i * 4096, &tm_w2, 64 * i, 32 * f, bar_w2 + i * 8);
                        }
                    }
                    break;
                }
                const int s = t & (NS - 1);
                if (t >= NS) {
                    mbar_wait(bar_empty + s * 8, ((t >> 3) - 1) & 1);
                    while ((int)(gtime32() - t_start) < sched + t * PACE_TAU) { }
                }
                else if (t >= INFLIGHT) {
                    mbar_wait(bar_full + (t - INFLIGHT) * 8, 0);
                }
                if (t < NITEM - 2) {
                    const int pair = t == NITEM - 3 ? NITEM / 2 - 1 : t >> 1;
                    mbar_expect_tx(bar_full + s * 8, TILE_BYTES);
                    bulk_load(sb + OFF_RING + s * TILE_BYTES, ((t & 1) && t != NITEM - 3 ? vb : kb) + (size_t)((pair + rot) & (NITEM / 2 - 1)) * TILE_BYTES, TILE_BYTES, bar_full + s * 8, pol);
                } else {
                    const int row = (bown * NH + head) * SK + (SK - WIN) + ((t - NITEM / 2 + rot) & (NITEM / 2 - 1)) * TILE_KEYS;
#pragma unroll 1
                    for (int i = 0; i < 2; i++) {
                        const uint32_t bar = bar_v + (2 * (t - (NITEM - 2)) + i) * 8;
                        mbar_expect_tx(bar, TILE_BYTES / 2);
                        tma2d_hint(sb + OFF_RING + s * TILE_BYTES + i * (TILE_BYTES / 2), &tm_v, 64 * i, row, bar, pol);
                    }
                }
            }
        }
        __syncwarp();
    }

    if (warp == 9) {
        int side = 0;
        if (lane == 0) {
            uint32_t best[2] = {~0u, ~0u};
#pragma unroll 1
            for (int i = 0; i < 2 * NPROBE && ((i & 1) || (int)(gtime32() - t_start) < PROBE_END); i++) {
                uint32_t t0 = clock32(), v, t1;
                asm volatile("atom.relaxed.gpu.global.exch.b32 %0, [%1], %2;" : "=r"(v) : "l"(slot(SL_SIDE, i & 1) + cta * 8), "r"(0u) : "memory");
                asm volatile("{\n.reg .pred p;\nsetp.ne.u32 p, %1, 0xffffffff;\nmov.u32 %0, 0;\n@p mov.u32 %0, %%clock;\n}" : "=r"(t1) : "r"(v) : "memory");
                if (i & 1) best[1] = min(best[1], t1 - t0); else best[0] = min(best[0], t1 - t0);
            }
            side = best[1] < best[0];
        }
        side = __shfl_sync(0xffffffffu, side, 0);
        HPROF(1);
        mbar_wait(bar_full + (NS - 1) * 8, 0);
        stg_zero4(slot(SL_O + (cta >> 4), lane >> 4) + (cta & 15) * 64 + (lane & 15) * 4);
        if (is_owner) {
#pragma unroll 1
            for (int i = lane; i < NH * 8; i += 32) stg_zero4(slot(SL_P1 + own, side) + i * 4);
#pragma unroll 1
            for (int i = lane; i < NF * 8; i += 32) stg_zero4(slot(SL_P2 + 2 * own + (i >> 8), side) + (i & 255) * 4);
            if (lane < 8) stg_zero4(slot(SL_X1 + own / 30, lane >> 2) + (own % 30) * 32 + (lane & 3) * 4);
        }
        __threadfence();
        __syncwarp();
        if (lane == 0) stg_relaxed(g_clr + cta, 1u + side);
        HPROF(0);
        HPROF(2);
        while ((int)(gtime32() - t_start) < CLR_CHECK) __nanosleep(1000);
        mbar_wait(bar_xfree, 0);
        {
            uint4 v = make_uint4(1, 1, 1, 1), gv = v, mv[20];
#pragma unroll
            for (int i = 0; i < 20; i++) mv[i] = v;
#pragma unroll 1
            for (int it = 0;; it++) {
                v = ldg_relaxed(g_clr + lane * 4);
                ldg_relaxed_if(is_owner && lane < 8, gv, mod_slot(lane < 4 ? 2 : 5, own, lane & 3));
#pragma unroll
                for (int i = 0; i < 20; i++) ldg_relaxed_if(is_f, mv[i], mod_slot(3, 8 * i + (lane >> 2), lane & 3));
                bool ok = ready(v) && ready(gv);
#pragma unroll
                for (int i = 0; i < 20; i++) ok = ok && ready(mv[i]);
                if (__all_sync(0xffffffffu, ok)) break;
                if (it > SPIN_LIMIT) __trap();
                __nanosleep(2000);
            }
            const uint32_t w[4] = {v.x, v.y, v.z, v.w};
#pragma unroll
            for (int i = 0; i < 4; i++) {
                const Roles r = roles(4 * lane + i);
                if (r.is_owner) {
                    sts32(sb + OFF_TAB1 + r.own * 4, (uint32_t)(size_t)(slot(SL_P1 + r.own, w[i] - 1) + head * 32));
                    sts32(sb + OFF_TAB2 + r.own * 4, (uint32_t)(size_t)(slot(SL_P2 + 2 * r.own + (f >> 5), w[i] - 1) + (f & 31) * 32));
                }
            }
            if (lane == 0) sts32(sb + OFF_SIDE, side);
            if (lane < 8) sts128(sb + OWN_GA + lane * 16, inv4(gv));
            const uint32_t dst = sb + OFF_VA + (lane & 3) * VEC_STRIDE + (lane >> 2) * 16;
#pragma unroll
            for (int i = 0; i < 10; i++) {
                const uint4 c = inv4(mv[10 + i]);
                sts128(dst + i * 128, make_uint4(bf2_add(c.x, 0x3f803f80u), bf2_add(c.y, 0x3f803f80u), bf2_add(c.z, 0x3f803f80u), bf2_add(c.w, 0x3f803f80u)));
                sts128(dst + (OFF_VB - OFF_VA) + i * 128, inv4(mv[i]));
            }
        }
        asm volatile("fence.acq_rel.gpu;" ::: "memory");
        __syncwarp();
        HPROF(3);
        if (lane == 0) mbar_arrive(bar_help);
        {
            const uint32_t* const src = pin(slot(SL_O + (cta >> 4), side) + (cta & 12) * 64 + lane * 4);
            const uint32_t dst = pin(sb + OFF_O + (lane >> 4) * O_STRIDE + (lane & 15) * 16);
            mbar_wait(bar_v + 16, 0);
            mbar_wait(bar_v + 24, 0);
            uint4 v[2];
            const uint32_t* const ptr[2] = {src, src + 128};
            const bool on[2] = {true, true};
            poll_n<2>(v, ptr, on);
            sts128(dst, v[0]);
            sts128(dst + 2 * O_STRIDE, v[1]);
#pragma unroll
            for (int w = 0; w < 8; w++) asm volatile("bar.arrive %0, 64;" ::"r"(NB_O + w) : "memory");
        }
        HPROF(4);
    }
    if (warp >= 8) {
        if (is_f) gelu_stage(sb, warp - 8, lane);
        return;
    }

    const int g = lane >> 2, t4 = lane & 3;
    const int mi = lane >> 3, r8 = lane & 7;

    {
        auto silu4 = [&](const uint4& cv) {
            uint32_t w4[4] = {cv.x, cv.y, cv.z, cv.w};
#pragma unroll
            for (int e = 0; e < 4; e++) {
                float c0 = bf_lo(w4[e]), c1 = bf_hi(w4[e]);
                w4[e] = pack_bf(c0 * rcp_fast(1.f + ex2(-1.4426950408889634f * c0)), c1 * rcp_fast(1.f + ex2(-1.4426950408889634f * c1)));
            }
            return make_uint4(w4[0], w4[1], w4[2], w4[3]);
        };
        if (crit || late) {
            uint4 v = silu4(ca0);
            sts128(sb + OFF_VA + (tid / 80) * VEC_STRIDE + (tid % 80) * 16, v);
            if (tid < 64) { v = silu4(ca1); sts128(sb + OFF_VA + 3 * VEC_STRIDE + (16 + tid) * 16, v); }
        }
        if (warp < 4) {
            float s = 0.f, q = 0.f;
            const float pv = __shfl_sync(0xffffffffu, bf_lo(xs[0].x), 0);
#pragma unroll
            for (int i = 0; i < 3; i++) if (i < 2 || lane < 16) acc_stats(xs[i], pv, s, q);
#pragma unroll
            for (int of = 16; of > 0; of >>= 1) { s += __shfl_xor_sync(0xffffffffu, s, of); q += __shfl_xor_sync(0xffffffffu, q, of); }
            uint32_t m2; float rden;
            ln_finish(pv, s, q, m2, rden);
            if (lane == 0) { sts32(sb + OFF_STAT + warp * 8, m2); sts_f32(sb + OFF_STAT + warp * 8 + 4, rden); }
        } else if (warp == 4) {
            sts32(sb + OWN_X + lane * 4, bf2_add(own0, 0u));
            sts_f32(sb + OWN_B1 + lane * 4, bf2f(own2));
        }
    }
    bar_cons();
    PROF(24);
    uint32_t qf[8][2];
    float o[8][4];
#pragma unroll
    for (int c = 0; c < 8; c++) { o[c][0] = o[c][1] = o[c][2] = o[c][3] = 0.f; }
    float m_run = -INFINITY, l_run = 0.f;
    const bool diag = (t4 == (g >> 1));
    const bool odd = g & 1;
    const uint32_t koff = (warp & 3) * 4096 + (r8 + 8 * (mi & 1)) * 256 + (mi >> 1) * 128 + (r8 << 4);
    const uint32_t voff = TILE_BYTES + (warp & 3) * 4096 + (r8 + 8 * (mi >> 1)) * 256 + (mi & 1) * 128 + (r8 << 4);
    const int src0 = (2 * t4) * 4 + t4, src1 = (2 * t4 + 1) * 4 + t4;
#pragma unroll 1
    for (int step = crit ? 0 : 1; step < 3; step++) {
        if (step < 2 || late) {
            if (step == 1) {
                if (!crit) mbar_wait(bar_wq, 0);
                const uint32_t m2 = lds32(sb + OFF_STAT + (tid & 3) * 8);
                const float rden = lds_f32(sb + OFF_STAT + (tid & 3) * 8 + 4);
                uint4 v[4] = {xa, xa, xa, xa};
                const uint32_t* const ptr[4] = {mod_slot(0, tid >> 2, tid & 3), mod_slot(1, tid >> 2, tid & 3),
                                                mod_slot(0, 64 + ((tid & 63) >> 2), tid & 3), mod_slot(1, 64 + ((tid & 63) >> 2), tid & 3)};
                const bool on[4] = {true, true, tid < 64, tid < 64};
                poll_n<4>(v, ptr, on);
                uint4 h0 = ln_mod4(xa, v[1], v[0], m2, rden);
                sts128(sb + OFF_VB + (tid & 3) * VEC_STRIDE + (tid >> 2) * 16, h0);
                if (tid < 64) {
                    h0 = ln_mod4(xb, v[3], v[2], m2, rden);
                    sts128(sb + OFF_VB + (tid & 3) * VEC_STRIDE + (64 + (tid >> 2)) * 16, h0);
                }
            }
            mbar_wait(step == 1 ? bar_wq : bar_wm, 0);
            bar_cons();
            const uint32_t strip = sb + (step == 1 ? X_WQ : X_WM), vec = sb + (step == 1 ? OFF_VB : OFF_VA);
            float acc[2][4];
#pragma unroll
            for (int m = 0; m < 2; m++) { acc[m][0] = acc[m][1] = acc[m][2] = acc[m][3] = 0.f; }
#pragma unroll
            for (int i = 0; i < 5; i++) {
                int k0 = (warp * 5 + i) * 16;
                uint32_t b0, b1;
                load_bfrag(vec, VEC_STRIDE, k0, g, t4, b0, b1);
                int krow = k0 + r8 + 8 * (mi >> 1);
#pragma unroll
                for (int m = 0; m < 2; m++) {
                    uint32_t a[4];
                    int ch = 2 * m + (mi & 1);
                    ldsm4t(a, strip + krow * 64 + ((ch ^ ((krow >> 1) & 3)) << 4));
                    mma16816(acc[m], a, b0, b1);
                }
            }
            if (t4 < 2) {
#pragma unroll
                for (int m = 0; m < 2; m++) {
                    sts_f32x2(sb + OFF_RED + ((warp * 32 + m * 16 + g) * 4 + 2 * t4) * 4, acc[m][0], acc[m][1]);
                    sts_f32x2(sb + OFF_RED + ((warp * 32 + m * 16 + g + 8) * 4 + 2 * t4) * 4, acc[m][2], acc[m][3]);
                }
            }
            bar_cons();
            if (tid < 128) {
                float v = 0.f;
#pragma unroll
                for (int w = 0; w < 8; w++) v += lds_f32(sb + OFF_RED + (w * 128 + tid) * 4);
                float vn = __shfl_down_sync(0xffffffffu, v, 4);
                uint32_t* dst = step == 1 ? g_q + ((cta & ~3) + (tid & 3)) * 64 + bown * 16 + (tid >> 3) : g_mod + mc * 64 + (tid & 3) * 16 + (tid >> 3);
                if (!((tid >> 2) & 1)) stg_relaxed(dst, ~pack_bf(v, vn));
            }
        }
        if (step == 0) continue;
        if (step == 1) {
            if (warp == 0) {
                uint4 v = poll1(g_q + cta * 64 + (lane & 15) * 4, lane < 16);
                if (lane < 16) {
                    sts128(sb + OFF_Q + lane * 16, v);
                    stg_zero4(g_q + cta * 64 + lane * 4);
                }
            }
            bar_cons();
            PROF(4);

#pragma unroll
            for (int c = 0; c < 8; c++) {
                qf[c][0] = lds32(sb + OFF_Q + (((c ^ g) * 4 + t4) << 2));
                qf[c][1] = lds32(sb + OFF_Q + 128 + (((c ^ g) * 4 + t4) << 2));
            }
        } else {
            bar_cons();
            if (tid == 0) mbar_arrive(bar_xfree);
        }
#pragma unroll 1
        for (int j = (step == 1 ? 0 : SEG_J) + (warp >> 2); j < (step == 1 ? SEG_J : NITEM / 2 - 2); j += 2) {
            const int s = (2 * j) & (NS - 1);
            const uint32_t par = (j >> 2) & 1;
            mbar_wait(bar_full + s * 8, par);
            const uint32_t base = sb + OFF_RING + s * TILE_BYTES;
            float sa[4] = {0.f, 0.f, 0.f, 0.f}, sb2[4] = {0.f, 0.f, 0.f, 0.f};
#pragma unroll
            for (int c = 0; c < 8; c += 2) {
                uint32_t a[4], a2[4];
                ldsm4(a, (base + koff) ^ (c << 4));
                ldsm4(a2, (base + koff) ^ ((c + 1) << 4));
                mma16816(sa, a, qf[c][0], qf[c][1]);
                mma16816(sb2, a2, qf[c + 1][0], qf[c + 1][1]);
            }
            const uint32_t sw = pack_bf(odd ? sa[1] + sb2[1] : sa[0] + sb2[0], odd ? sa[3] + sb2[3] : sa[2] + sb2[2]);
            const uint32_t sv = pack_bf(bf_lo(sw) * 0.08838834764831845f, bf_hi(sw) * 0.08838834764831845f);
            const float s0 = bf_lo(sv) * 1.4426950408889634f, s1 = bf_hi(sv) * 1.4426950408889634f;
            float m_new = fmaxf(m_run, fmaxf(s0, s1));
            const bool grow = __any_sync(0xffffffffu, (diag && (m_new > m_run)));
            if (lane == 0) mbar_arrive(bar_empty + s * 8);
            if (grow) {
                float al = ex2(m_run - m_new);
                float a0 = __shfl_sync(0xffffffffu, al, src0), a1 = __shfl_sync(0xffffffffu, al, src1);
#pragma unroll
                for (int c = 0; c < 8; c++) { o[c][0] *= a0; o[c][1] *= a1; o[c][2] *= a0; o[c][3] *= a1; }
                l_run *= al;
                m_run = m_new;
            }
            uint32_t pw = pack_bf(ex2(s0 - m_run), ex2(s1 - m_run));
            l_run += bf_lo(pw) + bf_hi(pw);
            uint32_t b0 = odd ? (pw << 16) : (pw & 0xffffu);
            uint32_t b1 = odd ? (pw & 0xffff0000u) : (pw >> 16);
            if (!diag) { b0 = 0u; b1 = 0u; }
            mbar_wait(bar_full + (s + 1) * 8, par);
#pragma unroll
            for (int c = 0; c < 8; c++) {
                uint32_t a[4];
                ldsm4t(a, (base + voff) ^ (c << 4));
                mma16816(o[c], a, b0, b1);
            }
            __syncwarp();
            if (lane == 0) mbar_arrive(bar_empty + (s + 1) * 8);
        }
    }
    PROF(5);
    float acc[4][4];
    uint32_t pa[8][2];
    float rinv;
    {
        const int s = 4 + (warp >> 2);
        mbar_wait(bar_full + s * 8, 1);
        const uint32_t base = sb + OFF_RING + s * TILE_BYTES;
        float sa[4] = {0.f, 0.f, 0.f, 0.f}, sb2[4] = {0.f, 0.f, 0.f, 0.f};
#pragma unroll
        for (int c = 0; c < 8; c += 2) {
            uint32_t a[4], a2[4];
            ldsm4(a, (base + koff) ^ (c << 4));
            ldsm4(a2, (base + koff) ^ ((c + 1) << 4));
            mma16816(sa, a, qf[c][0], qf[c][1]);
            mma16816(sb2, a2, qf[c + 1][0], qf[c + 1][1]);
        }
        const uint32_t sw = pack_bf(odd ? sa[1] + sb2[1] : sa[0] + sb2[0], odd ? sa[3] + sb2[3] : sa[2] + sb2[2]);
        const uint32_t sv = pack_bf(bf_lo(sw) * 0.08838834764831845f, bf_hi(sw) * 0.08838834764831845f);
        const float s0 = bf_lo(sv) * 1.4426950408889634f, s1 = bf_hi(sv) * 1.4426950408889634f;
        int mi_ = __float_as_int(diag ? fmaxf(m_run, fmaxf(s0, s1)) : -INFINITY);
        mi_ ^= (mi_ >> 31) & 0x7fffffff;
        mi_ = __reduce_max_sync(0xffffffffu, mi_);
        mi_ ^= (mi_ >> 31) & 0x7fffffff;
        if (lane == 0) sts32(sb + OFF_ML + warp * 4, mi_);
        bar_cons();
        const float4 m0 = lds_f32x4(sb + OFF_ML), m1 = lds_f32x4(sb + OFF_ML + 16);
        const float mx = fmaxf(fmaxf(fmaxf(m0.x, m0.y), fmaxf(m0.z, m0.w)), fmaxf(fmaxf(m1.x, m1.y), fmaxf(m1.z, m1.w)));
        const float scl = ex2(m_run - mx);
        const uint32_t pw = pack_bf(ex2(s0 - mx), ex2(s1 - mx));
        if (diag) { sts16(sb + SC_P + (warp * 16 + g) * 2, pw); sts16(sb + SC_P + (warp * 16 + g + 8) * 2, pw >> 16); }
        const float lw = warp_sum(diag ? fmaf(l_run, scl, bf_lo(pw) + bf_hi(pw)) : 0.f);
        const float a0 = __shfl_sync(0xffffffffu, scl, src0), a1 = __shfl_sync(0xffffffffu, scl, src1);
        float v[8], u[8];
#pragma unroll
        for (int c = 0; c < 8; c++) {
            v[c] = a0 * o[c][0] + a1 * o[c ^ 1][1];
            u[c] = a0 * o[c][2] + a1 * o[c ^ 1][3];
        }
#pragma unroll
        for (int c = 0; c < 8; c++) {
            if (!(c & 2)) {
                v[c] += __shfl_xor_sync(0xffffffffu, v[c ^ 2], 1);
                u[c] += __shfl_xor_sync(0xffffffffu, u[c ^ 2], 1);
            }
        }
#pragma unroll
        for (int c = 0; c < 2; c++) {
            v[c] += __shfl_xor_sync(0xffffffffu, v[c ^ 4], 2);
            u[c] += __shfl_xor_sync(0xffffffffu, u[c ^ 4], 2);
        }
        const uint32_t dst = sb + SC_OP + (warp * 128 + 16 * t4 + g) * 4;
        sts_f32(dst, v[0]); sts_f32(dst + 32, v[1]); sts_f32(dst + 256, u[0]); sts_f32(dst + 288, u[1]);
        if (lane == 0) sts_f32(sb + OFF_ML + 32 + warp * 4, lw);
        mbar_wait(bar_help, 0);
        bar_cons();
        const float4 l0 = lds_f32x4(sb + OFF_ML + 32), l1 = lds_f32x4(sb + OFF_ML + 48);
        rinv = rcp_fast(((l0.x + l0.y) + (l0.z + l0.w)) + ((l1.x + l1.y) + (l1.z + l1.w)));
#pragma unroll
        for (int i = 0; i < 4; i++) acc[i][0] = acc[i][1] = acc[i][2] = acc[i][3] = 0.f;
#pragma unroll
        for (int w = 0; w < 8; w++) {
            const float2 x0 = lds_f32x2(sb + SC_OP + (w * 128 + 16 * warp + 2 * t4) * 4), x1 = lds_f32x2(sb + SC_OP + (w * 128 + 16 * warp + 8 + 2 * t4) * 4);
            acc[2 * (w & 1)][0] += x0.x; acc[2 * (w & 1)][1] += x0.y;
            acc[2 * (w & 1) + 1][0] += x1.x; acc[2 * (w & 1) + 1][1] += x1.y;
        }
#pragma unroll
        for (int ks = 0; ks < 8; ks++) { pa[ks][0] = lds32(sb + SC_P + (8 * ks + t4) * 4); pa[ks][1] = lds32(sb + SC_P + (8 * ks + 4 + t4) * 4); }
    }
    PROF(20);
    const int mt = warp < 2 ? warp : warp + 2;
    {
        const uint32_t va = pin(sb + OFF_RING + 6 * TILE_BYTES + (warp >> 2) * (TILE_BYTES / 2) + (8 * (mi & 1) + r8) * 128 + (((2 * (warp & 3) + (mi >> 1)) ^ r8) << 4));
        const uint32_t vbar = pin(bar_v + (warp >> 2) * 8);
        uint32_t* const o_dst = pin(slot(SL_O + (cta >> 4), g) + (cta & 15) * 64 + warp * 8 + 2 * t4);
#pragma unroll
        for (int tl = 0; tl < 2; tl++) {
            mbar_wait(vbar + tl * 16, 0);
            uint32_t r[4][4];
#pragma unroll
            for (int ks = 0; ks < 4; ks++) ldsm4t(r[ks], va + tl * TILE_BYTES + ks * 2048);
#pragma unroll
            for (int ks = 0; ks < 4; ks++) {
                const uint32_t a[4] = {pa[4 * tl + ks][0], 0u, pa[4 * tl + ks][1], 0u};
                mma16816(acc[2 * (ks & 1)], a, r[ks][0], r[ks][1]);
                mma16816(acc[2 * (ks & 1) + 1], a, r[ks][2], r[ks][3]);
            }
        }
        stg_relaxed2_if(g < 2, o_dst, ~pack_bf((acc[0][0] + acc[2][0]) * rinv, (acc[0][1] + acc[2][1]) * rinv),
                        ~pack_bf((acc[1][0] + acc[3][0]) * rinv, (acc[1][1] + acc[3][1]) * rinv));
    }
    PROF(7);
    const int side = lds32(sb + OFF_SIDE);
    const uint32_t red_st = pin(sb + SC_E4 + ((warp * 4 + 2 * ((lane >> 3) & 1) + (lane >> 4)) * 8 + (lane & 7)) * 4);
    const uint32_t red_ld = pin(sb + SC_E4 + (lane & 15) * 8);
    const uint32_t* const in1 = pin(slot(SL_P1 + own, side) + tid * 4);
    const uint32_t* const in2a = pin(slot(SL_P2 + 2 * own, side) + tid * 4);
    const uint32_t* const in2b = pin(slot(SL_P2 + 2 * own + 1, side) + tid * 4);
    uint32_t* const x1_dst = pin(slot(SL_X1 + own / 30, lane >> 4) + (own % 30) * 32 + (lane & 15));
    const uint32_t xw = lds32(sb + OWN_X + (lane & 15) * 4), ga_w = lds32(sb + OWN_GA + (lane & 15) * 4);
    uint32_t cs[15];
    uint32_t* dst2[10];
    uint32_t w2a[5];
#pragma unroll
    for (int j = 0; j < 10; j++) cs[j] = lds32(sb + OFF_VA + ((g & 1) * 4 + (g >> 1)) * VEC_STRIDE + warp * 160 + t4 * 4 + j * 16);
#pragma unroll
    for (int i = 0; i < 5; i++) {
        cs[10 + i] = lds32(sb + OFF_VA + (g >> 1) * VEC_STRIDE + warp * 160 + (g & 1) * 16 + t4 * 4 + i * 32);
        const uint2 t = lds64(sb + OFF_TAB2 + warp * 40 + i * 8);
        dst2[2 * i] = slot_ptr(t.x + g * 16 + t4 * 8);
        dst2[2 * i + 1] = slot_ptr(t.y + g * 16 + t4 * 8);
        const int cc = 2 * (warp * 5 + i) + (mi & 1);
        w2a[i] = pin(sb + X_W2 + (cc >> 3) * 4096 + (r8 + 8 * (mi >> 1)) * 128 + (((cc & 7) ^ r8) << 4));
    }
    const uint32_t piv = lds32(sb + OFF_STAT + (g >> 1) * 8);
    const uint32_t* const xin = pin(slot(SL_X1 + warp / 3, side) + ((warp % 3) * 10 + (g & 1)) * 32 + (g >> 1) * 4 + t4);
    const uint32_t w1a = pin(sb + X_W1 + (warp * 80 + r8 + 8 * (mi >> 1)) * 64 + (((mi & 1) ^ ((r8 >> 1) & 3)) << 4));
    const uint32_t w1bar = pin(bar_w1 + (warp >> 1) * 8), w2bar = pin(bar_w2 + (warp + (warp >> 2)) * 8);
    const uint32_t wbar = pin(NB_O + warp);
    const uint32_t ab_st = pin(sb + SC_AB + warp * 1024 + lane * 16), y_st = pin(sb + SC_Y + warp * 512 + lane * 8), s_st = pin(sb + SC_ST + (t4 * 8 + warp) * 8);
    const uint32_t h_ld = pin(sb + SC_H1 + ((g & 3) ^ (2 * (f & 1) + ((f >> 1) & 1))) * 64 + t4 * 16);
    {
        const int kap = 2 * (head & 1) + ((head >> 1) & 1);
        const uint32_t wa = pin(sb + X_WO + (mt >> 1) * (DH * 64) + (r8 + 8 * (mi >> 1)) * 64 + ((((mt & 1) * 2 + (mi & 1)) ^ ((r8 >> 1) & 3)) << 4));
        const uint32_t oa = pin(sb + OFF_O + ((g & 3) ^ kap) * O_STRIDE + t4 * 8);
        uint32_t* dst[4];
#pragma unroll
        for (int i = 0; i < 2; i++) {
            const uint2 t = lds64(sb + OFF_TAB1 + (bown * 20 + 2 * mt + (warp < 2 ? 4 * i : 0)) * 4);
            dst[2 * i] = slot_ptr(t.x + g * 16 + t4 * 8);
            dst[2 * i + 1] = slot_ptr(t.y + g * 16 + t4 * 8);
        }
        PROF(6);
        uint32_t wf[8][4], wg[8][4];
        mbar_wait(bar_wo + (mt >> 1) * 8, 0);
#pragma unroll
        for (int ks = 0; ks < 8; ks++) ldsm4t(wf[ks], wa + ks * 1024);
        if (warp < 2) {
            mbar_wait(bar_wo + 8, 0);
#pragma unroll
            for (int ks = 0; ks < 8; ks++) ldsm4t(wg[ks], wa + DH * 64 + ks * 1024);
        }
        asm volatile("bar.sync %0, 64;" ::"r"(wbar) : "memory");
        PROF(8);
        uint2 ob[8];
#pragma unroll
        for (int ks = 0; ks < 8; ks++) ob[ks] = lds64(oa + ks * 32);
        float c0[4] = {0.f, 0.f, 0.f, 0.f}, c1[4] = {0.f, 0.f, 0.f, 0.f};
        if (warp < 2) {
            float c2[4] = {0.f, 0.f, 0.f, 0.f}, c3[4] = {0.f, 0.f, 0.f, 0.f};
#pragma unroll
            for (int ks = 0; ks < 8; ks += 2) {
                mma16816(c0, wf[ks], ob[ks].x, ob[ks].y);
                mma16816(c2, wg[ks], ob[ks].x, ob[ks].y);
                mma16816(c1, wf[ks + 1], ob[ks + 1].x, ob[ks + 1].y);
                mma16816(c3, wg[ks + 1], ob[ks + 1].x, ob[ks + 1].y);
            }
            stg_relaxed2_if(t4 < 2, dst[2], flag(c2[0] + c3[0]), flag(c2[1] + c3[1]));
            stg_relaxed2_if(t4 < 2, dst[3], flag(c2[2] + c3[2]), flag(c2[3] + c3[3]));
        } else {
#pragma unroll
            for (int ks = 0; ks < 8; ks += 2) {
                mma16816(c0, wf[ks], ob[ks].x, ob[ks].y);
                mma16816(c1, wf[ks + 1], ob[ks + 1].x, ob[ks + 1].y);
            }
        }
        stg_relaxed2_if(t4 < 2, dst[0], flag(c0[0] + c1[0]), flag(c0[1] + c1[1]));
        stg_relaxed2_if(t4 < 2, dst[1], flag(c0[2] + c1[2]), flag(c0[3] + c1[3]));
    }
    PROF(9);
    uint32_t x1w = 0;
    if (is_owner) {
        uint4 v;
        for (int it = 0;; it++) {
            v = ldg_relaxed(in1);
            if (__all_sync(0xffffffffu, and3(and3(v.x, v.y, v.z), v.w, 1u))) break;
            if (it > SPIN_LIMIT) __trap();
        }
        PROF(11);
        const float s0 = __uint_as_float(v.x) + __shfl_xor_sync(0xffffffffu, __uint_as_float(v.z), 8);
        const float s1 = __uint_as_float(v.y) + __shfl_xor_sync(0xffffffffu, __uint_as_float(v.w), 8);
        sts_f32(red_st, s0 + __shfl_xor_sync(0xffffffffu, s1, 16));
        if (warp == 0) {
            nbar_sync<NB_E4, 256>();
            float2 a[8];
#pragma unroll
            for (int w = 0; w < 8; w++) a[w] = lds_f32x2(red_ld + w * 128);
            const uint32_t aw = pack_bf(((a[0].x + a[1].x) + (a[2].x + a[3].x)) + ((a[4].x + a[5].x) + (a[6].x + a[7].x)),
                                        ((a[0].y + a[1].y) + (a[2].y + a[3].y)) + ((a[4].y + a[5].y) + (a[6].y + a[7].y)));
            x1w = bf2_add(xw, bf2_mul(ga_w, aw));
            stg_relaxed(x1_dst, x1w ^ 0x80008000u);
        } else {
            nbar_arrive<NB_E4, 256>();
        }
    }
    PROF(12);
    if (is_f) {
        uint32_t f1[5][2][4], f2[5][2][4];
        uint32_t d[6];
        auto load_x1 = [&] {
#pragma unroll
            for (int i = 0; i < 5; i++) d[i] = ldg_relaxed32(xin + i * 64);
        };
        auto have_x1 = [&] { return __all_sync(0xffffffffu, __vimin3_u32(__vimin3_u32(d[0], d[1], d[2]), d[3], d[4]) != 0u); };
        mbar_wait(w1bar, 0);
        load_x1();
        {
#pragma unroll
            for (int i = 0; i < 5; i++) { ldsm4t(f1[i][0], w1a + i * 1024); ldsm4t(f1[i][1], (w1a ^ 32) + i * 1024); }
            float c[2][4];
#pragma unroll
            for (int m = 0; m < 2; m++) c[m][0] = c[m][1] = c[m][2] = c[m][3] = 0.f;
#pragma unroll
            for (int i = 0; i < 5; i++) { mma16816(c[0], f1[i][0], cs[2 * i], cs[2 * i + 1]); mma16816(c[1], f1[i][1], cs[2 * i], cs[2 * i + 1]); }
#pragma unroll
            for (int i = 0; i < 5; i++) { cs[2 * i] = pin(odd ? 0u : cs[10 + i]); cs[2 * i + 1] = pin(odd ? cs[10 + i] : 0u); }
#pragma unroll
            for (int m = 0; m < 2; m++) sts128(ab_st + m * 512, make_uint4(__float_as_uint(c[m][0]), __float_as_uint(c[m][1]), __float_as_uint(c[m][2]), __float_as_uint(c[m][3])));
            nbar_arrive<NB_AB, 320>();
            d[0] |= __float_as_uint(c[1][3]) & (side >> 1);
        }
        PROF(10);
#pragma unroll 1
        for (int it = 0; !have_x1(); it++) {
            load_x1();
            if (it > SPIN_LIMIT) __trap();
        }
        PROF(13);
        {
            float y[2][4], st[4] = {0.f, 0.f, 0.f, 0.f};
#pragma unroll
            for (int m = 0; m < 2; m++) y[m][0] = y[m][1] = y[m][2] = y[m][3] = 0.f;
#pragma unroll
            for (int i = 0; i < 5; i++) d[i] = bf2_add(d[i], piv);
            d[5] = 0u;
#pragma unroll
            for (int i = 0; i < 5; i++) {
                if (i < 3) {
                    const uint32_t a[4] = {d[2 * i], 0x3f803f80u, d[2 * i + 1], 0x3f803f80u};
                    mma16816(st, a, d[2 * i], d[2 * i + 1]);
                }
                const uint32_t y0 = bf2_mul(d[i], cs[2 * i]), y1 = bf2_mul(d[i], cs[2 * i + 1]);
                mma16816(y[0], f1[i][0], y0, y1);
                mma16816(y[1], f1[i][1], y0, y1);
            }
            const float q = odd ? st[1] : st[0];
            const float q2 = q + __shfl_xor_sync(0xffffffffu, q, 4);
            if (diag && !odd) sts_f32x2(s_st, q2, st[2] + st[3]);
#pragma unroll
            for (int m = 0; m < 2; m++) sts_f32x2(y_st + m * 256, y[m][0] + y[m][1], y[m][2] + y[m][3]);
        }
        nbar_arrive<NB_Y, 320>();
        PROF(14);
        mbar_wait(w2bar, 0);
        mbar_wait(w2bar + 8, 0);
#pragma unroll
        for (int i = 0; i < 5; i++) { ldsm4t(f2[i][0], w2a[i]); ldsm4t(f2[i][1], w2a[i] + 2048); }
        asm volatile("bar.sync %0, 96;" ::"r"(wbar) : "memory");
        PROF(15);
        {
            const uint4 hb = lds128(h_ld);
            float c[5][4];
#pragma unroll
            for (int i = 0; i < 7; i++) {
                if (i < 5) { c[i][0] = c[i][1] = c[i][2] = c[i][3] = 0.f; mma16816(c[i], f2[i][0], hb.x, hb.y); }
                if (i > 0 && i < 6) mma16816(c[i - 1], f2[i - 1][1], hb.z, hb.w);
                if (i > 1) {
                    stg_relaxed2_if(t4 < 2, dst2[2 * i - 4], flag(c[i - 2][0]), flag(c[i - 2][1]));
                    stg_relaxed2_if(t4 < 2, dst2[2 * i - 3], flag(c[i - 2][2]), flag(c[i - 2][3]));
                }
            }
        }
    }
    PROF(16);
    if (is_owner) {
        uint32_t* const dst = pin((uint32_t*)(p.out + ((lane >> 2) & 3) * D + 8 * own) + t4);
        const uint32_t b2w = lds32(sb + OWN_B2 + (lane & 15) * 4), gb_w = lds32(sb + OWN_GB + (lane & 15) * 4);
        const bool two = tid < NF * 8 - 256;
        uint4 v, w = make_uint4(1, 1, 1, 1);
        for (int it = 0;; it++) {
            ldg_relaxed_if(two, w, in2b);
            v = ldg_relaxed(in2a);
            if (__all_sync(0xffffffffu, and3(and3(v.x, v.y, v.z), and3(v.w, w.x, w.y), and3(w.z, w.w, 1u)))) break;
            if (it > SPIN_LIMIT) __trap();
        }
        PROF(17);
        const float s0 = (__uint_as_float(v.x) + __uint_as_float(w.x)) + __shfl_xor_sync(0xffffffffu, __uint_as_float(v.z) + __uint_as_float(w.z), 8);
        const float s1 = (__uint_as_float(v.y) + __uint_as_float(w.y)) + __shfl_xor_sync(0xffffffffu, __uint_as_float(v.w) + __uint_as_float(w.w), 8);
        sts_f32(red_st + (SC_E6 - SC_E4), s0 + __shfl_xor_sync(0xffffffffu, s1, 16));
        nbar_sync<NB_E6, 256>();
        if (warp == 0) {
            float2 a[8];
#pragma unroll
            for (int i = 0; i < 8; i++) a[i] = lds_f32x2(red_ld + (SC_E6 - SC_E4) + i * 128);
            const uint32_t aw = pack_bf(((a[0].x + a[1].x) + (a[2].x + a[3].x)) + ((a[4].x + a[5].x) + (a[6].x + a[7].x)),
                                        ((a[0].y + a[1].y) + (a[2].y + a[3].y)) + ((a[4].y + a[5].y) + (a[6].y + a[7].y)));
            const uint32_t r = bf2_add(x1w, bf2_mul(gb_w, bf2_add(aw, b2w)));
            if (lane < 16) asm volatile("st.global.u32 [%0], %1;" ::"l"(dst), "r"(r) : "memory");
        }
        if (tid >= 32 && tid < 56) stg_zero4(mod_slot((tid - 32) >> 2, own, tid & 3));
    }
    if (tid == 96) stg_relaxed(g_clr + cta, 0u);
    PROF(18);
    PROF_DUMP;
}

typedef CUresult (*EncodeFn)(CUtensorMap*, CUtensorMapDataType, cuuint32_t, void*, const cuuint64_t*, const cuuint64_t*, const cuuint32_t*,
                             const cuuint32_t*, CUtensorMapInterleave, CUtensorMapSwizzle, CUtensorMapL2promotion, CUtensorMapFloatOOBfill);

static CUtensorMap make_map(EncodeFn enc, const void* ptr, int cols, int rows, int box_cols, int box_rows, CUtensorMapSwizzle sw) {
    CUtensorMap m;
    cuuint64_t dims[2] = {(cuuint64_t)cols, (cuuint64_t)rows};
    cuuint64_t strides[1] = {(cuuint64_t)cols * 2};
    cuuint32_t box[2] = {(cuuint32_t)box_cols, (cuuint32_t)box_rows};
    cuuint32_t es[2] = {1, 1};
    enc(&m, CU_TENSOR_MAP_DATA_TYPE_BFLOAT16, 2, const_cast<void*>(ptr), dims, strides, box, es, CU_TENSOR_MAP_INTERLEAVE_NONE, sw,
        CU_TENSOR_MAP_L2_PROMOTION_NONE, CU_TENSOR_MAP_FLOAT_OOB_FILL_NONE);
    return m;
}

}

extern "C" void kernel_launch(void* const* d_in, const int* in_sizes, int n_in, void* d_out, int out_size) {
    (void)in_sizes; (void)n_in; (void)out_size;
    static EncodeFn enc = nullptr;
    if (!enc) {
        void* fn = nullptr;
        cudaDriverEntryPointQueryResult qr;
        cudaGetDriverEntryPoint("cuTensorMapEncodeTiled", &fn, cudaEnableDefault, &qr);
        enc = (EncodeFn)fn;
        cudaFuncSetAttribute(fused_kernel, cudaFuncAttributeMaxDynamicSharedMemorySize, SMEM_BYTES);
    }
    Params p;
    p.x = (const __nv_bfloat16*)d_in[0];
    p.kc = (const __nv_bfloat16*)d_in[1];
    p.vc = (const __nv_bfloat16*)d_in[2];
    p.b1 = (const __nv_bfloat16*)d_in[7];
    p.b2 = (const __nv_bfloat16*)d_in[9];
    p.c = (const __nv_bfloat16*)d_in[10];
    p.out = (__nv_bfloat16*)d_out;
    CUtensorMap tm_wmod = make_map(enc, d_in[11], NMOD, D, 32, 160, CU_TENSOR_MAP_SWIZZLE_64B);
    CUtensorMap tm_wq = make_map(enc, d_in[3], NH * DH, D, 32, 160, CU_TENSOR_MAP_SWIZZLE_64B);
    CUtensorMap tm_wo = make_map(enc, d_in[4], D, NH * DH, 32, 128, CU_TENSOR_MAP_SWIZZLE_64B);
    CUtensorMap tm_w1 = make_map(enc, d_in[6], FF, D, 32, 160, CU_TENSOR_MAP_SWIZZLE_64B);
    CUtensorMap tm_w2 = make_map(enc, d_in[8], D, FF, 64, 32, CU_TENSOR_MAP_SWIZZLE_128B);
    CUtensorMap tm_v = make_map(enc, d_in[2], DH, NB * NH * SK, 64, TILE_KEYS, CU_TENSOR_MAP_SWIZZLE_128B);
    fused_kernel<<<NCTA, NTHREADS, SMEM_BYTES>>>(p, tm_wmod, tm_wq, tm_wo, tm_w1, tm_w2, tm_v);
}
```

```cpp
#include <cuda_runtime.h>
#include <cuda.h>
#include <cuda_bf16.h>
#include <stdint.h>

namespace {

constexpr int NB = 4, D = 640, NH = 32, DH = 128, SK = 8192, WIN = 2048, FF = 1728, NMOD = 6 * D;
constexpr int NCTA = 128;
constexpr int NOWN = 80;
constexpr int NF = 54;
constexpr int NTHREADS = 320;
constexpr int TILE_KEYS = 64;
constexpr int TILE_BYTES = TILE_KEYS * DH * 2;
constexpr int NITEM = 2 * WIN / TILE_KEYS;
constexpr int NS = 8;
constexpr int NMODC = 120;
constexpr int SPIN_LIMIT = 1 << 18;
#define INFLIGHT 3
#define PACE_A 8000
#define PACE_TAU 635
#define WQ_DELAY 400
#define WO_GATE 2
#define WF_GATE 2
#define WF_DELAY 0
#define W2_DELAY 0
#define WF_ALL 0
#define NPROBE 8
#define PROBE_END 10000
#define LAT_T 2100
#define WO_T -1100
#define WO_S 200
#define W1_T 900
#define W2_T 1200
#define PH_GAIN 8
#define LAT_FROM 99
#define LAT_END 0
#define PH_FIRST 20
#define PH_LAG 5
#define W1_S 0
#define W2_S 0
#define PF_END 14
#define FIRST_TOP 2
#define CLR_CHECK 28000
constexpr int SEG_J = 8;

constexpr int OFF_RING = 0;
constexpr int OFF_X = OFF_RING + NS * TILE_BYTES;
constexpr int X_WM = OFF_X;
constexpr int X_WQ = OFF_X + D * 64;
constexpr int X_WO = OFF_X;
constexpr int X_W1 = X_WO + 5 * DH * 64;
constexpr int X_END = X_W1 + D * 64;
constexpr int X_W2 = OFF_RING;
static_assert(X_WQ + D * 64 <= X_END, "prologue weights must fit");
constexpr int VEC_STRIDE = 1296;
constexpr int OFF_VA = X_END;
constexpr int OFF_VB = OFF_VA + 4 * VEC_STRIDE;
constexpr int OFF_RED = OFF_VB + 4 * VEC_STRIDE;
constexpr int OFF_ML = OFF_RED + 4096;
constexpr int O_STRIDE = 288;
constexpr int OFF_O = OFF_ML + 64;
constexpr int OFF_Q = OFF_O + 4 * O_STRIDE;
constexpr int OFF_OWN = OFF_Q + 256;
constexpr int OWN_X = OFF_OWN, OWN_B2 = OWN_X + 64, OWN_GA = OWN_B2 + 64, OWN_GB = OWN_GA + 64, OWN_B1 = OWN_GB + 64;
constexpr int OFF_STAT = OWN_B1 + 128;
constexpr int OFF_TAB1 = OFF_STAT + 32;
constexpr int OFF_TAB2 = OFF_TAB1 + NOWN * 4;
constexpr int OFF_SIDE = OFF_TAB2 + NOWN * 4;
constexpr int OFF_BAR = OFF_SIDE + 8;
constexpr int NBAR = 2 * NS + 27;
constexpr int SMEM_BYTES = OFF_BAR + NBAR * 8;
constexpr int SC_OP = OFF_RING + 4 * TILE_BYTES;
constexpr int SC_AB = SC_OP + 4096;
constexpr int SC_Y = SC_AB + 8192;
constexpr int SC_ST = SC_Y + 4096;
constexpr int SC_E4 = SC_ST + 256;
constexpr int SC_E6 = SC_E4 + 1024;
constexpr int SC_P = SC_E6 + 1024;
constexpr int SC_H1 = SC_P + 256;
static_assert(SMEM_BYTES <= 232448, "smem");
static_assert(OFF_BAR % 8 == 0 && OFF_X % 1024 == 0 && X_WQ % 512 == 0 && X_W1 % 512 == 0 && OFF_VA % 16 == 0 && OFF_RED % 16 == 0 && OFF_ML % 16 == 0 && OFF_O % 16 == 0 && OFF_Q % 16 == 0, "align");
constexpr int NB_O = 2  , NB_E4 = 10, NB_E6 = 11, NB_AB = 12, NB_Y = 13;

__device__ uint32_t g_mod[NMODC * 64];
__device__ uint32_t g_q[NCTA * 64];
__device__ uint32_t g_clr[NCTA];
__device__ uint32_t g_phase[16 * 32];
constexpr int SL_P1 = 0;
constexpr int SL_P2 = SL_P1 + NOWN;
constexpr int SL_O = SL_P2 + 2 * NOWN;
constexpr int SL_X1 = SL_O + 8;
constexpr int SL_SIDE = SL_X1 + 3;
static_assert(SL_SIDE < 256, "one 2 MB page");
__device__ uint32_t g_slots[2 * 256 * 2048];
__device__ __forceinline__ uint32_t* slot(int i, int side) {
    const size_t base = ((size_t)g_slots + 0x1fffff) & ~(size_t)0x1fffff;
    return (uint32_t*)base + i * 2048 + (((__popc(i & 0x59) ^ side) & 1) << 10);
}
#define PROF_DECL
#define HPROF(i) do { } while (0)
#define PROF(i) do { } while (0)
#define PROF_DUMP do { } while (0)

__device__ __forceinline__ uint32_t smem_u32(const void* p) { return (uint32_t)__cvta_generic_to_shared(p); }
__device__ __forceinline__ void mbar_init(uint32_t bar, uint32_t cnt) { asm volatile("mbarrier.init.shared::cta.b64 [%0], %1;" ::"r"(bar), "r"(cnt) : "memory"); }
__device__ __forceinline__ void mbar_expect_tx(uint32_t bar, uint32_t bytes) { asm volatile("mbarrier.arrive.expect_tx.shared::cta.b64 _, [%0], %1;" ::"r"(bar), "r"(bytes) : "memory"); }
__device__ __forceinline__ void mbar_arrive(uint32_t bar) { asm volatile("mbarrier.arrive.shared::cta.b64 _, [%0];" ::"r"(bar) : "memory"); }
__device__ __forceinline__ void mbar_wait(uint32_t bar, uint32_t parity) {
    uint32_t ok;
    int it = 0;
    while (true) {
        asm volatile("{\n.reg .pred p;\nmbarrier.try_wait.parity.shared::cta.b64 p, [%1], %2;\nselp.u32 %0, 1, 0, p;\n}" : "=r"(ok) : "r"(bar), "r"(parity) : "memory");
        if (ok) break;
        if (++it > SPIN_LIMIT) __trap();
    }
}
__device__ __forceinline__ void bulk_load(uint32_t dst, const void* src, uint32_t bytes, uint32_t bar, uint64_t pol) {
    asm volatile("cp.async.bulk.shared::cluster.global.mbarrier::complete_tx::bytes.L2::cache_hint [%0], [%1], %2, [%3], %4;"
                 ::"r"(dst), "l"(src), "r"(bytes), "r"(bar), "l"(pol) : "memory");
}
__device__ __forceinline__ void bar_cons() { asm volatile("bar.sync 1, 256;" ::: "memory"); }
template <int ID, int N> __device__ __forceinline__ void nbar_sync() { asm volatile("bar.sync %0, %1;" ::"n"(ID), "n"(N) : "memory"); }
template <int ID, int N> __device__ __forceinline__ void nbar_arrive() { asm volatile("bar.arrive %0, %1;" ::"n"(ID), "n"(N) : "memory"); }
__device__ __forceinline__ bool mbar_test(uint32_t bar, uint32_t parity) {
    uint32_t ok;
    asm volatile("{\n.reg .pred p;\nmbarrier.test_wait.parity.shared::cta.b64 p, [%1], %2;\nselp.u32 %0, 1, 0, p;\n}" : "=r"(ok) : "r"(bar), "r"(parity) : "memory");
    return ok;
}
__device__ __forceinline__ uint32_t pin(uint32_t v) { asm volatile("" : "+r"(v)); return v; }
template <class T> __device__ __forceinline__ T* pin(T* v) { asm volatile("" : "+l"(v)); return v; }
__device__ __forceinline__ void ldsm4(uint32_t (&a)[4], uint32_t addr) {
    asm volatile("ldmatrix.sync.aligned.m8n8.x4.shared.b16 {%0,%1,%2,%3}, [%4];" : "=r"(a[0]), "=r"(a[1]), "=r"(a[2]), "=r"(a[3]) : "r"(addr) : "memory");
}
__device__ __forceinline__ void ldsm4t(uint32_t (&a)[4], uint32_t addr) {
    asm volatile("ldmatrix.sync.aligned.m8n8.x4.trans.shared.b16 {%0,%1,%2,%3}, [%4];" : "=r"(a[0]), "=r"(a[1]), "=r"(a[2]), "=r"(a[3]) : "r"(addr) : "memory");
}
__device__ __forceinline__ void mma16816(float (&c)[4], const uint32_t (&a)[4], uint32_t b0, uint32_t b1) {
    asm volatile("mma.sync.aligned.m16n8k16.row.col.f32.bf16.bf16.f32 {%0,%1,%2,%3}, {%4,%5,%6,%7}, {%8,%9}, {%0,%1,%2,%3};"
                 : "+f"(c[0]), "+f"(c[1]), "+f"(c[2]), "+f"(c[3]) : "r"(a[0]), "r"(a[1]), "r"(a[2]), "r"(a[3]), "r"(b0), "r"(b1));
}
__device__ __forceinline__ uint32_t lds32(uint32_t addr) { uint32_t v; asm volatile("ld.shared.u32 %0, [%1];" : "=r"(v) : "r"(addr) : "memory"); return v; }
__device__ __forceinline__ float lds_f32(uint32_t addr) { float v; asm volatile("ld.shared.f32 %0, [%1];" : "=f"(v) : "r"(addr) : "memory"); return v; }
__device__ __forceinline__ float2 lds_f32x2(uint32_t addr) { float2 v; asm volatile("ld.shared.v2.f32 {%0,%1}, [%2];" : "=f"(v.x), "=f"(v.y) : "r"(addr) : "memory"); return v; }
__device__ __forceinline__ float4 lds_f32x4(uint32_t addr) { float4 v; asm volatile("ld.shared.v4.f32 {%0,%1,%2,%3}, [%4];" : "=f"(v.x), "=f"(v.y), "=f"(v.z), "=f"(v.w) : "r"(addr) : "memory"); return v; }
__device__ __forceinline__ uint2 lds64(uint32_t addr) { uint2 v; asm volatile("ld.shared.v2.u32 {%0,%1}, [%2];" : "=r"(v.x), "=r"(v.y) : "r"(addr) : "memory"); return v; }
__device__ __forceinline__ uint4 lds128(uint32_t addr) { uint4 v; asm volatile("ld.shared.v4.u32 {%0,%1,%2,%3}, [%4];" : "=r"(v.x), "=r"(v.y), "=r"(v.z), "=r"(v.w) : "r"(addr) : "memory"); return v; }
__device__ __forceinline__ void sts16(uint32_t addr, uint32_t v) { asm volatile("st.shared.b16 [%0], %1;" ::"r"(addr), "h"((unsigned short)v) : "memory"); }
__device__ __forceinline__ void sts32(uint32_t addr, uint32_t v) { asm volatile("st.shared.u32 [%0], %1;" ::"r"(addr), "r"(v) : "memory"); }
__device__ __forceinline__ void sts_f32(uint32_t addr, float v) { asm volatile("st.shared.f32 [%0], %1;" ::"r"(addr), "f"(v) : "memory"); }
__device__ __forceinline__ void sts_f32x2(uint32_t addr, float a, float b) { asm volatile("st.shared.v2.f32 [%0], {%1,%2};" ::"r"(addr), "f"(a), "f"(b) : "memory"); }
__device__ __forceinline__ void sts128(uint32_t addr, uint4 v) { asm volatile("st.shared.v4.u32 [%0], {%1,%2,%3,%4};" ::"r"(addr), "r"(v.x), "r"(v.y), "r"(v.z), "r"(v.w) : "memory"); }
__device__ __forceinline__ uint4 ldg_relaxed(const uint32_t* p) {
    uint4 v;
    asm volatile("ld.relaxed.gpu.global.v4.u32 {%0,%1,%2,%3}, [%4];" : "=r"(v.x), "=r"(v.y), "=r"(v.z), "=r"(v.w) : "l"(p) : "memory");
    return v;
}
__device__ __forceinline__ void ldg_relaxed_if(bool on, uint4& v, const uint32_t* p) {
    asm volatile("{\n.reg .pred q;\nsetp.ne.u32 q, %5, 0;\n@q ld.relaxed.gpu.global.v4.u32 {%0,%1,%2,%3}, [%4];\n}"
                 : "+r"(v.x), "+r"(v.y), "+r"(v.z), "+r"(v.w) : "l"(p), "r"((uint32_t)on) : "memory");
}
__device__ __forceinline__ void stg_relaxed2_if(bool on, uint32_t* p, uint32_t a, uint32_t b) {
    asm volatile("{\n.reg .pred q;\nsetp.ne.u32 q, %3, 0;\n@q st.relaxed.gpu.global.v2.u32 [%0], {%1,%2};\n}" ::"l"(p), "r"(a), "r"(b), "r"((uint32_t)on) : "memory");
}
__device__ __forceinline__ uint32_t ldg_relaxed32(const uint32_t* p) { uint32_t v; asm volatile("ld.relaxed.gpu.global.u32 %0, [%1];" : "=r"(v) : "l"(p) : "memory"); return v; }
__device__ __forceinline__ void stg_relaxed(uint32_t* p, uint32_t v) { asm volatile("st.relaxed.gpu.global.u32 [%0], %1;" ::"l"(p), "r"(v) : "memory"); }
__device__ __forceinline__ void stg_relaxed2(uint32_t* p, uint32_t a, uint32_t b) { asm volatile("st.relaxed.gpu.global.v2.u32 [%0], {%1,%2};" ::"l"(p), "r"(a), "r"(b) : "memory"); }
__device__ __forceinline__ void stg_zero4(uint32_t* p) { asm volatile("st.relaxed.gpu.global.v4.u32 [%0], {%1,%1,%1,%1};" ::"l"(p), "r"(0u) : "memory"); }
__device__ __forceinline__ bool ready(const uint4& v) { return (v.x != 0u) & (v.y != 0u) & (v.z != 0u) & (v.w != 0u); }
__device__ __forceinline__ uint4 inv4(const uint4& v) { return make_uint4(~v.x, ~v.y, ~v.z, ~v.w); }
__device__ __forceinline__ uint32_t pack_bf(float lo, float hi) {
    uint32_t r;
    asm("cvt.rn.bf16x2.f32 %0, %1, %2;" : "=r"(r) : "f"(hi), "f"(lo));
    return r;
}
__device__ __forceinline__ float bfr(float x) { return __uint_as_float(pack_bf(0.f, x) & 0xffff0000u); }
__device__ __forceinline__ float bf_lo(uint32_t w) { return __uint_as_float(w << 16); }
__device__ __forceinline__ float bf_hi(uint32_t w) { return __uint_as_float(w & 0xffff0000u); }
__device__ __forceinline__ float bf2f(__nv_bfloat16 v) { return __bfloat162float(v); }
__device__ __forceinline__ float ex2(float x) { float y; asm("ex2.approx.ftz.f32 %0, %1;" : "=f"(y) : "f"(x)); return y; }
__device__ __forceinline__ float rcp_fast(float x) { float y; asm("rcp.approx.ftz.f32 %0, %1;" : "=f"(y) : "f"(x)); return y; }
__device__ __forceinline__ float rsqrt_fast(float x) { float y; asm("rsqrt.approx.ftz.f32 %0, %1;" : "=f"(y) : "f"(x)); return y; }
__device__ __forceinline__ float sqrt_fast(float x) { float y; asm("sqrt.approx.f32 %0, %1;" : "=f"(y) : "f"(x)); return y; }
__device__ __forceinline__ uint32_t bf2_add(uint32_t a, uint32_t b) { uint32_t r; asm("add.rn.bf16x2 %0, %1, %2;" : "=r"(r) : "r"(a), "r"(b)); return r; }
__device__ __forceinline__ uint32_t bf2_sub(uint32_t a, uint32_t b) { uint32_t r; asm("sub.rn.bf16x2 %0, %1, %2;" : "=r"(r) : "r"(a), "r"(b)); return r; }
__device__ __forceinline__ uint32_t bf2_mul(uint32_t a, uint32_t b) { uint32_t r; asm("mul.rn.bf16x2 %0, %1, %2;" : "=r"(r) : "r"(a), "r"(b)); return r; }
__device__ __forceinline__ uint32_t gtime32() { uint32_t c; asm volatile("mov.u32 %0, %%globaltimer_lo;" : "=r"(c)); return c; }
__device__ __forceinline__ uint32_t clock32() { uint32_t c; asm volatile("mov.u32 %0, %%clock;" : "=r"(c)); return c; }

__device__ __forceinline__ float warp_sum(float v) {
#pragma unroll
    for (int o = 16; o > 0; o >>= 1) v += __shfl_xor_sync(0xffffffffu, v, o);
    return v;
}

struct Params {
    const __nv_bfloat16 *x, *kc, *vc, *b1, *b2, *c;
    __nv_bfloat16* out;
};

__device__ __forceinline__ void tma2d(uint32_t dst, const CUtensorMap* tm, int x, int y, uint32_t bar) {
    asm volatile("cp.async.bulk.tensor.2d.shared::cluster.global.mbarrier::complete_tx::bytes [%0], [%1, {%2, %3}], [%4];"
                 ::"r"(dst), "l"(tm), "r"(x), "r"(y), "r"(bar) : "memory");
}

__device__ __forceinline__ void tma2d_hint(uint32_t dst, const CUtensorMap* tm, int x, int y, uint32_t bar, uint64_t pol) {
    asm volatile("cp.async.bulk.tensor.2d.shared::cluster.global.mbarrier::complete_tx::bytes.L2::cache_hint [%0], [%1, {%2, %3}], [%4], %5;"
                 ::"r"(dst), "l"(tm), "r"(x), "r"(y), "r"(bar), "l"(pol) : "memory");
}
__device__ __forceinline__ uint32_t flag(float v) { return __float_as_uint(v) | 1u; }
__device__ __forceinline__ uint32_t and3(uint32_t a, uint32_t b, uint32_t c) { uint32_t r; asm("lop3.b32 %0, %1, %2, %3, 0x80;" : "=r"(r) : "r"(a), "r"(b), "r"(c)); return r; }
__device__ __forceinline__ uint32_t* slot_ptr(uint32_t lo) {
    uint32_t* r;
    asm volatile("mov.b64 %0, {%1, %2};" : "=l"(r) : "r"(lo), "r"((uint32_t)((size_t)slot(0, 0) >> 32)));
    return r;
}

__device__ __forceinline__ void load_bfrag(uint32_t vec, int stride, int k0, int g, int t, uint32_t& b0, uint32_t& b1) {
    uint32_t a = vec + (g & 3) * stride + (k0 + 2 * t) * 2;
    b0 = lds32(a);
    b1 = lds32(a + 16);
}

__device__ __forceinline__ void ln_finish(float pivot, float sum, float sumsq, uint32_t& m2, float& rden) {
    float dm = sum * (1.f / D);
    float var = fmaxf(sumsq * (1.f / D) - dm * dm, 0.f);
    float mean = pivot + dm;
    m2 = pack_bf(mean, mean);
    rden = rcp_fast(bfr(sqrt_fast(bfr(bfr(var) + 1e-5f))));
}
__device__ __forceinline__ uint32_t ln_mod_pair(uint32_t xw, uint32_t cw, uint32_t sw, uint32_t m2, float rden) {
    uint32_t d = bf2_sub(xw, m2);
    uint32_t ln = pack_bf(bf_lo(d) * rden, bf_hi(d) * rden);
    return bf2_add(bf2_mul(ln, bf2_add(cw, 0x3f803f80u)), sw);
}
__device__ __forceinline__ uint4 ln_mod4(const uint4& x, const uint4& c, const uint4& s, uint32_t m2, float rden) {
    return make_uint4(ln_mod_pair(x.x, c.x, s.x, m2, rden), ln_mod_pair(x.y, c.y, s.y, m2, rden),
                      ln_mod_pair(x.z, c.z, s.z, m2, rden), ln_mod_pair(x.w, c.w, s.w, m2, rden));
}
__device__ __forceinline__ void acc_stats(const uint4& v, float pv, float& s, float& q) {
    const float a0 = bf_lo(v.x) - pv, a1 = bf_hi(v.x) - pv, a2 = bf_lo(v.y) - pv, a3 = bf_hi(v.y) - pv;
    const float a4 = bf_lo(v.z) - pv, a5 = bf_hi(v.z) - pv, a6 = bf_lo(v.w) - pv, a7 = bf_hi(v.w) - pv;
    s += ((a0 + a1) + (a2 + a3)) + ((a4 + a5) + (a6 + a7));
    q += (fmaf(a0, a0, a1 * a1) + fmaf(a2, a2, a3 * a3)) + (fmaf(a4, a4, a5 * a5) + fmaf(a6, a6, a7 * a7));
}
__device__ __forceinline__ uint32_t* mod_slot(int kind, int j, int b) { return g_mod + (kind * 20 + (j >> 2)) * 64 + b * 16 + (j & 3) * 4; }

template <int N>
__device__ __forceinline__ void poll_n(uint4 (&v)[N], const uint32_t* const* ptr, const bool* on) {
    bool pend[N];
#pragma unroll
    for (int i = 0; i < N; i++) pend[i] = on[i];
    int it = 0;
    while (true) {
#pragma unroll
        for (int i = 0; i < N; i++) if (pend[i]) v[i] = ldg_relaxed(ptr[i]);
        bool any = false;
#pragma unroll
        for (int i = 0; i < N; i++) { pend[i] = pend[i] && !ready(v[i]); any |= pend[i]; }
        if (!__any_sync(0xffffffffu, any)) break;
        if (++it > SPIN_LIMIT) __trap();
    }
#pragma unroll
    for (int i = 0; i < N; i++) v[i] = inv4(v[i]);
}
__device__ __forceinline__ uint4 poll1(const uint32_t* p, bool on) {
    uint4 v[1] = {make_uint4(0, 0, 0, 0)};
    const uint32_t* const ptr[1] = {p};
    const bool o[1] = {on};
    poll_n<1>(v, ptr, o);
    return v[0];
}

__device__ __forceinline__ void gelu_stage(uint32_t sb, int m, int lane) {
    const int g = lane >> 2, b = lane & 3;
    const uint32_t y_ld = pin(sb + SC_Y + m * 256 + lane * 8), s_ld = pin(sb + SC_ST + b * 64);
    const uint32_t h_st = pin(sb + SC_H1 + b * 64 + (g >> 1) * 16 + m * 8 + (g & 1) * 2);
    float a0 = 0.f, b0 = lds_f32(sb + OWN_B1 + (16 * m + g) * 4), a1 = 0.f, b1 = lds_f32(sb + OWN_B1 + (16 * m + g + 8) * 4);
    nbar_sync<NB_AB, 320>();
#pragma unroll
    for (int w = 0; w < 8; w++) {
        const float4 t = lds_f32x4(sb + SC_AB + w * 1024 + m * 512 + lane * 16);
        a0 += t.x; b0 += t.y; a1 += t.z; b1 += t.w;
    }
    nbar_sync<NB_Y, 320>();
    float4 q[4];
    float2 y[8];
#pragma unroll
    for (int i = 0; i < 4; i++) q[i] = lds_f32x4(s_ld + i * 16);
#pragma unroll
    for (int w = 0; w < 8; w++) y[w] = lds_f32x2(y_ld + w * 512);
    const float dm = (((q[0].y + q[0].w) + (q[1].y + q[1].w)) + ((q[2].y + q[2].w) + (q[3].y + q[3].w))) * (1.f / D);
    const float sq = ((q[0].x + q[0].z) + (q[1].x + q[1].z)) + ((q[2].x + q[2].z) + (q[3].x + q[3].z));
    const float r = rsqrt_fast(fmaxf(fmaf(-dm, dm, sq * (1.f / D)), 0.f) + 1e-5f);
    const float y0 = ((y[0].x + y[1].x) + (y[2].x + y[3].x)) + ((y[4].x + y[5].x) + (y[6].x + y[7].x));
    const float y1 = ((y[0].y + y[1].y) + (y[2].y + y[3].y)) + ((y[4].y + y[5].y) + (y[6].y + y[7].y));
    const float u0 = fmaf(r, fmaf(dm, a0, -y0), b0), u1 = fmaf(r, fmaf(dm, a1, -y1), b1);
    const float e0 = ex2(u0 * fmaf(u0 * u0, -0.044715f * 2.302208198144325f, -2.302208198144325f));
    const float e1 = ex2(u1 * fmaf(u1 * u1, -0.044715f * 2.302208198144325f, -2.302208198144325f));
    sts16(h_st, pack_bf(u0 * rcp_fast(1.f + e0), 0.f));
    sts16(h_st + 4, pack_bf(u1 * rcp_fast(1.f + e1), 0.f));
#pragma unroll
    for (int w = 0; w < 8; w++) asm volatile("bar.arrive %0, 96;" ::"r"(NB_O + w) : "memory");
}

struct Roles { bool is_f, is_owner; int f, own; };
__device__ __forceinline__ Roles roles(int cta) {
    Roles r;
    r.f = (cta * 27) >> 6;
    r.is_f = (((cta + 1) * 27) >> 6) != r.f;
    r.is_owner = !r.is_f || r.f % 9 == 4;
    r.own = r.is_f ? 74 + r.f / 9 : cta - r.f;
    return r;
}

__global__ void __launch_bounds__(NTHREADS, 1)
fused_kernel(const Params p, const __grid_constant__ CUtensorMap tm_wmod, const __grid_constant__ CUtensorMap tm_wq,
             const __grid_constant__ CUtensorMap tm_wo, const __grid_constant__ CUtensorMap tm_w1, const __grid_constant__ CUtensorMap tm_w2,
             const __grid_constant__ CUtensorMap tm_v) {
    extern __shared__ __align__(1024) unsigned char smem[];
    const uint32_t t_start = gtime32();
    const uint32_t sb = smem_u32(smem);
    const int cta = blockIdx.x;
    const int head = cta >> 2, bown = cta & 3;
    const int rot = (head & 1) * (NITEM / 4);
    const char* const kb = (const char*)(p.kc + ((size_t)(bown * NH + head) * SK + (SK - WIN)) * DH);
    uint64_t pol = 0;
    if (threadIdx.x == 256) {
        mbar_init(sb + OFF_BAR, 1);
        asm volatile("fence.mbarrier_init.release.cluster;" ::: "memory");
        asm volatile("createpolicy.fractional.L2::evict_first.b64 %0, 1.0;" : "=l"(pol));
        mbar_expect_tx(sb + OFF_BAR, TILE_BYTES);
        bulk_load(sb + OFF_RING, kb + (size_t)rot * TILE_BYTES, TILE_BYTES, sb + OFF_BAR, pol);
        if ((((cta + 1) * 5) >> 4) != ((cta * 5) >> 4)) {
            const uint32_t bar = sb + OFF_BAR + 2 * NS * 8;
            mbar_init(bar, 1);
            asm volatile("fence.mbarrier_init.release.cluster;" ::: "memory");
            mbar_expect_tx(bar, D * 64);
#pragma unroll 1
            for (int r = 0; r < D; r += 160) tma2d(sb + X_WM + r * 64, &tm_wmod, 32 * ((cta * 5) >> 4), r, bar);
        }
    }
    const uint32_t bar_full = sb + OFF_BAR, bar_empty = bar_full + NS * 8;
    const uint32_t bar_wm = bar_empty + NS * 8, bar_wq = bar_wm + 8, bar_xfree = bar_wq + 8, bar_wo = bar_xfree + 8  ;
    const uint32_t bar_w1 = bar_wo + 40  , bar_w2 = bar_w1 + 32  , bar_help = bar_w2 + 80, bar_v = bar_help + 8  ;
    const int tid = threadIdx.x, warp = tid >> 5, lane = tid & 31;
    const Roles role = roles(cta);
    const bool is_f = role.is_f, is_owner = role.is_owner;
    const int f = role.f, own = role.own;
    const bool crit = (((cta + 1) * 5) >> 4) != ((cta * 5) >> 4);
    const int mr = cta - ((cta * 5) >> 4);
    const bool late = !crit && mr % 11 != 10;
    const int mc = crit ? (cta * 5) >> 4 : 40 + mr - mr / 11;

    PROF_DECL
    PROF(0);
    uint4 xa = make_uint4(0, 0, 0, 0), xb = xa, ca0 = xa, ca1 = xa, xs[3] = {xa, xa, xa};
    uint32_t own0 = 0;
    __nv_bfloat16 own2 = __float2bfloat16(0.f);
    if (warp < 8) {
        xa = *(const uint4*)(p.x + (tid & 3) * D + (tid >> 2) * 8);
        ca0 = ((const uint4*)p.c)[tid];
        if (tid < 64) { xb = *(const uint4*)(p.x + (tid & 3) * D + (64 + (tid >> 2)) * 8); ca1 = ((const uint4*)p.c)[256 + tid]; }
        if (warp < 4) {
#pragma unroll
            for (int i = 0; i < 3; i++) if (lane + 32 * i < 80) xs[i] = ((const uint4*)p.x)[warp * 80 + lane + 32 * i];
        } else if (warp == 4) {
            if (is_owner) own0 = *(const uint32_t*)((lane < 16 ? p.x + (lane >> 2) * D : p.b2) + 8 * own + 2 * (lane & 3));
            if (is_f) own2 = p.b1[32 * f + lane];
        }
    }
    const char* const vb = (const char*)(p.vc + ((size_t)(bown * NH + head) * SK + (SK - WIN)) * DH);
    const uint32_t bar_first = crit ? bar_wm : bar_wq;
    if (threadIdx.x == 256) {
        const uint32_t dst = sb + (crit ? X_WM : X_WQ);
        const CUtensorMap* tm = crit ? &tm_wmod : &tm_wq;
        if (!crit) {
            mbar_init(bar_first, 1);
            asm volatile("fence.mbarrier_init.release.cluster;" ::: "memory");
            mbar_expect_tx(bar_first, D * 64);
        }
        if (!crit) {
            const uint32_t c0 = clock32();
            while (clock32() - c0 < WQ_DELAY) { }
#pragma unroll
            for (int r = 0; r < D; r += 160) tma2d(dst + r * 64, tm, 32 * cta, r, bar_first);
        }
    } else if (threadIdx.x == 0) {
#pragma unroll
        for (int s = 0; s < NS; s++) { if (s) mbar_init(bar_full + s * 8, 1); mbar_init(bar_empty + s * 8, 4); }
        mbar_init(crit ? bar_wq : bar_wm, 1);
        mbar_init(bar_xfree, 1);
#pragma unroll
        for (int i = 0; i < 5; i++) { mbar_init(bar_wo + i * 8, 1); mbar_init(bar_w2 + i * 16, 1); mbar_init(bar_w2 + i * 16 + 8, 1); }
        mbar_init(bar_help, 1);
#pragma unroll
        for (int i = 0; i < 4; i++) { mbar_init(bar_v + i * 8, 1); mbar_init(bar_w1 + i * 8, 1); }
        asm volatile("fence.mbarrier_init.release.cluster;" ::: "memory");
    }
    __syncthreads();

    if (warp == 8) {
        if (lane == 0) {
            int tp = NS;
            int sched = PACE_A - NS * PACE_TAU;
            int phase = 0;
#pragma unroll 1
            for (int t = 1; t <= NITEM; t++) {
                if (t == 1) mbar_wait(bar_full, 0);
                if (t == 2) {
                    mbar_wait(bar_first, 0);
                    if (crit) {
                        mbar_expect_tx(bar_wq, D * 64);
#pragma unroll 1
                        for (int r = 0; r < D; r += 160) tma2d(sb + X_WQ + r * 64, &tm_wq, 32 * cta, r, bar_wq);
                    }
                }
                if (t == 3) {
                    asm volatile("prefetch.tensormap [%0];" ::"l"(&tm_v) : "memory");
                    asm volatile("prefetch.tensormap [%0];" ::"l"(&tm_wo) : "memory");
                    asm volatile("prefetch.tensormap [%0];" ::"l"(&tm_w1) : "memory");
                    asm volatile("prefetch.tensormap [%0];" ::"l"(&tm_w2) : "memory");
                }
                if (t == NS && late) {
                    mbar_wait(bar_full + (NS - INFLIGHT) * 8, 0);
                    mbar_expect_tx(bar_wm, D * 64);
#pragma unroll 1
                    for (int r = 0; r < D; r += 160) tma2d(sb + X_WM + r * 64, &tm_wmod, 32 * mc, r, bar_wm);
                }
                if (t >= NS && t < PF_END) {
                    int it = 0;
                    while (!mbar_test(bar_empty + (t & (NS - 1)) * 8, ((t >> 3) - 1) & 1)) {
                        if (tp < PF_END && (int)(gtime32() - t_start) >= PACE_A + (tp - NS) * PACE_TAU) {
                            asm volatile("cp.async.bulk.prefetch.L2.global.L2::cache_hint [%0], %1, %2;"
                                         ::"l"(((tp & 1) ? vb : kb) + (size_t)(((tp >> 1) + rot) & (NITEM / 2 - 1)) * TILE_BYTES), "r"(TILE_BYTES), "l"(pol) : "memory");
                            tp++;
                        }
                        if (++it > 16 * SPIN_LIMIT) __trap();
                    }
                    if (tp <= t) tp = t + 1;
                }
                if (t == NITEM) {
                    mbar_wait(bar_xfree, 0);
                    const uint32_t t_ref = t_start + phase + (NITEM - 1) * PACE_TAU;
#pragma unroll 1
                    for (int i = 0; i < 5; i++) {
                        while ((int)(gtime32() - t_ref) < WO_T + i * WO_S) { }
                        mbar_expect_tx(bar_wo + i * 8, DH * 64);
                        tma2d(sb + X_WO + i * (DH * 64), &tm_wo, bown * 160 + i * 32, head * DH, bar_wo + i * 8);
                    }
                    if (is_f) {
#pragma unroll 1
                        for (int i = 0; i < 4; i++) {
                            while ((int)(gtime32() - t_ref) < W1_T + i * W1_S) { }
                            mbar_expect_tx(bar_w1 + i * 8, 160 * 64);
                            tma2d(sb + X_W1 + i * (160 * 64), &tm_w1, 32 * f, 160 * i, bar_w1 + i * 8);
                        }
#pragma unroll 1
                        for (int i = 0; i < 3; i++) mbar_wait(bar_empty + i * 8, ((NITEM >> 3) - 1) & 1);
#pragma unroll 1
                        for (int i = 0; i < 10; i++) {
                            while ((int)(gtime32() - t_ref) < W2_T + i * W2_S) { }
                            mbar_expect_tx(bar_w2 + i * 8, 4096);
                            tma2d(sb + X_W2 + i * 4096, &tm_w2, 64 * i, 32 * f, bar_w2 + i * 8);
                        }
                    }
                    break;
                    if (WO_GATE <= 2) { mbar_wait(bar_v + (2 - WO_GATE) * 16, 0); mbar_wait(bar_v + (2 - WO_GATE) * 16 + 8, 0); }
                    else mbar_wait(bar_full + ((NITEM - WO_GATE) & (NS - 1)) * 8, ((NITEM - WO_GATE) >> 3) & 1);
#pragma unroll 1
                    for (int i = 0; i < 5; i++) {
                        mbar_expect_tx(bar_wo + i * 8, DH * 64);
                        tma2d(sb + X_WO + i * (DH * 64), &tm_wo, bown * 160 + i * 32, head * DH, bar_wo + i * 8);
                    }
                    if (is_f) {
                        mbar_wait(bar_wo + WF_GATE * 8, 0);
                        { const uint32_t c0 = clock32(); while (clock32() - c0 < WF_DELAY) { } }
#pragma unroll 1
                        for (int i = 0; i < 4; i++) {
                            mbar_expect_tx(bar_w1 + i * 8, 160 * 64);
                            tma2d(sb + X_W1 + i * (160 * 64), &tm_w1, 32 * f, 160 * i, bar_w1 + i * 8);
                        }
#pragma unroll 1
                        for (int i = 0; i < 3; i++) mbar_wait(bar_empty + i * 8, ((NITEM >> 3) - 1) & 1);
                        { const uint32_t c0 = clock32(); while (clock32() - c0 < W2_DELAY) { } }
#pragma unroll 1
                        for (int i = 0; i < 10; i++) {
                            mbar_expect_tx(bar_w2 + i * 8, 4096);
                            tma2d(sb + X_W2 + i * 4096, &tm_w2, 64 * i, 32 * f, bar_w2 + i * 8);
                        }
                    }
                    break;
                }
                const int s = t & (NS - 1);
                if (t >= NS) {
                    mbar_wait(bar_empty + s * 8, ((t >> 3) - 1) & 1);
                    while ((int)(gtime32() - t_start) < sched + t * PACE_TAU) { }
                } else if (t >= INFLIGHT) {
                    mbar_wait(bar_full + (t - INFLIGHT) * 8, 0);
                }
                if (t < NITEM - 2) {
                    const int pair = t == NITEM - 3 ? NITEM / 2 - 1 : t >> 1;
                    mbar_expect_tx(bar_full + s * 8, TILE_BYTES);
                    bulk_load(sb + OFF_RING + s * TILE_BYTES, ((t & 1) && t != NITEM - 3 ? vb : kb) + (size_t)((pair + rot) & (NITEM / 2 - 1)) * TILE_BYTES, TILE_BYTES, bar_full + s * 8, pol);
                } else {
                    const int row = (bown * NH + head) * SK + (SK - WIN) + ((t - NITEM / 2 + rot) & (NITEM / 2 - 1)) * TILE_KEYS;
#pragma unroll 1
                    for (int i = 0; i < 2; i++) {
                        const uint32_t bar = bar_v + (2 * (t - (NITEM - 2)) + i) * 8;
                        mbar_expect_tx(bar, TILE_BYTES / 2);
                        tma2d_hint(sb + OFF_RING + s * TILE_BYTES + i * (TILE_BYTES / 2), &tm_v, 64 * i, row, bar, pol);
                    }
                }
                if (t >= PH_FIRST + PH_LAG && (t & 3) == (PH_LAG & 3)) {
                    const int now = (int)(gtime32() - t_start) - (t - PH_LAG) * PACE_TAU;
                    uint32_t ph;
                    asm volatile("atom.relaxed.gpu.global.add.u32 %0, [%1], 0;" : "=r"(ph) : "l"(g_phase + ((t - PH_LAG) >> 2) * 32) : "memory");
                    const int mean = ((ph & 0xffffffu) * 4 + (NCTA - (ph >> 24)) * now) >> 7;
                    phase = t < PH_FIRST + PH_LAG + 4 ? mean : phase + (mean - phase) * PH_GAIN / 8;
                    sched = phase - (t >= LAT_FROM ? LAT_END : LAT_T);
                }
            }
        }
        __syncwarp();
    }

    if (warp == 9) {
        int side = 0;
        if (lane == 0) {
            uint32_t best[2] = {~0u, ~0u};
#pragma unroll 1
            for (int i = 0; i < 2 * NPROBE && ((i & 1) || (int)(gtime32() - t_start) < PROBE_END); i++) {
                uint32_t t0 = clock32(), v, t1;
                asm volatile("atom.relaxed.gpu.global.exch.b32 %0, [%1], %2;" : "=r"(v) : "l"(slot(SL_SIDE, i & 1) + cta * 8), "r"(0u) : "memory");
                asm volatile("{\n.reg .pred p;\nsetp.ne.u32 p, %1, 0xffffffff;\nmov.u32 %0, 0;\n@p mov.u32 %0, %%clock;\n}" : "=r"(t1) : "r"(v) : "memory");
                if (i & 1) best[1] = min(best[1], t1 - t0); else best[0] = min(best[0], t1 - t0);
            }
            side = best[1] < best[0];
        }
        side = __shfl_sync(0xffffffffu, side, 0);
        HPROF(1);
        mbar_wait(bar_full + (NS - 1) * 8, 0);
        stg_zero4(slot(SL_O + (cta >> 4), lane >> 4) + (cta & 15) * 64 + (lane & 15) * 4);
        if (is_owner) {
#pragma unroll 1
            for (int i = lane; i < NH * 8; i += 32) stg_zero4(slot(SL_P1 + own, side) + i * 4);
#pragma unroll 1
            for (int i = lane; i < NF * 8; i += 32) stg_zero4(slot(SL_P2 + 2 * own + (i >> 8), side) + (i & 255) * 4);
            if (lane < 8) stg_zero4(slot(SL_X1 + own / 30, lane >> 2) + (own % 30) * 32 + (lane & 3) * 4);
        }
        __threadfence();
        __syncwarp();
        if (lane == 0) stg_relaxed(g_clr + cta, 1u + side);
        HPROF(0);
        HPROF(2);
        while ((int)(gtime32() - t_start) < CLR_CHECK) __nanosleep(1000);
        mbar_wait(bar_xfree, 0);
        {
            uint4 v = make_uint4(1, 1, 1, 1), gv = v, mv[20];
#pragma unroll
            for (int i = 0; i < 20; i++) mv[i] = v;
#pragma unroll 1
            for (int it = 0;; it++) {
                v = ldg_relaxed(g_clr + lane * 4);
                ldg_relaxed_if(is_owner && lane < 8, gv, mod_slot(lane < 4 ? 2 : 5, own, lane & 3));
#pragma unroll
                for (int i = 0; i < 20; i++) ldg_relaxed_if(is_f, mv[i], mod_slot(3, 8 * i + (lane >> 2), lane & 3));
                bool ok = ready(v) && ready(gv);
#pragma unroll
                for (int i = 0; i < 20; i++) ok = ok && ready(mv[i]);
                if (__all_sync(0xffffffffu, ok)) break;
                if (it > SPIN_LIMIT) __trap();
                __nanosleep(2000);
            }
            const uint32_t w[4] = {v.x, v.y, v.z, v.w};
#pragma unroll
            for (int i = 0; i < 4; i++) {
                const Roles r = roles(4 * lane + i);
                if (r.is_owner) {
                    sts32(sb + OFF_TAB1 + r.own * 4, (uint32_t)(size_t)(slot(SL_P1 + r.own, w[i] - 1) + head * 32));
                    sts32(sb + OFF_TAB2 + r.own * 4, (uint32_t)(size_t)(slot(SL_P2 + 2 * r.own + (f >> 5), w[i] - 1) + (f & 31) * 32));
                }
            }
            if (lane == 0) sts32(sb + OFF_SIDE, side);
            if (lane < 8) sts128(sb + OWN_GA + lane * 16, inv4(gv));
            const uint32_t dst = sb + OFF_VA + (lane & 3) * VEC_STRIDE + (lane >> 2) * 16;
#pragma unroll
            for (int i = 0; i < 10; i++) {
                const uint4 c = inv4(mv[10 + i]);
                sts128(dst + i * 128, make_uint4(bf2_add(c.x, 0x3f803f80u), bf2_add(c.y, 0x3f803f80u), bf2_add(c.z, 0x3f803f80u), bf2_add(c.w, 0x3f803f80u)));
                sts128(dst + (OFF_VB - OFF_VA) + i * 128, inv4(mv[i]));
            }
        }
        asm volatile("fence.acq_rel.gpu;" ::: "memory");
        __syncwarp();
        HPROF(3);
        if (lane == 0) mbar_arrive(bar_help);
        {
            const uint32_t* const src = pin(slot(SL_O + (cta >> 4), side) + (cta & 12) * 64 + lane * 4);
            const uint32_t dst = pin(sb + OFF_O + (lane >> 4) * O_STRIDE + (lane & 15) * 16);
            mbar_wait(bar_v + 16, 0);
            mbar_wait(bar_v + 24, 0);
            uint4 v[2];
            const uint32_t* const ptr[2] = {src, src + 128};
            const bool on[2] = {true, true};
            poll_n<2>(v, ptr, on);
            sts128(dst, v[0]);
            sts128(dst + 2 * O_STRIDE, v[1]);
#pragma unroll
            for (int w = 0; w < 8; w++) asm volatile("bar.arrive %0, 64;" ::"r"(NB_O + w) : "memory");
        }
        HPROF(4);
    }
    if (warp >= 8) {
        if (is_f) gelu_stage(sb, warp - 8, lane);
        return;
    }

    const int g = lane >> 2, t4 = lane & 3;
    const int mi = lane >> 3, r8 = lane & 7;

    {
        auto silu4 = [&](const uint4& cv) {
            uint32_t w4[4] = {cv.x, cv.y, cv.z, cv.w};
#pragma unroll
            for (int e = 0; e < 4; e++) {
                float c0 = bf_lo(w4[e]), c1 = bf_hi(w4[e]);
                w4[e] = pack_bf(c0 * rcp_fast(1.f + ex2(-1.4426950408889634f * c0)), c1 * rcp_fast(1.f + ex2(-1.4426950408889634f * c1)));
            }
            return make_uint4(w4[0], w4[1], w4[2], w4[3]);
        };
        if (crit || late) {
            uint4 v = silu4(ca0);
            sts128(sb + OFF_VA + (tid / 80) * VEC_STRIDE + (tid % 80) * 16, v);
            if (tid < 64) { v = silu4(ca1); sts128(sb + OFF_VA + 3 * VEC_STRIDE + (16 + tid) * 16, v); }
        }
        if (warp < 4) {
            float s = 0.f, q = 0.f;
            const float pv = __shfl_sync(0xffffffffu, bf_lo(xs[0].x), 0);
#pragma unroll
            for (int i = 0; i < 3; i++) if (i < 2 || lane < 16) acc_stats(xs[i], pv, s, q);
#pragma unroll
            for (int of = 16; of > 0; of >>= 1) { s += __shfl_xor_sync(0xffffffffu, s, of); q += __shfl_xor_sync(0xffffffffu, q, of); }
            uint32_t m2; float rden;
            ln_finish(pv, s, q, m2, rden);
            if (lane == 0) { sts32(sb + OFF_STAT + warp * 8, m2); sts_f32(sb + OFF_STAT + warp * 8 + 4, rden); }
        } else if (warp == 4) {
            sts32(sb + OWN_X + lane * 4, bf2_add(own0, 0u));
            sts_f32(sb + OWN_B1 + lane * 4, bf2f(own2));
        }
    }
    bar_cons();
    PROF(24);
    uint32_t qf[8][2];
    float o[8][4];
#pragma unroll
    for (int c = 0; c < 8; c++) { o[c][0] = o[c][1] = o[c][2] = o[c][3] = 0.f; }
    float m_run = -INFINITY, l_run = 0.f;
    const bool diag = (t4 == (g >> 1));
    const bool odd = g & 1;
    const uint32_t koff = (warp & 3) * 4096 + (r8 + 8 * (mi & 1)) * 256 + (mi >> 1) * 128 + (r8 << 4);
    const uint32_t voff = TILE_BYTES + (warp & 3) * 4096 + (r8 + 8 * (mi >> 1)) * 256 + (mi & 1) * 128 + (r8 << 4);
    const int src0 = (2 * t4) * 4 + t4, src1 = (2 * t4 + 1) * 4 + t4;
#pragma unroll 1
    for (int step = crit ? 0 : 1; step < 3; step++) {
        if (step < 2 || late) {
            if (step == 1) {
                if (!crit) mbar_wait(bar_wq, 0);
                const uint32_t m2 = lds32(sb + OFF_STAT + (tid & 3) * 8);
                const float rden = lds_f32(sb + OFF_STAT + (tid & 3) * 8 + 4);
                uint4 v[4] = {xa, xa, xa, xa};
                const uint32_t* const ptr[4] = {mod_slot(0, tid >> 2, tid & 3), mod_slot(1, tid >> 2, tid & 3),
                                                mod_slot(0, 64 + ((tid & 63) >> 2), tid & 3), mod_slot(1, 64 + ((tid & 63) >> 2), tid & 3)};
                const bool on[4] = {true, true, tid < 64, tid < 64};
                poll_n<4>(v, ptr, on);
                uint4 h0 = ln_mod4(xa, v[1], v[0], m2, rden);
                sts128(sb + OFF_VB + (tid & 3) * VEC_STRIDE + (tid >> 2) * 16, h0);
                if (tid < 64) {
                    h0 = ln_mod4(xb, v[3], v[2], m2, rden);
                    sts128(sb + OFF_VB + (tid & 3) * VEC_STRIDE + (64 + (tid >> 2)) * 16, h0);
                }
            }
            mbar_wait(step == 1 ? bar_wq : bar_wm, 0);
            bar_cons();
            const uint32_t strip = sb + (step == 1 ? X_WQ : X_WM), vec = sb + (step == 1 ? OFF_VB : OFF_VA);
            float acc[2][4];
#pragma unroll
            for (int m = 0; m < 2; m++) { acc[m][0] = acc[m][1] = acc[m][2] = acc[m][3] = 0.f; }
#pragma unroll
            for (int i = 0; i < 5; i++) {
                int k0 = (warp * 5 + i) * 16;
                uint32_t b0, b1;
                load_bfrag(vec, VEC_STRIDE, k0, g, t4, b0, b1);
                int krow = k0 + r8 + 8 * (mi >> 1);
#pragma unroll
                for (int m = 0; m < 2; m++) {
                    uint32_t a[4];
                    int ch = 2 * m + (mi & 1);
                    ldsm4t(a, strip + krow * 64 + ((ch ^ ((krow >> 1) & 3)) << 4));
                    mma16816(acc[m], a, b0, b1);
                }
            }
            if (t4 < 2) {
#pragma unroll
                for (int m = 0; m < 2; m++) {
                    sts_f32x2(sb + OFF_RED + ((warp * 32 + m * 16 + g) * 4 + 2 * t4) * 4, acc[m][0], acc[m][1]);
                    sts_f32x2(sb + OFF_RED + ((warp * 32 + m * 16 + g + 8) * 4 + 2 * t4) * 4, acc[m][2], acc[m][3]);
                }
            }
            bar_cons();
            if (tid < 128) {
                float v = 0.f;
#pragma unroll
                for (int w = 0; w < 8; w++) v += lds_f32(sb + OFF_RED + (w * 128 + tid) * 4);
                float vn = __shfl_down_sync(0xffffffffu, v, 4);
                uint32_t* dst = step == 1 ? g_q + ((cta & ~3) + (tid & 3)) * 64 + bown * 16 + (tid >> 3) : g_mod + mc * 64 + (tid & 3) * 16 + (tid >> 3);
                if (!((tid >> 2) & 1)) stg_relaxed(dst, ~pack_bf(v, vn));
            }
        }
        if (step == 0) continue;
        if (step == 1) {
            if (warp == 0) {
                uint4 v = poll1(g_q + cta * 64 + (lane & 15) * 4, lane < 16);
                if (lane < 16) {
                    sts128(sb + OFF_Q + lane * 16, v);
                    stg_zero4(g_q + cta * 64 + lane * 4);
                }
            }
            bar_cons();
            PROF(4);

#pragma unroll
            for (int c = 0; c < 8; c++) {
                qf[c][0] = lds32(sb + OFF_Q + (((c ^ g) * 4 + t4) << 2));
                qf[c][1] = lds32(sb + OFF_Q + 128 + (((c ^ g) * 4 + t4) << 2));
            }
        } else {
            bar_cons();
            if (tid == 0) mbar_arrive(bar_xfree);
        }
#pragma unroll 1
        for (int j = (step == 1 ? 0 : SEG_J) + (warp >> 2); j < (step == 1 ? SEG_J : NITEM / 2 - 2); j += 2) {
            const int s = (2 * j) & (NS - 1);
            const uint32_t par = (j >> 2) & 1;
            mbar_wait(bar_full + s * 8, par);
            if (tid == 0 && 2 * j >= PH_FIRST) {
                const int x = min(max((int)(gtime32() - t_start) - 2 * j * PACE_TAU, 0), 65535);
                asm volatile("red.relaxed.gpu.global.add.u32 [%0], %1;" ::"l"(g_phase + (j >> 1) * 32), "r"((1u << 24) + (x >> 2)) : "memory");
            }
            const uint32_t base = sb + OFF_RING + s * TILE_BYTES;
            float sa[4] = {0.f, 0.f, 0.f, 0.f}, sb2[4] = {0.f, 0.f, 0.f, 0.f};
#pragma unroll
            for (int c = 0; c < 8; c += 2) {
                uint32_t a[4], a2[4];
                ldsm4(a, (base + koff) ^ (c << 4));
                ldsm4(a2, (base + koff) ^ ((c + 1) << 4));
                mma16816(sa, a, qf[c][0], qf[c][1]);
                mma16816(sb2, a2, qf[c + 1][0], qf[c + 1][1]);
            }
            const uint32_t sw = pack_bf(odd ? sa[1] + sb2[1] : sa[0] + sb2[0], odd ? sa[3] + sb2[3] : sa[2] + sb2[2]);
            const uint32_t sv = pack_bf(bf_lo(sw) * 0.08838834764831845f, bf_hi(sw) * 0.08838834764831845f);
            const float s0 = bf_lo(sv) * 1.4426950408889634f, s1 = bf_hi(sv) * 1.4426950408889634f;
            float m_new = fmaxf(m_run, fmaxf(s0, s1));
            const bool grow = __any_sync(0xffffffffu, (diag && (m_new > m_run)));
            if (lane == 0) mbar_arrive(bar_empty + s * 8);
            if (grow) {
                float al = ex2(m_run - m_new);
                float a0 = __shfl_sync(0xffffffffu, al, src0), a1 = __shfl_sync(0xffffffffu, al, src1);
#pragma unroll
                for (int c = 0; c < 8; c++) { o[c][0] *= a0; o[c][1] *= a1; o[c][2] *= a0; o[c][3] *= a1; }
                l_run *= al;
                m_run = m_new;
            }
            uint32_t pw = pack_bf(ex2(s0 - m_run), ex2(s1 - m_run));
            l_run += bf_lo(pw) + bf_hi(pw);
            uint32_t b0 = odd ? (pw << 16) : (pw & 0xffffu);
            uint32_t b1 = odd ? (pw & 0xffff0000u) : (pw >> 16);
            if (!diag) { b0 = 0u; b1 = 0u; }
            mbar_wait(bar_full + (s + 1) * 8, par);
#pragma unroll
            for (int c = 0; c < 8; c++) {
                uint32_t a[4];
                ldsm4t(a, (base + voff) ^ (c << 4));
                mma16816(o[c], a, b0, b1);
            }
            __syncwarp();
            if (lane == 0) mbar_arrive(bar_empty + (s + 1) * 8);
        }
    }
    PROF(5);
    float acc[4][4];
    uint32_t pa[8][2];
    float rinv;
    {
        const int s = 4 + (warp >> 2);
        mbar_wait(bar_full + s * 8, 1);
        const uint32_t base = sb + OFF_RING + s * TILE_BYTES;
        float sa[4] = {0.f, 0.f, 0.f, 0.f}, sb2[4] = {0.f, 0.f, 0.f, 0.f};
#pragma unroll
        for (int c = 0; c < 8; c += 2) {
            uint32_t a[4], a2[4];
            ldsm4(a, (base + koff) ^ (c << 4));
            ldsm4(a2, (base + koff) ^ ((c + 1) << 4));
            mma16816(sa, a, qf[c][0], qf[c][1]);
            mma16816(sb2, a2, qf[c + 1][0], qf[c + 1][1]);
        }
        const uint32_t sw = pack_bf(odd ? sa[1] + sb2[1] : sa[0] + sb2[0], odd ? sa[3] + sb2[3] : sa[2] + sb2[2]);
        const uint32_t sv = pack_bf(bf_lo(sw) * 0.08838834764831845f, bf_hi(sw) * 0.08838834764831845f);
        const float s0 = bf_lo(sv) * 1.4426950408889634f, s1 = bf_hi(sv) * 1.4426950408889634f;
        int mi_ = __float_as_int(diag ? fmaxf(m_run, fmaxf(s0, s1)) : -INFINITY);
        mi_ ^= (mi_ >> 31) & 0x7fffffff;
        mi_ = __reduce_max_sync(0xffffffffu, mi_);
        mi_ ^= (mi_ >> 31) & 0x7fffffff;
        if (lane == 0) sts32(sb + OFF_ML + warp * 4, mi_);
        bar_cons();
        const float4 m0 = lds_f32x4(sb + OFF_ML), m1 = lds_f32x4(sb + OFF_ML + 16);
        const float mx = fmaxf(fmaxf(fmaxf(m0.x, m0.y), fmaxf(m0.z, m0.w)), fmaxf(fmaxf(m1.x, m1.y), fmaxf(m1.z, m1.w)));
        const float scl = ex2(m_run - mx);
        const uint32_t pw = pack_bf(ex2(s0 - mx), ex2(s1 - mx));
        if (diag) { sts16(sb + SC_P + (warp * 16 + g) * 2, pw); sts16(sb + SC_P + (warp * 16 + g + 8) * 2, pw >> 16); }
        const float lw = warp_sum(diag ? fmaf(l_run, scl, bf_lo(pw) + bf_hi(pw)) : 0.f);
        const float a0 = __shfl_sync(0xffffffffu, scl, src0), a1 = __shfl_sync(0xffffffffu, scl, src1);
        float v[8], u[8];
#pragma unroll
        for (int c = 0; c < 8; c++) {
            v[c] = a0 * o[c][0] + a1 * o[c ^ 1][1];
            u[c] = a0 * o[c][2] + a1 * o[c ^ 1][3];
        }
#pragma unroll
        for (int c = 0; c < 8; c++) {
            if (!(c & 2)) {
                v[c] += __shfl_xor_sync(0xffffffffu, v[c ^ 2], 1);
                u[c] += __shfl_xor_sync(0xffffffffu, u[c ^ 2], 1);
            }
        }
#pragma unroll
        for (int c = 0; c < 2; c++) {
            v[c] += __shfl_xor_sync(0xffffffffu, v[c ^ 4], 2);
            u[c] += __shfl_xor_sync(0xffffffffu, u[c ^ 4], 2);
        }
        const uint32_t dst = sb + SC_OP + (warp * 128 + 16 * t4 + g) * 4;
        sts_f32(dst, v[0]); sts_f32(dst + 32, v[1]); sts_f32(dst + 256, u[0]); sts_f32(dst + 288, u[1]);
        if (lane == 0) sts_f32(sb + OFF_ML + 32 + warp * 4, lw);
        mbar_wait(bar_help, 0);
        bar_cons();
        const float4 l0 = lds_f32x4(sb + OFF_ML + 32), l1 = lds_f32x4(sb + OFF_ML + 48);
        rinv = rcp_fast(((l0.x + l0.y) + (l0.z + l0.w)) + ((l1.x + l1.y) + (l1.z + l1.w)));
#pragma unroll
        for (int i = 0; i < 4; i++) acc[i][0] = acc[i][1] = acc[i][2] = acc[i][3] = 0.f;
#pragma unroll
        for (int w = 0; w < 8; w++) {
            const float2 x0 = lds_f32x2(sb + SC_OP + (w * 128 + 16 * warp + 2 * t4) * 4), x1 = lds_f32x2(sb + SC_OP + (w * 128 + 16 * warp + 8 + 2 * t4) * 4);
            acc[2 * (w & 1)][0] += x0.x; acc[2 * (w & 1)][1] += x0.y;
            acc[2 * (w & 1) + 1][0] += x1.x; acc[2 * (w & 1) + 1][1] += x1.y;
        }
#pragma unroll
        for (int ks = 0; ks < 8; ks++) { pa[ks][0] = lds32(sb + SC_P + (8 * ks + t4) * 4); pa[ks][1] = lds32(sb + SC_P + (8 * ks + 4 + t4) * 4); }
    }
    PROF(20);
    const int mt = warp < 2 ? warp : warp + 2;
    {
        const uint32_t va = pin(sb + OFF_RING + 6 * TILE_BYTES + (warp >> 2) * (TILE_BYTES / 2) + (8 * (mi & 1) + r8) * 128 + (((2 * (warp & 3) + (mi >> 1)) ^ r8) << 4));
        const uint32_t vbar = pin(bar_v + (warp >> 2) * 8);
        uint32_t* const o_dst = pin(slot(SL_O + (cta >> 4), g) + (cta & 15) * 64 + warp * 8 + 2 * t4);
#pragma unroll
        for (int tl = 0; tl < 2; tl++) {
            mbar_wait(vbar + tl * 16, 0);
            uint32_t r[4][4];
#pragma unroll
            for (int ks = 0; ks < 4; ks++) ldsm4t(r[ks], va + tl * TILE_BYTES + ks * 2048);
#pragma unroll
            for (int ks = 0; ks < 4; ks++) {
                const uint32_t a[4] = {pa[4 * tl + ks][0], 0u, pa[4 * tl + ks][1], 0u};
                mma16816(acc[2 * (ks & 1)], a, r[ks][0], r[ks][1]);
                mma16816(acc[2 * (ks & 1) + 1], a, r[ks][2], r[ks][3]);
            }
        }
        stg_relaxed2_if(g < 2, o_dst, ~pack_bf((acc[0][0] + acc[2][0]) * rinv, (acc[0][1] + acc[2][1]) * rinv),
                        ~pack_bf((acc[1][0] + acc[3][0]) * rinv, (acc[1][1] + acc[3][1]) * rinv));
    }
    PROF(7);
    const int side = lds32(sb + OFF_SIDE);
    const uint32_t red_st = pin(sb + SC_E4 + ((warp * 4 + 2 * ((lane >> 3) & 1) + (lane >> 4)) * 8 + (lane & 7)) * 4);
    const uint32_t red_ld = pin(sb + SC_E4 + (lane & 15) * 8);
    const uint32_t* const in1 = pin(slot(SL_P1 + own, side) + tid * 4);
    const uint32_t* const in2a = pin(slot(SL_P2 + 2 * own, side) + tid * 4);
    const uint32_t* const in2b = pin(slot(SL_P2 + 2 * own + 1, side) + tid * 4);
    uint32_t* const x1_dst = pin(slot(SL_X1 + own / 30, lane >> 4) + (own % 30) * 32 + (lane & 15));
    const uint32_t xw = lds32(sb + OWN_X + (lane & 15) * 4), ga_w = lds32(sb + OWN_GA + (lane & 15) * 4);
    uint32_t cs[15];
    uint32_t* dst2[10];
    uint32_t w2a[5];
#pragma unroll
    for (int j = 0; j < 10; j++) cs[j] = lds32(sb + OFF_VA + ((g & 1) * 4 + (g >> 1)) * VEC_STRIDE + warp * 160 + t4 * 4 + j * 16);
#pragma unroll
    for (int i = 0; i < 5; i++) {
        cs[10 + i] = lds32(sb + OFF_VA + (g >> 1) * VEC_STRIDE + warp * 160 + (g & 1) * 16 + t4 * 4 + i * 32);
        const uint2 t = lds64(sb + OFF_TAB2 + warp * 40 + i * 8);
        dst2[2 * i] = slot_ptr(t.x + g * 16 + t4 * 8);
        dst2[2 * i + 1] = slot_ptr(t.y + g * 16 + t4 * 8);
        const int cc = 2 * (warp * 5 + i) + (mi & 1);
        w2a[i] = pin(sb + X_W2 + (cc >> 3) * 4096 + (r8 + 8 * (mi >> 1)) * 128 + (((cc & 7) ^ r8) << 4));
    }
    const uint32_t piv = lds32(sb + OFF_STAT + (g >> 1) * 8);
    const uint32_t* const xin = pin(slot(SL_X1 + warp / 3, side) + ((warp % 3) * 10 + (g & 1)) * 32 + (g >> 1) * 4 + t4);
    const uint32_t w1a = pin(sb + X_W1 + (warp * 80 + r8 + 8 * (mi >> 1)) * 64 + (((mi & 1) ^ ((r8 >> 1) & 3)) << 4));
    const uint32_t w1bar = pin(bar_w1 + (warp >> 1) * 8), w2bar = pin(bar_w2 + (warp + (warp >> 2)) * 8);
    const uint32_t wbar = pin(NB_O + warp);
    const uint32_t ab_st = pin(sb + SC_AB + warp * 1024 + lane * 16), y_st = pin(sb + SC_Y + warp * 512 + lane * 8), s_st = pin(sb + SC_ST + (t4 * 8 + warp) * 8);
    const uint32_t h_ld = pin(sb + SC_H1 + ((g & 3) ^ (2 * (f & 1) + ((f >> 1) & 1))) * 64 + t4 * 16);
    {
        const int kap = 2 * (head & 1) + ((head >> 1) & 1);
        const uint32_t wa = pin(sb + X_WO + (mt >> 1) * (DH * 64) + (r8 + 8 * (mi >> 1)) * 64 + ((((mt & 1) * 2 + (mi & 1)) ^ ((r8 >> 1) & 3)) << 4));
        const uint32_t oa = pin(sb + OFF_O + ((g & 3) ^ kap) * O_STRIDE + t4 * 8);
        uint32_t* dst[4];
#pragma unroll
        for (int i = 0; i < 2; i++) {
            const uint2 t = lds64(sb + OFF_TAB1 + (bown * 20 + 2 * mt + (warp < 2 ? 4 * i : 0)) * 4);
            dst[2 * i] = slot_ptr(t.x + g * 16 + t4 * 8);
            dst[2 * i + 1] = slot_ptr(t.y + g * 16 + t4 * 8);
        }
        PROF(6);
        uint32_t wf[8][4], wg[8][4];
        mbar_wait(bar_wo + (mt >> 1) * 8, 0);
#pragma unroll
        for (int ks = 0; ks < 8; ks++) ldsm4t(wf[ks], wa + ks * 1024);
        if (warp < 2) {
            mbar_wait(bar_wo + 8, 0);
#pragma unroll
            for (int ks = 0; ks < 8; ks++) ldsm4t(wg[ks], wa + DH * 64 + ks * 1024);
        }
        asm volatile("bar.sync %0, 64;" ::"r"(wbar) : "memory");
        PROF(8);
        uint2 ob[8];
#pragma unroll
        for (int ks = 0; ks < 8; ks++) ob[ks] = lds64(oa + ks * 32);
        float c0[4] = {0.f, 0.f, 0.f, 0.f}, c1[4] = {0.f, 0.f, 0.f, 0.f};
        if (warp < 2) {
            float c2[4] = {0.f, 0.f, 0.f, 0.f}, c3[4] = {0.f, 0.f, 0.f, 0.f};
#pragma unroll
            for (int ks = 0; ks < 8; ks += 2) {
                mma16816(c0, wf[ks], ob[ks].x, ob[ks].y);
                mma16816(c2, wg[ks], ob[ks].x, ob[ks].y);
                mma16816(c1, wf[ks + 1], ob[ks + 1].x, ob[ks + 1].y);
                mma16816(c3, wg[ks + 1], ob[ks + 1].x, ob[ks + 1].y);
            }
            stg_relaxed2_if(t4 < 2, dst[2], flag(c2[0] + c3[0]), flag(c2[1] + c3[1]));
            stg_relaxed2_if(t4 < 2, dst[3], flag(c2[2] + c3[2]), flag(c2[3] + c3[3]));
        } else {
#pragma unroll
            for (int ks = 0; ks < 8; ks += 2) {
                mma16816(c0, wf[ks], ob[ks].x, ob[ks].y);
                mma16816(c1, wf[ks + 1], ob[ks + 1].x, ob[ks + 1].y);
            }
        }
        stg_relaxed2_if(t4 < 2, dst[0], flag(c0[0] + c1[0]), flag(c0[1] + c1[1]));
        stg_relaxed2_if(t4 < 2, dst[1], flag(c0[2] + c1[2]), flag(c0[3] + c1[3]));
    }
    PROF(9);
    uint32_t x1w = 0;
    if (is_owner) {
        uint4 v;
        for (int it = 0;; it++) {
            v = ldg_relaxed(in1);
            if (__all_sync(0xffffffffu, and3(and3(v.x, v.y, v.z), v.w, 1u))) break;
            if (it > SPIN_LIMIT) __trap();
        }
        PROF(11);
        const float s0 = __uint_as_float(v.x) + __shfl_xor_sync(0xffffffffu, __uint_as_float(v.z), 8);
        const float s1 = __uint_as_float(v.y) + __shfl_xor_sync(0xffffffffu, __uint_as_float(v.w), 8);
        sts_f32(red_st, s0 + __shfl_xor_sync(0xffffffffu, s1, 16));
        if (warp == 0) {
            nbar_sync<NB_E4, 256>();
            float2 a[8];
#pragma unroll
            for (int w = 0; w < 8; w++) a[w] = lds_f32x2(red_ld + w * 128);
            const uint32_t aw = pack_bf(((a[0].x + a[1].x) + (a[2].x + a[3].x)) + ((a[4].x + a[5].x) + (a[6].x + a[7].x)),
                                        ((a[0].y + a[1].y) + (a[2].y + a[3].y)) + ((a[4].y + a[5].y) + (a[6].y + a[7].y)));
            x1w = bf2_add(xw, bf2_mul(ga_w, aw));
            stg_relaxed(x1_dst, x1w ^ 0x80008000u);
        } else {
            nbar_arrive<NB_E4, 256>();
        }
    }
    PROF(12);
    if (is_f) {
        uint32_t f1[5][2][4], f2[5][2][4];
        uint32_t d[6];
        auto load_x1 = [&] {
#pragma unroll
            for (int i = 0; i < 5; i++) d[i] = ldg_relaxed32(xin + i * 64);
        };
        auto have_x1 = [&] { return __all_sync(0xffffffffu, __vimin3_u32(__vimin3_u32(d[0], d[1], d[2]), d[3], d[4]) != 0u); };
        mbar_wait(w1bar, 0);
        load_x1();
        {
#pragma unroll
            for (int i = 0; i < 5; i++) { ldsm4t(f1[i][0], w1a + i * 1024); ldsm4t(f1[i][1], (w1a ^ 32) + i * 1024); }
            float c[2][4];
#pragma unroll
            for (int m = 0; m < 2; m++) c[m][0] = c[m][1] = c[m][2] = c[m][3] = 0.f;
#pragma unroll
            for (int i = 0; i < 5; i++) { mma16816(c[0], f1[i][0], cs[2 * i], cs[2 * i + 1]); mma16816(c[1], f1[i][1], cs[2 * i], cs[2 * i + 1]); }
#pragma unroll
            for (int i = 0; i < 5; i++) { cs[2 * i] = pin(odd ? 0u : cs[10 + i]); cs[2 * i + 1] = pin(odd ? cs[10 + i] : 0u); }
#pragma unroll
            for (int m = 0; m < 2; m++) sts128(ab_st + m * 512, make_uint4(__float_as_uint(c[m][0]), __float_as_uint(c[m][1]), __float_as_uint(c[m][2]), __float_as_uint(c[m][3])));
            nbar_arrive<NB_AB, 320>();
            d[0] |= __float_as_uint(c[1][3]) & (side >> 1);
        }
        PROF(10);
#pragma unroll 1
        for (int it = 0; !have_x1(); it++) {
            load_x1();
            if (it > SPIN_LIMIT) __trap();
        }
        PROF(13);
        {
            float y[2][4], st[4] = {0.f, 0.f, 0.f, 0.f};
#pragma unroll
            for (int m = 0; m < 2; m++) y[m][0] = y[m][1] = y[m][2] = y[m][3] = 0.f;
#pragma unroll
            for (int i = 0; i < 5; i++) d[i] = bf2_add(d[i], piv);
            d[5] = 0u;
#pragma unroll
            for (int i = 0; i < 5; i++) {
                if (i < 3) {
                    const uint32_t a[4] = {d[2 * i], 0x3f803f80u, d[2 * i + 1], 0x3f803f80u};
                    mma16816(st, a, d[2 * i], d[2 * i + 1]);
                }
                const uint32_t y0 = bf2_mul(d[i], cs[2 * i]), y1 = bf2_mul(d[i], cs[2 * i + 1]);
                mma16816(y[0], f1[i][0], y0, y1);
                mma16816(y[1], f1[i][1], y0, y1);
            }
            const float q = odd ? st[1] : st[0];
            const float q2 = q + __shfl_xor_sync(0xffffffffu, q, 4);
            if (diag && !odd) sts_f32x2(s_st, q2, st[2] + st[3]);
#pragma unroll
            for (int m = 0; m < 2; m++) sts_f32x2(y_st + m * 256, y[m][0] + y[m][1], y[m][2] + y[m][3]);
        }
        nbar_arrive<NB_Y, 320>();
        PROF(14);
        mbar_wait(w2bar, 0);
        mbar_wait(w2bar + 8, 0);
#pragma unroll
        for (int i = 0; i < 5; i++) { ldsm4t(f2[i][0], w2a[i]); ldsm4t(f2[i][1], w2a[i] + 2048); }
        asm volatile("bar.sync %0, 96;" ::"r"(wbar) : "memory");
        PROF(15);
        {
            const uint4 hb = lds128(h_ld);
            float c[5][4];
#pragma unroll
            for (int i = 0; i < 7; i++) {
                if (i < 5) { c[i][0] = c[i][1] = c[i][2] = c[i][3] = 0.f; mma16816(c[i], f2[i][0], hb.x, hb.y); }
                if (i > 0 && i < 6) mma16816(c[i - 1], f2[i - 1][1], hb.z, hb.w);
                if (i > 1) {
                    stg_relaxed2_if(t4 < 2, dst2[2 * i - 4], flag(c[i - 2][0]), flag(c[i - 2][1]));
                    stg_relaxed2_if(t4 < 2, dst2[2 * i - 3], flag(c[i - 2][2]), flag(c[i - 2][3]));
                }
            }
        }
    }
    PROF(16);
    if (is_owner) {
        uint32_t* const dst = pin((uint32_t*)(p.out + ((lane >> 2) & 3) * D + 8 * own) + t4);
        const uint32_t b2w = lds32(sb + OWN_B2 + (lane & 15) * 4), gb_w = lds32(sb + OWN_GB + (lane & 15) * 4);
        const bool two = tid < NF * 8 - 256;
        uint4 v, w = make_uint4(1, 1, 1, 1);
        for (int it = 0;; it++) {
            ldg_relaxed_if(two, w, in2b);
            v = ldg_relaxed(in2a);
            if (__all_sync(0xffffffffu, and3(and3(v.x, v.y, v.z), and3(v.w, w.x, w.y), and3(w.z, w.w, 1u)))) break;
            if (it > SPIN_LIMIT) __trap();
        }
        PROF(17);
        const float s0 = (__uint_as_float(v.x) + __uint_as_float(w.x)) + __shfl_xor_sync(0xffffffffu, __uint_as_float(v.z) + __uint_as_float(w.z), 8);
        const float s1 = (__uint_as_float(v.y) + __uint_as_float(w.y)) + __shfl_xor_sync(0xffffffffu, __uint_as_float(v.w) + __uint_as_float(w.w), 8);
        sts_f32(red_st + (SC_E6 - SC_E4), s0 + __shfl_xor_sync(0xffffffffu, s1, 16));
        nbar_sync<NB_E6, 256>();
        if (warp == 0) {
            float2 a[8];
#pragma unroll
            for (int i = 0; i < 8; i++) a[i] = lds_f32x2(red_ld + (SC_E6 - SC_E4) + i * 128);
            const uint32_t aw = pack_bf(((a[0].x + a[1].x) + (a[2].x + a[3].x)) + ((a[4].x + a[5].x) + (a[6].x + a[7].x)),
                                        ((a[0].y + a[1].y) + (a[2].y + a[3].y)) + ((a[4].y + a[5].y) + (a[6].y + a[7].y)));
            const uint32_t r = bf2_add(x1w, bf2_mul(gb_w, bf2_add(aw, b2w)));
            if (lane < 16) asm volatile("st.global.u32 [%0], %1;" ::"l"(dst), "r"(r) : "memory");
        }
        if (tid >= 32 && tid < 56) stg_zero4(mod_slot((tid - 32) >> 2, own, tid & 3));
    }
    if (cta == 0 && tid >= 64 && tid < 80) stg_relaxed(g_phase + (tid - 64) * 32, 0u);
    if (tid == 96) stg_relaxed(g_clr + cta, 0u);
    PROF(18);
    PROF_DUMP;
}

typedef CUresult (*EncodeFn)(CUtensorMap*, CUtensorMapDataType, cuuint32_t, void*, const cuuint64_t*, const cuuint64_t*, const cuuint32_t*,
                             const cuuint32_t*, CUtensorMapInterleave, CUtensorMapSwizzle, CUtensorMapL2promotion, CUtensorMapFloatOOBfill);

static CUtensorMap make_map(EncodeFn enc, const void* ptr, int cols, int rows, int box_cols, int box_rows, CUtensorMapSwizzle sw) {
    CUtensorMap m;
    cuuint64_t dims[2] = {(cuuint64_t)cols, (cuuint64_t)rows};
    cuuint64_t strides[1] = {(cuuint64_t)cols * 2};
    cuuint32_t box[2] = {(cuuint32_t)box_cols, (cuuint32_t)box_rows};
    cuuint32_t es[2] = {1, 1};
    enc(&m, CU_TENSOR_MAP_DATA_TYPE_BFLOAT16, 2, const_cast<void*>(ptr), dims, strides, box, es, CU_TENSOR_MAP_INTERLEAVE_NONE, sw,
        CU_TENSOR_MAP_L2_PROMOTION_NONE, CU_TENSOR_MAP_FLOAT_OOB_FILL_NONE);
    return m;
}

}

extern "C" void kernel_launch(void* const* d_in, const int* in_sizes, int n_in, void* d_out, int out_size) {
    (void)in_sizes; (void)n_in; (void)out_size;
    static EncodeFn enc = nullptr;
    if (!enc) {
        void* fn = nullptr;
        cudaDriverEntryPointQueryResult qr;
        cudaGetDriverEntryPoint("cuTensorMapEncodeTiled", &fn, cudaEnableDefault, &qr);
        enc = (EncodeFn)fn;
        cudaFuncSetAttribute(fused_kernel, cudaFuncAttributeMaxDynamicSharedMemorySize, SMEM_BYTES);
    }
    Params p;
    p.x = (const __nv_bfloat16*)d_in[0];
    p.kc = (const __nv_bfloat16*)d_in[1];
    p.vc = (const __nv_bfloat16*)d_in[2];
    p.b1 = (const __nv_bfloat16*)d_in[7];
    p.b2 = (const __nv_bfloat16*)d_in[9];
    p.c = (const __nv_bfloat16*)d_in[10];
    p.out = (__nv_bfloat16*)d_out;
    CUtensorMap tm_wmod = make_map(enc, d_in[11], NMOD, D, 32, 160, CU_TENSOR_MAP_SWIZZLE_64B);
    CUtensorMap tm_wq = make_map(enc, d_in[3], NH * DH, D, 32, 160, CU_TENSOR_MAP_SWIZZLE_64B);
    CUtensorMap tm_wo = make_map(enc, d_in[4], D, NH * DH, 32, 128, CU_TENSOR_MAP_SWIZZLE_64B);
    CUtensorMap tm_w1 = make_map(enc, d_in[6], FF, D, 32, 160, CU_TENSOR_MAP_SWIZZLE_64B);
    CUtensorMap tm_w2 = make_map(enc, d_in[8], D, FF, 64, 32, CU_TENSOR_MAP_SWIZZLE_128B);
    CUtensorMap tm_v = make_map(enc, d_in[2], DH, NB * NH * SK, 64, TILE_KEYS, CU_TENSOR_MAP_SWIZZLE_128B);
    fused_kernel<<<NCTA, NTHREADS, SMEM_BYTES>>>(p, tm_wmod, tm_wq, tm_wo, tm_w1, tm_w2, tm_v);
}
```

```cpp
#include <cuda_runtime.h>
#include <cuda.h>
#include <cuda_bf16.h>
#include <stdint.h>

namespace {

constexpr int NB = 4, D = 640, NH = 32, DH = 128, SK = 8192, WIN = 2048, FF = 1728, NMOD = 6 * D;
constexpr int NCTA = 128;
constexpr int NOWN = 80;
constexpr int NF = 54;
constexpr int NTHREADS = 320;
constexpr int TILE_KEYS = 64;
constexpr int TILE_BYTES = TILE_KEYS * DH * 2;
constexpr int NITEM = 2 * WIN / TILE_KEYS;
constexpr int NS = 8;
constexpr int NMODC = 120;
constexpr int SPIN_LIMIT = 1 << 18;
#define INFLIGHT 3
#define PACE_A 8000
#define PACE_TAU 635
#define WQ_DELAY 400
#define WO_GATE 2
#define WF_GATE 2
#define WF_DELAY 0
#define W2_DELAY 0
#define WF_ALL 0
#define NPROBE 8
#define PROBE_END 10000
#define LAT_T 2100
#define WO_T -1100
#define WO_S 200
#define W1_T 900
#define W2_T 1200
#define EARLY_RESET
#define PH_GAIN 8
#define LAT_FROM 99
#define LAT_END 0
#define PH_FIRST 20
#define PH_LAG 5
#define W1_S 0
#define W2_S 0
#define PF_END 14
#define FIRST_TOP 2
#define CLR_CHECK 28000
constexpr int SEG_J = 8;

constexpr int OFF_RING = 0;
constexpr int OFF_X = OFF_RING + NS * TILE_BYTES;
constexpr int X_WM = OFF_X;
constexpr int X_WQ = OFF_X + D * 64;
constexpr int X_WO = OFF_X;
constexpr int X_W1 = X_WO + 5 * DH * 64;
constexpr int X_END = X_W1 + D * 64;
constexpr int X_W2 = OFF_RING;
static_assert(X_WQ + D * 64 <= X_END, "prologue weights must fit");
constexpr int VEC_STRIDE = 1296;
constexpr int OFF_VA = X_END;
constexpr int OFF_VB = OFF_VA + 4 * VEC_STRIDE;
constexpr int OFF_RED = OFF_VB + 4 * VEC_STRIDE;
constexpr int OFF_ML = OFF_RED + 4096;
constexpr int O_STRIDE = 288;
constexpr int OFF_O = OFF_ML + 64;
constexpr int OFF_Q = OFF_O + 4 * O_STRIDE;
constexpr int OFF_OWN = OFF_Q + 256;
constexpr int OWN_X = OFF_OWN, OWN_B2 = OWN_X + 64, OWN_GA = OWN_B2 + 64, OWN_GB = OWN_GA + 64, OWN_B1 = OWN_GB + 64;
constexpr int OFF_STAT = OWN_B1 + 128;
constexpr int OFF_TAB1 = OFF_STAT + 32;
constexpr int OFF_TAB2 = OFF_TAB1 + NOWN * 4;
constexpr int OFF_SIDE = OFF_TAB2 + NOWN * 4;
constexpr int OFF_BAR = OFF_SIDE + 8;
constexpr int NBAR = 2 * NS + 27;
constexpr int SMEM_BYTES = OFF_BAR + NBAR * 8;
constexpr int SC_OP = OFF_RING + 4 * TILE_BYTES;
constexpr int SC_AB = SC_OP + 4096;
constexpr int SC_Y = SC_AB + 8192;
constexpr int SC_ST = SC_Y + 4096;
constexpr int SC_E4 = SC_ST + 256;
constexpr int SC_E6 = SC_E4 + 1024;
constexpr int SC_P = SC_E6 + 1024;
constexpr int SC_H1 = SC_P + 256;
static_assert(SMEM_BYTES <= 232448, "smem");
static_assert(OFF_BAR % 8 == 0 && OFF_X % 1024 == 0 && X_WQ % 512 == 0 && X_W1 % 512 == 0 && OFF_VA % 16 == 0 && OFF_RED % 16 == 0 && OFF_ML % 16 == 0 && OFF_O % 16 == 0 && OFF_Q % 16 == 0, "align");
constexpr int NB_O = 2  , NB_E4 = 10, NB_E6 = 11, NB_AB = 12, NB_Y = 13;

__device__ uint32_t g_mod[NMODC * 64];
__device__ uint32_t g_q[NCTA * 64];
__device__ uint32_t g_clr[NCTA];
__device__ uint32_t g_phase[16 * 32];
constexpr int SL_P1 = 0;
constexpr int SL_P2 = SL_P1 + NOWN;
constexpr int SL_O = SL_P2 + 2 * NOWN;
constexpr int SL_X1 = SL_O + 8;
constexpr int SL_SIDE = SL_X1 + 3;
static_assert(SL_SIDE < 256, "one 2 MB page");
__device__ uint32_t g_slots[2 * 256 * 2048];
__device__ __forceinline__ uint32_t* slot(int i, int side) {
    const size_t base = ((size_t)g_slots + 0x1fffff) & ~(size_t)0x1fffff;
    return (uint32_t*)base + i * 2048 + (((__popc(i & 0x59) ^ side) & 1) << 10);
}
#define PROF_DECL
#define HPROF(i) do { } while (0)
#define PROF(i) do { } while (0)
#define PROF_DUMP do { } while (0)

__device__ __forceinline__ uint32_t smem_u32(const void* p) { return (uint32_t)__cvta_generic_to_shared(p); }
__device__ __forceinline__ void mbar_init(uint32_t bar, uint32_t cnt) { asm volatile("mbarrier.init.shared::cta.b64 [%0], %1;" ::"r"(bar), "r"(cnt) : "memory"); }
__device__ __forceinline__ void mbar_expect_tx(uint32_t bar, uint32_t bytes) { asm volatile("mbarrier.arrive.expect_tx.shared::cta.b64 _, [%0], %1;" ::"r"(bar), "r"(bytes) : "memory"); }
__device__ __forceinline__ void mbar_arrive(uint32_t bar) { asm volatile("mbarrier.arrive.shared::cta.b64 _, [%0];" ::"r"(bar) : "memory"); }
__device__ __forceinline__ void mbar_wait(uint32_t bar, uint32_t parity) {
    uint32_t ok;
    int it = 0;
    while (true) {
        asm volatile("{\n.reg .pred p;\nmbarrier.try_wait.parity.shared::cta.b64 p, [%1], %2;\nselp.u32 %0, 1, 0, p;\n}" : "=r"(ok) : "r"(bar), "r"(parity) : "memory");
        if (ok) break;
        if (++it > SPIN_LIMIT) __trap();
    }
}
__device__ __forceinline__ void bulk_load(uint32_t dst, const void* src, uint32_t bytes, uint32_t bar, uint64_t pol) {
    asm volatile("cp.async.bulk.shared::cluster.global.mbarrier::complete_tx::bytes.L2::cache_hint [%0], [%1], %2, [%3], %4;"
                 ::"r"(dst), "l"(src), "r"(bytes), "r"(bar), "l"(pol) : "memory");
}
__device__ __forceinline__ void bar_cons() { asm volatile("bar.sync 1, 256;" ::: "memory"); }
template <int ID, int N> __device__ __forceinline__ void nbar_sync() { asm volatile("bar.sync %0, %1;" ::"n"(ID), "n"(N) : "memory"); }
template <int ID, int N> __device__ __forceinline__ void nbar_arrive() { asm volatile("bar.arrive %0, %1;" ::"n"(ID), "n"(N) : "memory"); }
__device__ __forceinline__ bool mbar_test(uint32_t bar, uint32_t parity) {
    uint32_t ok;
    asm volatile("{\n.reg .pred p;\nmbarrier.test_wait.parity.shared::cta.b64 p, [%1], %2;\nselp.u32 %0, 1, 0, p;\n}" : "=r"(ok) : "r"(bar), "r"(parity) : "memory");
    return ok;
}
__device__ __forceinline__ uint32_t pin(uint32_t v) { asm volatile("" : "+r"(v)); return v; }
template <class T> __device__ __forceinline__ T* pin(T* v) { asm volatile("" : "+l"(v)); return v; }
__device__ __forceinline__ void ldsm4(uint32_t (&a)[4], uint32_t addr) {
    asm volatile("ldmatrix.sync.aligned.m8n8.x4.shared.b16 {%0,%1,%2,%3}, [%4];" : "=r"(a[0]), "=r"(a[1]), "=r"(a[2]), "=r"(a[3]) : "r"(addr) : "memory");
}
__device__ __forceinline__ void ldsm4t(uint32_t (&a)[4], uint32_t addr) {
    asm volatile("ldmatrix.sync.aligned.m8n8.x4.trans.shared.b16 {%0,%1,%2,%3}, [%4];" : "=r"(a[0]), "=r"(a[1]), "=r"(a[2]), "=r"(a[3]) : "r"(addr) : "memory");
}
__device__ __forceinline__ void mma16816(float (&c)[4], const uint32_t (&a)[4], uint32_t b0, uint32_t b1) {
    asm volatile("mma.sync.aligned.m16n8k16.row.col.f32.bf16.bf16.f32 {%0,%1,%2,%3}, {%4,%5,%6,%7}, {%8,%9}, {%0,%1,%2,%3};"
                 : "+f"(c[0]), "+f"(c[1]), "+f"(c[2]), "+f"(c[3]) : "r"(a[0]), "r"(a[1]), "r"(a[2]), "r"(a[3]), "r"(b0), "r"(b1));
}
__device__ __forceinline__ uint32_t lds32(uint32_t addr) { uint32_t v; asm volatile("ld.shared.u32 %0, [%1];" : "=r"(v) : "r"(addr) : "memory"); return v; }
__device__ __forceinline__ float lds_f32(uint32_t addr) { float v; asm volatile("ld.shared.f32 %0, [%1];" : "=f"(v) : "r"(addr) : "memory"); return v; }
__device__ __forceinline__ float2 lds_f32x2(uint32_t addr) { float2 v; asm volatile("ld.shared.v2.f32 {%0,%1}, [%2];" : "=f"(v.x), "=f"(v.y) : "r"(addr) : "memory"); return v; }
__device__ __forceinline__ float4 lds_f32x4(uint32_t addr) { float4 v; asm volatile("ld.shared.v4.f32 {%0,%1,%2,%3}, [%4];" : "=f"(v.x), "=f"(v.y), "=f"(v.z), "=f"(v.w) : "r"(addr) : "memory"); return v; }
__device__ __forceinline__ uint2 lds64(uint32_t addr) { uint2 v; asm volatile("ld.shared.v2.u32 {%0,%1}, [%2];" : "=r"(v.x), "=r"(v.y) : "r"(addr) : "memory"); return v; }
__device__ __forceinline__ uint4 lds128(uint32_t addr) { uint4 v; asm volatile("ld.shared.v4.u32 {%0,%1,%2,%3}, [%4];" : "=r"(v.x), "=r"(v.y), "=r"(v.z), "=r"(v.w) : "r"(addr) : "memory"); return v; }
__device__ __forceinline__ void sts16(uint32_t addr, uint32_t v) { asm volatile("st.shared.b16 [%0], %1;" ::"r"(addr), "h"((unsigned short)v) : "memory"); }
__device__ __forceinline__ void sts32(uint32_t addr, uint32_t v) { asm volatile("st.shared.u32 [%0], %1;" ::"r"(addr), "r"(v) : "memory"); }
__device__ __forceinline__ void sts_f32(uint32_t addr, float v) { asm volatile("st.shared.f32 [%0], %1;" ::"r"(addr), "f"(v) : "memory"); }
__device__ __forceinline__ void sts_f32x2(uint32_t addr, float a, float b) { asm volatile("st.shared.v2.f32 [%0], {%1,%2};" ::"r"(addr), "f"(a), "f"(b) : "memory"); }
__device__ __forceinline__ void sts128(uint32_t addr, uint4 v) { asm volatile("st.shared.v4.u32 [%0], {%1,%2,%3,%4};" ::"r"(addr), "r"(v.x), "r"(v.y), "r"(v.z), "r"(v.w) : "memory"); }
__device__ __forceinline__ uint4 ldg_relaxed(const uint32_t* p) {
    uint4 v;
    asm volatile("ld.relaxed.gpu.global.v4.u32 {%0,%1,%2,%3}, [%4];" : "=r"(v.x), "=r"(v.y), "=r"(v.z), "=r"(v.w) : "l"(p) : "memory");
    return v;
}
__device__ __forceinline__ void ldg_relaxed_if(bool on, uint4& v, const uint32_t* p) {
    asm volatile("{\n.reg .pred q;\nsetp.ne.u32 q, %5, 0;\n@q ld.relaxed.gpu.global.v4.u32 {%0,%1,%2,%3}, [%4];\n}"
                 : "+r"(v.x), "+r"(v.y), "+r"(v.z), "+r"(v.w) : "l"(p), "r"((uint32_t)on) : "memory");
}
__device__ __forceinline__ void stg_relaxed2_if(bool on, uint32_t* p, uint32_t a, uint32_t b) {
    asm volatile("{\n.reg .pred q;\nsetp.ne.u32 q, %3, 0;\n@q st.relaxed.gpu.global.v2.u32 [%0], {%1,%2};\n}" ::"l"(p), "r"(a), "r"(b), "r"((uint32_t)on) : "memory");
}
__device__ __forceinline__ uint32_t ldg_relaxed32(const uint32_t* p) { uint32_t v; asm volatile("ld.relaxed.gpu.global.u32 %0, [%1];" : "=r"(v) : "l"(p) : "memory"); return v; }
__device__ __forceinline__ void stg_relaxed(uint32_t* p, uint32_t v) { asm volatile("st.relaxed.gpu.global.u32 [%0], %1;" ::"l"(p), "r"(v) : "memory"); }
__device__ __forceinline__ void stg_relaxed2(uint32_t* p, uint32_t a, uint32_t b) { asm volatile("st.relaxed.gpu.global.v2.u32 [%0], {%1,%2};" ::"l"(p), "r"(a), "r"(b) : "memory"); }
__device__ __forceinline__ void stg_zero4(uint32_t* p) { asm volatile("st.relaxed.gpu.global.v4.u32 [%0], {%1,%1,%1,%1};" ::"l"(p), "r"(0u) : "memory"); }
__device__ __forceinline__ bool ready(const uint4& v) { return (v.x != 0u) & (v.y != 0u) & (v.z != 0u) & (v.w != 0u); }
__device__ __forceinline__ uint4 inv4(const uint4& v) { return make_uint4(~v.x, ~v.y, ~v.z, ~v.w); }
__device__ __forceinline__ uint32_t pack_bf(float lo, float hi) {
    uint32_t r;
    asm("cvt.rn.bf16x2.f32 %0, %1, %2;" : "=r"(r) : "f"(hi), "f"(lo));
    return r;
}
__device__ __forceinline__ float bfr(float x) { return __uint_as_float(pack_bf(0.f, x) & 0xffff0000u); }
__device__ __forceinline__ float bf_lo(uint32_t w) { return __uint_as_float(w << 16); }
__device__ __forceinline__ float bf_hi(uint32_t w) { return __uint_as_float(w & 0xffff0000u); }
__device__ __forceinline__ float bf2f(__nv_bfloat16 v) { return __bfloat162float(v); }
__device__ __forceinline__ float ex2(float x) { float y; asm("ex2.approx.ftz.f32 %0, %1;" : "=f"(y) : "f"(x)); return y; }
__device__ __forceinline__ float rcp_fast(float x) { float y; asm("rcp.approx.ftz.f32 %0, %1;" : "=f"(y) : "f"(x)); return y; }
__device__ __forceinline__ float rsqrt_fast(float x) { float y; asm("rsqrt.approx.ftz.f32 %0, %1;" : "=f"(y) : "f"(x)); return y; }
__device__ __forceinline__ float sqrt_fast(float x) { float y; asm("sqrt.approx.f32 %0, %1;" : "=f"(y) : "f"(x)); return y; }
__device__ __forceinline__ uint32_t bf2_add(uint32_t a, uint32_t b) { uint32_t r; asm("add.rn.bf16x2 %0, %1, %2;" : "=r"(r) : "r"(a), "r"(b)); return r; }
__device__ __forceinline__ uint32_t bf2_sub(uint32_t a, uint32_t b) { uint32_t r; asm("sub.rn.bf16x2 %0, %1, %2;" : "=r"(r) : "r"(a), "r"(b)); return r; }
__device__ __forceinline__ uint32_t bf2_mul(uint32_t a, uint32_t b) { uint32_t r; asm("mul.rn.bf16x2 %0, %1, %2;" : "=r"(r) : "r"(a), "r"(b)); return r; }
__device__ __forceinline__ uint32_t gtime32() { uint32_t c; asm volatile("mov.u32 %0, %%globaltimer_lo;" : "=r"(c)); return c; }
__device__ __forceinline__ uint32_t clock32() { uint32_t c; asm volatile("mov.u32 %0, %%clock;" : "=r"(c)); return c; }

__device__ __forceinline__ float warp_sum(float v) {
#pragma unroll
    for (int o = 16; o > 0; o >>= 1) v += __shfl_xor_sync(0xffffffffu, v, o);
    return v;
}

struct Params {
    const __nv_bfloat16 *x, *kc, *vc, *b1, *b2, *c;
    __nv_bfloat16* out;
};

__device__ __forceinline__ void tma2d(uint32_t dst, const CUtensorMap* tm, int x, int y, uint32_t bar) {
    asm volatile("cp.async.bulk.tensor.2d.shared::cluster.global.mbarrier::complete_tx::bytes [%0], [%1, {%2, %3}], [%4];"
                 ::"r"(dst), "l"(tm), "r"(x), "r"(y), "r"(bar) : "memory");
}

__device__ __forceinline__ void tma2d_hint(uint32_t dst, const CUtensorMap* tm, int x, int y, uint32_t bar, uint64_t pol) {
    asm volatile("cp.async.bulk.tensor.2d.shared::cluster.global.mbarrier::complete_tx::bytes.L2::cache_hint [%0], [%1, {%2, %3}], [%4], %5;"
                 ::"r"(dst), "l"(tm), "r"(x), "r"(y), "r"(bar), "l"(pol) : "memory");
}
__device__ __forceinline__ uint32_t flag(float v) { return __float_as_uint(v) | 1u; }
__device__ __forceinline__ uint32_t and3(uint32_t a, uint32_t b, uint32_t c) { uint32_t r; asm("lop3.b32 %0, %1, %2, %3, 0x80;" : "=r"(r) : "r"(a), "r"(b), "r"(c)); return r; }
__device__ __forceinline__ uint32_t* slot_ptr(uint32_t lo) {
    uint32_t* r;
    asm volatile("mov.b64 %0, {%1, %2};" : "=l"(r) : "r"(lo), "r"((uint32_t)((size_t)slot(0, 0) >> 32)));
    return r;
}

__device__ __forceinline__ void load_bfrag(uint32_t vec, int stride, int k0, int g, int t, uint32_t& b0, uint32_t& b1) {
    uint32_t a = vec + (g & 3) * stride + (k0 + 2 * t) * 2;
    b0 = lds32(a);
    b1 = lds32(a + 16);
}

__device__ __forceinline__ void ln_finish(float pivot, float sum, float sumsq, uint32_t& m2, float& rden) {
    float dm = sum * (1.f / D);
    float var = fmaxf(sumsq * (1.f / D) - dm * dm, 0.f);
    float mean = pivot + dm;
    m2 = pack_bf(mean, mean);
    rden = rcp_fast(bfr(sqrt_fast(bfr(bfr(var) + 1e-5f))));
}
__device__ __forceinline__ uint32_t ln_mod_pair(uint32_t xw, uint32_t cw, uint32_t sw, uint32_t m2, float rden) {
    uint32_t d = bf2_sub(xw, m2);
    uint32_t ln = pack_bf(bf_lo(d) * rden, bf_hi(d) * rden);
    return bf2_add(bf2_mul(ln, bf2_add(cw, 0x3f803f80u)), sw);
}
__device__ __forceinline__ uint4 ln_mod4(const uint4& x, const uint4& c, const uint4& s, uint32_t m2, float rden) {
    return make_uint4(ln_mod_pair(x.x, c.x, s.x, m2, rden), ln_mod_pair(x.y, c.y, s.y, m2, rden),
                      ln_mod_pair(x.z, c.z, s.z, m2, rden), ln_mod_pair(x.w, c.w, s.w, m2, rden));
}
__device__ __forceinline__ void acc_stats(const uint4& v, float pv, float& s, float& q) {
    const float a0 = bf_lo(v.x) - pv, a1 = bf_hi(v.x) - pv, a2 = bf_lo(v.y) - pv, a3 = bf_hi(v.y) - pv;
    const float a4 = bf_lo(v.z) - pv, a5 = bf_hi(v.z) - pv, a6 = bf_lo(v.w) - pv, a7 = bf_hi(v.w) - pv;
    s += ((a0 + a1) + (a2 + a3)) + ((a4 + a5) + (a6 + a7));
    q += (fmaf(a0, a0, a1 * a1) + fmaf(a2, a2, a3 * a3)) + (fmaf(a4, a4, a5 * a5) + fmaf(a6, a6, a7 * a7));
}
__device__ __forceinline__ uint32_t* mod_slot(int kind, int j, int b) { return g_mod + (kind * 20 + (j >> 2)) * 64 + b * 16 + (j & 3) * 4; }

template <int N>
__device__ __forceinline__ void poll_n(uint4 (&v)[N], const uint32_t* const* ptr, const bool* on) {
    bool pend[N];
#pragma unroll
    for (int i = 0; i < N; i++) pend[i] = on[i];
    int it = 0;
    while (true) {
#pragma unroll
        for (int i = 0; i < N; i++) if (pend[i]) v[i] = ldg_relaxed(ptr[i]);
        bool any = false;
#pragma unroll
        for (int i = 0; i < N; i++) { pend[i] = pend[i] && !ready(v[i]); any |= pend[i]; }
        if (!__any_sync(0xffffffffu, any)) break;
        if (++it > SPIN_LIMIT) __trap();
    }
#pragma unroll
    for (int i = 0; i < N; i++) v[i] = inv4(v[i]);
}
__device__ __forceinline__ uint4 poll1(const uint32_t* p, bool on) {
    uint4 v[1] = {make_uint4(0, 0, 0, 0)};
    const uint32_t* const ptr[1] = {p};
    const bool o[1] = {on};
    poll_n<1>(v, ptr, o);
    return v[0];
}

__device__ __forceinline__ void gelu_stage(uint32_t sb, int m, int lane) {
    const int g = lane >> 2, b = lane & 3;
    const uint32_t y_ld = pin(sb + SC_Y + m * 256 + lane * 8), s_ld = pin(sb + SC_ST + b * 64);
    const uint32_t h_st = pin(sb + SC_H1 + b * 64 + (g >> 1) * 16 + m * 8 + (g & 1) * 2);
    float a0 = 0.f, b0 = lds_f32(sb + OWN_B1 + (16 * m + g) * 4), a1 = 0.f, b1 = lds_f32(sb + OWN_B1 + (16 * m + g + 8) * 4);
    nbar_sync<NB_AB, 320>();
#pragma unroll
    for (int w = 0; w < 8; w++) {
        const float4 t = lds_f32x4(sb + SC_AB + w * 1024 + m * 512 + lane * 16);
        a0 += t.x; b0 += t.y; a1 += t.z; b1 += t.w;
    }
    nbar_sync<NB_Y, 320>();
    float4 q[4];
    float2 y[8];
#pragma unroll
    for (int i = 0; i < 4; i++) q[i] = lds_f32x4(s_ld + i * 16);
#pragma unroll
    for (int w = 0; w < 8; w++) y[w] = lds_f32x2(y_ld + w * 512);
    const float dm = (((q[0].y + q[0].w) + (q[1].y + q[1].w)) + ((q[2].y + q[2].w) + (q[3].y + q[3].w))) * (1.f / D);
    const float sq = ((q[0].x + q[0].z) + (q[1].x + q[1].z)) + ((q[2].x + q[2].z) + (q[3].x + q[3].z));
    const float r = rsqrt_fast(fmaxf(fmaf(-dm, dm, sq * (1.f / D)), 0.f) + 1e-5f);
    const float y0 = ((y[0].x + y[1].x) + (y[2].x + y[3].x)) + ((y[4].x + y[5].x) + (y[6].x + y[7].x));
    const float y1 = ((y[0].y + y[1].y) + (y[2].y + y[3].y)) + ((y[4].y + y[5].y) + (y[6].y + y[7].y));
    const float u0 = fmaf(r, fmaf(dm, a0, -y0), b0), u1 = fmaf(r, fmaf(dm, a1, -y1), b1);
    const float e0 = ex2(u0 * fmaf(u0 * u0, -0.044715f * 2.302208198144325f, -2.302208198144325f));
    const float e1 = ex2(u1 * fmaf(u1 * u1, -0.044715f * 2.302208198144325f, -2.302208198144325f));
    sts16(h_st, pack_bf(u0 * rcp_fast(1.f + e0), 0.f));
    sts16(h_st + 4, pack_bf(u1 * rcp_fast(1.f + e1), 0.f));
#pragma unroll
    for (int w = 0; w < 8; w++) asm volatile("bar.arrive %0, 96;" ::"r"(NB_O + w) : "memory");
}

struct Roles { bool is_f, is_owner; int f, own; };
__device__ __forceinline__ Roles roles(int cta) {
    Roles r;
    r.f = (cta * 27) >> 6;
    r.is_f = (((cta + 1) * 27) >> 6) != r.f;
    r.is_owner = !r.is_f || r.f % 9 == 4;
    r.own = r.is_f ? 74 + r.f / 9 : cta - r.f;
    return r;
}

__global__ void __launch_bounds__(NTHREADS, 1)
fused_kernel(const Params p, const __grid_constant__ CUtensorMap tm_wmod, const __grid_constant__ CUtensorMap tm_wq,
             const __grid_constant__ CUtensorMap tm_wo, const __grid_constant__ CUtensorMap tm_w1, const __grid_constant__ CUtensorMap tm_w2,
             const __grid_constant__ CUtensorMap tm_v) {
    extern __shared__ __align__(1024) unsigned char smem[];
    const uint32_t t_start = gtime32();
    const uint32_t sb = smem_u32(smem);
    const int cta = blockIdx.x;
    const int head = cta >> 2, bown = cta & 3;
#define ROTA 8
#define ROTC 0
    const int rot = (ROTA * head + ROTC * bown) & (NITEM / 2 - 1);
    const char* const kb = (const char*)(p.kc + ((size_t)(bown * NH + head) * SK + (SK - WIN)) * DH);
    uint64_t pol = 0;
    if (threadIdx.x == 256) {
        mbar_init(sb + OFF_BAR, 1);
        asm volatile("fence.mbarrier_init.release.cluster;" ::: "memory");
        asm volatile("createpolicy.fractional.L2::evict_first.b64 %0, 1.0;" : "=l"(pol));
        mbar_expect_tx(sb + OFF_BAR, TILE_BYTES);
        bulk_load(sb + OFF_RING, kb + (size_t)rot * TILE_BYTES, TILE_BYTES, sb + OFF_BAR, pol);
        if ((((cta + 1) * 5) >> 4) != ((cta * 5) >> 4)) {
            const uint32_t bar = sb + OFF_BAR + 2 * NS * 8;
            mbar_init(bar, 1);
            asm volatile("fence.mbarrier_init.release.cluster;" ::: "memory");
            mbar_expect_tx(bar, D * 64);
#pragma unroll 1
            for (int r = 0; r < D; r += 160) tma2d(sb + X_WM + r * 64, &tm_wmod, 32 * ((cta * 5) >> 4), r, bar);
        }
    }
    const uint32_t bar_full = sb + OFF_BAR, bar_empty = bar_full + NS * 8;
    const uint32_t bar_wm = bar_empty + NS * 8, bar_wq = bar_wm + 8, bar_xfree = bar_wq + 8, bar_wo = bar_xfree + 8  ;
    const uint32_t bar_w1 = bar_wo + 40  , bar_w2 = bar_w1 + 32  , bar_help = bar_w2 + 80, bar_v = bar_help + 8  ;
    const int tid = threadIdx.x, warp = tid >> 5, lane = tid & 31;
    const Roles role = roles(cta);
    const bool is_f = role.is_f, is_owner = role.is_owner;
    const int f = role.f, own = role.own;
    const bool crit = (((cta + 1) * 5) >> 4) != ((cta * 5) >> 4);
    const int mr = cta - ((cta * 5) >> 4);
    const bool late = !crit && mr % 11 != 10;
    const int mc = crit ? (cta * 5) >> 4 : 40 + mr - mr / 11;

    PROF_DECL
    PROF(0);
    uint4 xa = make_uint4(0, 0, 0, 0), xb = xa, ca0 = xa, ca1 = xa, xs[3] = {xa, xa, xa};
    uint32_t own0 = 0;
    __nv_bfloat16 own2 = __float2bfloat16(0.f);
    if (warp < 8) {
        xa = *(const uint4*)(p.x + (tid & 3) * D + (tid >> 2) * 8);
        ca0 = ((const uint4*)p.c)[tid];
        if (tid < 64) { xb = *(const uint4*)(p.x + (tid & 3) * D + (64 + (tid >> 2)) * 8); ca1 = ((const uint4*)p.c)[256 + tid]; }
        if (warp < 4) {
#pragma unroll
            for (int i = 0; i < 3; i++) if (lane + 32 * i < 80) xs[i] = ((const uint4*)p.x)[warp * 80 + lane + 32 * i];
        } else if (warp == 4) {
            if (is_owner) own0 = *(const uint32_t*)((lane < 16 ? p.x + (lane >> 2) * D : p.b2) + 8 * own + 2 * (lane & 3));
            if (is_f) own2 = p.b1[32 * f + lane];
        }
    }
    const char* const vb = (const char*)(p.vc + ((size_t)(bown * NH + head) * SK + (SK - WIN)) * DH);
    const uint32_t bar_first = crit ? bar_wm : bar_wq;
    if (threadIdx.x == 256) {
        const uint32_t dst = sb + (crit ? X_WM : X_WQ);
        const CUtensorMap* tm = crit ? &tm_wmod : &tm_wq;
        if (!crit) {
            mbar_init(bar_first, 1);
            asm volatile("fence.mbarrier_init.release.cluster;" ::: "memory");
            mbar_expect_tx(bar_first, D * 64);
        }
        if (!crit) {
            const uint32_t c0 = clock32();
            while (clock32() - c0 < WQ_DELAY) { }
#pragma unroll
            for (int r = 0; r < D; r += 160) tma2d(dst + r * 64, tm, 32 * cta, r, bar_first);
        }
    } else if (threadIdx.x == 0) {
#pragma unroll
        for (int s = 0; s < NS; s++) { if (s) mbar_init(bar_full + s * 8, 1); mbar_init(bar_empty + s * 8, 4); }
        mbar_init(crit ? bar_wq : bar_wm, 1);
        mbar_init(bar_xfree, 1);
#pragma unroll
        for (int i = 0; i < 5; i++) { mbar_init(bar_wo + i * 8, 1); mbar_init(bar_w2 + i * 16, 1); mbar_init(bar_w2 + i * 16 + 8, 1); }
        mbar_init(bar_help, 1);
#pragma unroll
        for (int i = 0; i < 4; i++) { mbar_init(bar_v + i * 8, 1); mbar_init(bar_w1 + i * 8, 1); }
        asm volatile("fence.mbarrier_init.release.cluster;" ::: "memory");
    }
    __syncthreads();

    if (warp == 8) {
        if (lane == 0) {
            int tp = NS;
            int sched = PACE_A - NS * PACE_TAU;
            int phase = 0;
#pragma unroll 1
            for (int t = 1; t <= NITEM; t++) {
                if (t == 1) mbar_wait(bar_full, 0);
                if (t == 2) {
                    mbar_wait(bar_first, 0);
                    if (crit) {
                        mbar_expect_tx(bar_wq, D * 64);
#pragma unroll 1
                        for (int r = 0; r < D; r += 160) tma2d(sb + X_WQ + r * 64, &tm_wq, 32 * cta, r, bar_wq);
                    }
                }
                if (t == 3) {
                    asm volatile("prefetch.tensormap [%0];" ::"l"(&tm_v) : "memory");
                    asm volatile("prefetch.tensormap [%0];" ::"l"(&tm_wo) : "memory");
                    asm volatile("prefetch.tensormap [%0];" ::"l"(&tm_w1) : "memory");
                    asm volatile("prefetch.tensormap [%0];" ::"l"(&tm_w2) : "memory");
                }
                if (t == NS && late) {
                    mbar_wait(bar_full + (NS - INFLIGHT) * 8, 0);
                    mbar_expect_tx(bar_wm, D * 64);
#pragma unroll 1
                    for (int r = 0; r < D; r += 160) tma2d(sb + X_WM + r * 64, &tm_wmod, 32 * mc, r, bar_wm);
                }
                if (t >= NS && t < PF_END) {
                    int it = 0;
                    while (!mbar_test(bar_empty + (t & (NS - 1)) * 8, ((t >> 3) - 1) & 1)) {
                        if (tp < PF_END && (int)(gtime32() - t_start) >= PACE_A + (tp - NS) * PACE_TAU) {
                            asm volatile("cp.async.bulk.prefetch.L2.global.L2::cache_hint [%0], %1, %2;"
                                         ::"l"(((tp & 1) ? vb : kb) + (size_t)(((tp >> 1) + rot) & (NITEM / 2 - 1)) * TILE_BYTES), "r"(TILE_BYTES), "l"(pol) : "memory");
                            tp++;
                        }
                        if (++it > 16 * SPIN_LIMIT) __trap();
                    }
                    if (tp <= t) tp = t + 1;
                }
                if (t == NITEM) {
                    mbar_wait(bar_xfree, 0);
                    const uint32_t t_ref = t_start + phase + (NITEM - 1) * PACE_TAU;
#pragma unroll 1
                    for (int i = 0; i < 5; i++) {
                        while ((int)(gtime32() - t_ref) < WO_T + i * WO_S) { }
                        mbar_expect_tx(bar_wo + i * 8, DH * 64);
                        tma2d(sb + X_WO + i * (DH * 64), &tm_wo, bown * 160 + i * 32, head * DH, bar_wo + i * 8);
                    }
                    if (is_f) {
#pragma unroll 1
                        for (int i = 0; i < 4; i++) {
                            while ((int)(gtime32() - t_ref) < W1_T + i * W1_S) { }
                            mbar_expect_tx(bar_w1 + i * 8, 160 * 64);
                            tma2d(sb + X_W1 + i * (160 * 64), &tm_w1, 32 * f, 160 * i, bar_w1 + i * 8);
                        }
#pragma unroll 1
                        for (int i = 0; i < 3; i++) mbar_wait(bar_empty + i * 8, ((NITEM >> 3) - 1) & 1);
#pragma unroll 1
                        for (int i = 0; i < 10; i++) {
                            while ((int)(gtime32() - t_ref) < W2_T + i * W2_S) { }
                            mbar_expect_tx(bar_w2 + i * 8, 4096);
                            tma2d(sb + X_W2 + i * 4096, &tm_w2, 64 * i, 32 * f, bar_w2 + i * 8);
                        }
                    }
                    break;
                    if (WO_GATE <= 2) { mbar_wait(bar_v + (2 - WO_GATE) * 16, 0); mbar_wait(bar_v + (2 - WO_GATE) * 16 + 8, 0); }
                    else mbar_wait(bar_full + ((NITEM - WO_GATE) & (NS - 1)) * 8, ((NITEM - WO_GATE) >> 3) & 1);
#pragma unroll 1
                    for (int i = 0; i < 5; i++) {
                        mbar_expect_tx(bar_wo + i * 8, DH * 64);
                        tma2d(sb + X_WO + i * (DH * 64), &tm_wo, bown * 160 + i * 32, head * DH, bar_wo + i * 8);
                    }
                    if (is_f) {
                        mbar_wait(bar_wo + WF_GATE * 8, 0);
                        { const uint32_t c0 = clock32(); while (clock32() - c0 < WF_DELAY) { } }
#pragma unroll 1
                        for (int i = 0; i < 4; i++) {
                            mbar_expect_tx(bar_w1 + i * 8, 160 * 64);
                            tma2d(sb + X_W1 + i * (160 * 64), &tm_w1, 32 * f, 160 * i, bar_w1 + i * 8);
                        }
#pragma unroll 1
                        for (int i = 0; i < 3; i++) mbar_wait(bar_empty + i * 8, ((NITEM >> 3) - 1) & 1);
                        { const uint32_t c0 = clock32(); while (clock32() - c0 < W2_DELAY) { } }
#pragma unroll 1
                        for (int i = 0; i < 10; i++) {
                            mbar_expect_tx(bar_w2 + i * 8, 4096);
                            tma2d(sb + X_W2 + i * 4096, &tm_w2, 64 * i, 32 * f, bar_w2 + i * 8);
                        }
                    }
                    break;
                }
                const int s = t & (NS - 1);
                if (t >= NS) {
                    mbar_wait(bar_empty + s * 8, ((t >> 3) - 1) & 1);
                    while ((int)(gtime32() - t_start) < sched + t * PACE_TAU) { }
                } else if (t >= INFLIGHT) {
                    mbar_wait(bar_full + (t - INFLIGHT) * 8, 0);
                }
                if (t < NITEM - 2) {
                    const int pair = t == NITEM - 3 ? NITEM / 2 - 1 : t >> 1;
                    mbar_expect_tx(bar_full + s * 8, TILE_BYTES);
                    bulk_load(sb + OFF_RING + s * TILE_BYTES, ((t & 1) && t != NITEM - 3 ? vb : kb) + (size_t)((pair + rot) & (NITEM / 2 - 1)) * TILE_BYTES, TILE_BYTES, bar_full + s * 8, pol);
                } else {
                    const int row = (bown * NH + head) * SK + (SK - WIN) + ((t - NITEM / 2 + rot) & (NITEM / 2 - 1)) * TILE_KEYS;
#pragma unroll 1
                    for (int i = 0; i < 2; i++) {
                        const uint32_t bar = bar_v + (2 * (t - (NITEM - 2)) + i) * 8;
                        mbar_expect_tx(bar, TILE_BYTES / 2);
                        tma2d_hint(sb + OFF_RING + s * TILE_BYTES + i * (TILE_BYTES / 2), &tm_v, 64 * i, row, bar, pol);
                    }
                }
                if (t >= PH_FIRST + PH_LAG && (t & 3) == (PH_LAG & 3)) {
                    const int now = (int)(gtime32() - t_start) - (t - PH_LAG) * PACE_TAU;
                    uint32_t ph;
                    asm volatile("atom.relaxed.gpu.global.add.u32 %0, [%1], 0;" : "=r"(ph) : "l"(g_phase + ((t - PH_LAG) >> 2) * 32) : "memory");
                    const int mean = ((ph & 0xffffffu) * 4 + (NCTA - (ph >> 24)) * now) >> 7;
                    phase = t < PH_FIRST + PH_LAG + 4 ? mean : phase + (mean - phase) * PH_GAIN / 8;
                    sched = phase - (t >= LAT_FROM ? LAT_END : LAT_T);
                }
            }
        }
        __syncwarp();
    }

    if (warp == 9) {
        int side = 0;
        if (lane == 0) {
            uint32_t best[2] = {~0u, ~0u};
#pragma unroll 1
            for (int i = 0; i < 2 * NPROBE && ((i & 1) || (int)(gtime32() - t_start) < PROBE_END); i++) {
                uint32_t t0 = clock32(), v, t1;
                asm volatile("atom.relaxed.gpu.global.exch.b32 %0, [%1], %2;" : "=r"(v) : "l"(slot(SL_SIDE, i & 1) + cta * 8), "r"(0u) : "memory");
                asm volatile("{\n.reg .pred p;\nsetp.ne.u32 p, %1, 0xffffffff;\nmov.u32 %0, 0;\n@p mov.u32 %0, %%clock;\n}" : "=r"(t1) : "r"(v) : "memory");
                if (i & 1) best[1] = min(best[1], t1 - t0); else best[0] = min(best[0], t1 - t0);
            }
            side = best[1] < best[0];
        }
        side = __shfl_sync(0xffffffffu, side, 0);
        HPROF(1);
        mbar_wait(bar_full + (NS - 1) * 8, 0);
        stg_zero4(slot(SL_O + (cta >> 4), lane >> 4) + (cta & 15) * 64 + (lane & 15) * 4);
        if (is_owner) {
#pragma unroll 1
            for (int i = lane; i < NH * 8; i += 32) stg_zero4(slot(SL_P1 + own, side) + i * 4);
#pragma unroll 1
            for (int i = lane; i < NF * 8; i += 32) stg_zero4(slot(SL_P2 + 2 * own + (i >> 8), side) + (i & 255) * 4);
            if (lane < 8) stg_zero4(slot(SL_X1 + own / 30, lane >> 2) + (own % 30) * 32 + (lane & 3) * 4);
        }
        __threadfence();
        __syncwarp();
        if (lane == 0) stg_relaxed(g_clr + cta, 1u + side);
        HPROF(0);
        HPROF(2);
        while ((int)(gtime32() - t_start) < CLR_CHECK) __nanosleep(1000);
        mbar_wait(bar_xfree, 0);
        {
            uint4 v = make_uint4(1, 1, 1, 1), gv = v, mv[20];
#pragma unroll
            for (int i = 0; i < 20; i++) mv[i] = v;
#pragma unroll 1
            for (int it = 0;; it++) {
                v = ldg_relaxed(g_clr + lane * 4);
                ldg_relaxed_if(is_owner && lane < 8, gv, mod_slot(lane < 4 ? 2 : 5, own, lane & 3));
#pragma unroll
                for (int i = 0; i < 20; i++) ldg_relaxed_if(is_f, mv[i], mod_slot(3, 8 * i + (lane >> 2), lane & 3));
                bool ok = ready(v) && ready(gv);
#pragma unroll
                for (int i = 0; i < 20; i++) ok = ok && ready(mv[i]);
                if (__all_sync(0xffffffffu, ok)) break;
                if (it > SPIN_LIMIT) __trap();
                __nanosleep(2000);
            }
            const uint32_t w[4] = {v.x, v.y, v.z, v.w};
#pragma unroll
            for (int i = 0; i < 4; i++) {
                const Roles r = roles(4 * lane + i);
                if (r.is_owner) {
                    sts32(sb + OFF_TAB1 + r.own * 4, (uint32_t)(size_t)(slot(SL_P1 + r.own, w[i] - 1) + head * 32));
                    sts32(sb + OFF_TAB2 + r.own * 4, (uint32_t)(size_t)(slot(SL_P2 + 2 * r.own + (f >> 5), w[i] - 1) + (f & 31) * 32));
                }
            }
            if (lane == 0) sts32(sb + OFF_SIDE, side);
            if (lane < 8) sts128(sb + OWN_GA + lane * 16, inv4(gv));
            const uint32_t dst = sb + OFF_VA + (lane & 3) * VEC_STRIDE + (lane >> 2) * 16;
#pragma unroll
            for (int i = 0; i < 10; i++) {
                const uint4 c = inv4(mv[10 + i]);
                sts128(dst + i * 128, make_uint4(bf2_add(c.x, 0x3f803f80u), bf2_add(c.y, 0x3f803f80u), bf2_add(c.z, 0x3f803f80u), bf2_add(c.w, 0x3f803f80u)));
                sts128(dst + (OFF_VB - OFF_VA) + i * 128, inv4(mv[i]));
            }
        }
        asm volatile("fence.acq_rel.gpu;" ::: "memory");
        __syncwarp();
        HPROF(3);
        if (lane == 0) mbar_arrive(bar_help);
        {
            const uint32_t* const src = pin(slot(SL_O + (cta >> 4), side) + (cta & 12) * 64 + lane * 4);
            const uint32_t dst = pin(sb + OFF_O + (lane >> 4) * O_STRIDE + (lane & 15) * 16);
            mbar_wait(bar_v + 16, 0);
            mbar_wait(bar_v + 24, 0);
            uint4 v[2];
            const uint32_t* const ptr[2] = {src, src + 128};
            const bool on[2] = {true, true};
            poll_n<2>(v, ptr, on);
            sts128(dst, v[0]);
            sts128(dst + 2 * O_STRIDE, v[1]);
#pragma unroll
            for (int w = 0; w < 8; w++) asm volatile("bar.arrive %0, 64;" ::"r"(NB_O + w) : "memory");
        }
        HPROF(4);
    }
    if (warp >= 8) {
        if (is_f) gelu_stage(sb, warp - 8, lane);
        return;
    }

    const int g = lane >> 2, t4 = lane & 3;
    const int mi = lane >> 3, r8 = lane & 7;

    {
        auto silu4 = [&](const uint4& cv) {
            uint32_t w4[4] = {cv.x, cv.y, cv.z, cv.w};
#pragma unroll
            for (int e = 0; e < 4; e++) {
                float c0 = bf_lo(w4[e]), c1 = bf_hi(w4[e]);
                w4[e] = pack_bf(c0 * rcp_fast(1.f + ex2(-1.4426950408889634f * c0)), c1 * rcp_fast(1.f + ex2(-1.4426950408889634f * c1)));
            }
            return make_uint4(w4[0], w4[1], w4[2], w4[3]);
        };
        if (crit || late) {
            uint4 v = silu4(ca0);
            sts128(sb + OFF_VA + (tid / 80) * VEC_STRIDE + (tid % 80) * 16, v);
            if (tid < 64) { v = silu4(ca1); sts128(sb + OFF_VA + 3 * VEC_STRIDE + (16 + tid) * 16, v); }
        }
        if (warp < 4) {
            float s = 0.f, q = 0.f;
            const float pv = __shfl_sync(0xffffffffu, bf_lo(xs[0].x), 0);
#pragma unroll
            for (int i = 0; i < 3; i++) if (i < 2 || lane < 16) acc_stats(xs[i], pv, s, q);
#pragma unroll
            for (int of = 16; of > 0; of >>= 1) { s += __shfl_xor_sync(0xffffffffu, s, of); q += __shfl_xor_sync(0xffffffffu, q, of); }
            uint32_t m2; float rden;
            ln_finish(pv, s, q, m2, rden);
            if (lane == 0) { sts32(sb + OFF_STAT + warp * 8, m2); sts_f32(sb + OFF_STAT + warp * 8 + 4, rden); }
        } else if (warp == 4) {
            sts32(sb + OWN_X + lane * 4, bf2_add(own0, 0u));
            sts_f32(sb + OWN_B1 + lane * 4, bf2f(own2));
        }
    }
    bar_cons();
    PROF(24);
    uint32_t qf[8][2];
    float o[8][4];
#pragma unroll
    for (int c = 0; c < 8; c++) { o[c][0] = o[c][1] = o[c][2] = o[c][3] = 0.f; }
    float m_run = -INFINITY, l_run = 0.f;
    const bool diag = (t4 == (g >> 1));
    const bool odd = g & 1;
    const uint32_t koff = (warp & 3) * 4096 + (r8 + 8 * (mi & 1)) * 256 + (mi >> 1) * 128 + (r8 << 4);
    const uint32_t voff = TILE_BYTES + (warp & 3) * 4096 + (r8 + 8 * (mi >> 1)) * 256 + (mi & 1) * 128 + (r8 << 4);
    const int src0 = (2 * t4) * 4 + t4, src1 = (2 * t4 + 1) * 4 + t4;
#pragma unroll 1
    for (int step = crit ? 0 : 1; step < 3; step++) {
        if (step < 2 || late) {
            if (step == 1) {
                if (!crit) mbar_wait(bar_wq, 0);
                const uint32_t m2 = lds32(sb + OFF_STAT + (tid & 3) * 8);
                const float rden = lds_f32(sb + OFF_STAT + (tid & 3) * 8 + 4);
                uint4 v[4] = {xa, xa, xa, xa};
                const uint32_t* const ptr[4] = {mod_slot(0, tid >> 2, tid & 3), mod_slot(1, tid >> 2, tid & 3),
                                                mod_slot(0, 64 + ((tid & 63) >> 2), tid & 3), mod_slot(1, 64 + ((tid & 63) >> 2), tid & 3)};
                const bool on[4] = {true, true, tid < 64, tid < 64};
                poll_n<4>(v, ptr, on);
                uint4 h0 = ln_mod4(xa, v[1], v[0], m2, rden);
                sts128(sb + OFF_VB + (tid & 3) * VEC_STRIDE + (tid >> 2) * 16, h0);
                if (tid < 64) {
                    h0 = ln_mod4(xb, v[3], v[2], m2, rden);
                    sts128(sb + OFF_VB + (tid & 3) * VEC_STRIDE + (64 + (tid >> 2)) * 16, h0);
                }
            }
            mbar_wait(step == 1 ? bar_wq : bar_wm, 0);
            bar_cons();
            const uint32_t strip = sb + (step == 1 ? X_WQ : X_WM), vec = sb + (step == 1 ? OFF_VB : OFF_VA);
            float acc[2][4];
#pragma unroll
            for (int m = 0; m < 2; m++) { acc[m][0] = acc[m][1] = acc[m][2] = acc[m][3] = 0.f; }
#pragma unroll
            for (int i = 0; i < 5; i++) {
                int k0 = (warp * 5 + i) * 16;
                uint32_t b0, b1;
                load_bfrag(vec, VEC_STRIDE, k0, g, t4, b0, b1);
                int krow = k0 + r8 + 8 * (mi >> 1);
#pragma unroll
                for (int m = 0; m < 2; m++) {
                    uint32_t a[4];
                    int ch = 2 * m + (mi & 1);
                    ldsm4t(a, strip + krow * 64 + ((ch ^ ((krow >> 1) & 3)) << 4));
                    mma16816(acc[m], a, b0, b1);
                }
            }
            if (t4 < 2) {
#pragma unroll
                for (int m = 0; m < 2; m++) {
                    sts_f32x2(sb + OFF_RED + ((warp * 32 + m * 16 + g) * 4 + 2 * t4) * 4, acc[m][0], acc[m][1]);
                    sts_f32x2(sb + OFF_RED + ((warp * 32 + m * 16 + g + 8) * 4 + 2 * t4) * 4, acc[m][2], acc[m][3]);
                }
            }
            bar_cons();
            if (tid < 128) {
                float v = 0.f;
#pragma unroll
                for (int w = 0; w < 8; w++) v += lds_f32(sb + OFF_RED + (w * 128 + tid) * 4);
                float vn = __shfl_down_sync(0xffffffffu, v, 4);
                uint32_t* dst = step == 1 ? g_q + ((cta & ~3) + (tid & 3)) * 64 + bown * 16 + (tid >> 3) : g_mod + mc * 64 + (tid & 3) * 16 + (tid >> 3);
                if (!((tid >> 2) & 1)) stg_relaxed(dst, ~pack_bf(v, vn));
            }
        }
        if (step == 0) continue;
        if (step == 1) {
            if (warp == 0) {
                uint4 v = poll1(g_q + cta * 64 + (lane & 15) * 4, lane < 16);
                if (lane < 16) {
                    sts128(sb + OFF_Q + lane * 16, v);
                    stg_zero4(g_q + cta * 64 + lane * 4);
                }
            }
            bar_cons();
            PROF(4);

#pragma unroll
            for (int c = 0; c < 8; c++) {
                qf[c][0] = lds32(sb + OFF_Q + (((c ^ g) * 4 + t4) << 2));
                qf[c][1] = lds32(sb + OFF_Q + 128 + (((c ^ g) * 4 + t4) << 2));
            }
        } else {
            bar_cons();
            if (tid == 0) mbar_arrive(bar_xfree);
        }
#pragma unroll 1
        for (int j = (step == 1 ? 0 : SEG_J) + (warp >> 2); j < (step == 1 ? SEG_J : NITEM / 2 - 2); j += 2) {
            const int s = (2 * j) & (NS - 1);
            const uint32_t par = (j >> 2) & 1;
            mbar_wait(bar_full + s * 8, par);
            if (tid == 0 && 2 * j >= PH_FIRST) {
                const int x = min(max((int)(gtime32() - t_start) - 2 * j * PACE_TAU, 0), 65535);
                asm volatile("red.relaxed.gpu.global.add.u32 [%0], %1;" ::"l"(g_phase + (j >> 1) * 32), "r"((1u << 24) + (x >> 2)) : "memory");
            }
            const uint32_t base = sb + OFF_RING + s * TILE_BYTES;
            float sa[4] = {0.f, 0.f, 0.f, 0.f}, sb2[4] = {0.f, 0.f, 0.f, 0.f};
#pragma unroll
            for (int c = 0; c < 8; c += 2) {
                uint32_t a[4], a2[4];
                ldsm4(a, (base + koff) ^ (c << 4));
                ldsm4(a2, (base + koff) ^ ((c + 1) << 4));
                mma16816(sa, a, qf[c][0], qf[c][1]);
                mma16816(sb2, a2, qf[c + 1][0], qf[c + 1][1]);
            }
            const uint32_t sw = pack_bf(odd ? sa[1] + sb2[1] : sa[0] + sb2[0], odd ? sa[3] + sb2[3] : sa[2] + sb2[2]);
            const uint32_t sv = pack_bf(bf_lo(sw) * 0.08838834764831845f, bf_hi(sw) * 0.08838834764831845f);
            const float s0 = bf_lo(sv) * 1.4426950408889634f, s1 = bf_hi(sv) * 1.4426950408889634f;
            float m_new = fmaxf(m_run, fmaxf(s0, s1));
            const bool grow = __any_sync(0xffffffffu, (diag && (m_new > m_run)));
            if (lane == 0) mbar_arrive(bar_empty + s * 8);
            if (grow) {
                float al = ex2(m_run - m_new);
                float a0 = __shfl_sync(0xffffffffu, al, src0), a1 = __shfl_sync(0xffffffffu, al, src1);
#pragma unroll
                for (int c = 0; c < 8; c++) { o[c][0] *= a0; o[c][1] *= a1; o[c][2] *= a0; o[c][3] *= a1; }
                l_run *= al;
                m_run = m_new;
            }
            uint32_t pw = pack_bf(ex2(s0 - m_run), ex2(s1 - m_run));
            l_run += bf_lo(pw) + bf_hi(pw);
            uint32_t b0 = odd ? (pw << 16) : (pw & 0xffffu);
            uint32_t b1 = odd ? (pw & 0xffff0000u) : (pw >> 16);
            if (!diag) { b0 = 0u; b1 = 0u; }
            mbar_wait(bar_full + (s + 1) * 8, par);
#pragma unroll
            for (int c = 0; c < 8; c++) {
                uint32_t a[4];
                ldsm4t(a, (base + voff) ^ (c << 4));
                mma16816(o[c], a, b0, b1);
            }
            __syncwarp();
            if (lane == 0) mbar_arrive(bar_empty + (s + 1) * 8);
        }
    }
    PROF(5);
    float acc[4][4];
    uint32_t pa[8][2];
    float rinv;
    {
        const int s = 4 + (warp >> 2);
        mbar_wait(bar_full + s * 8, 1);
        const uint32_t base = sb + OFF_RING + s * TILE_BYTES;
        float sa[4] = {0.f, 0.f, 0.f, 0.f}, sb2[4] = {0.f, 0.f, 0.f, 0.f};
#pragma unroll
        for (int c = 0; c < 8; c += 2) {
            uint32_t a[4], a2[4];
            ldsm4(a, (base + koff) ^ (c << 4));
            ldsm4(a2, (base + koff) ^ ((c + 1) << 4));
            mma16816(sa, a, qf[c][0], qf[c][1]);
            mma16816(sb2, a2, qf[c + 1][0], qf[c + 1][1]);
        }
        const uint32_t sw = pack_bf(odd ? sa[1] + sb2[1] : sa[0] + sb2[0], odd ? sa[3] + sb2[3] : sa[2] + sb2[2]);
        const uint32_t sv = pack_bf(bf_lo(sw) * 0.08838834764831845f, bf_hi(sw) * 0.08838834764831845f);
        const float s0 = bf_lo(sv) * 1.4426950408889634f, s1 = bf_hi(sv) * 1.4426950408889634f;
        int mi_ = __float_as_int(diag ? fmaxf(m_run, fmaxf(s0, s1)) : -INFINITY);
        mi_ ^= (mi_ >> 31) & 0x7fffffff;
        mi_ = __reduce_max_sync(0xffffffffu, mi_);
        mi_ ^= (mi_ >> 31) & 0x7fffffff;
        if (lane == 0) sts32(sb + OFF_ML + warp * 4, mi_);
        bar_cons();
        const float4 m0 = lds_f32x4(sb + OFF_ML), m1 = lds_f32x4(sb + OFF_ML + 16);
        const float mx = fmaxf(fmaxf(fmaxf(m0.x, m0.y), fmaxf(m0.z, m0.w)), fmaxf(fmaxf(m1.x, m1.y), fmaxf(m1.z, m1.w)));
        const float scl = ex2(m_run - mx);
        const uint32_t pw = pack_bf(ex2(s0 - mx), ex2(s1 - mx));
        if (diag) { sts16(sb + SC_P + (warp * 16 + g) * 2, pw); sts16(sb + SC_P + (warp * 16 + g + 8) * 2, pw >> 16); }
        const float lw = warp_sum(diag ? fmaf(l_run, scl, bf_lo(pw) + bf_hi(pw)) : 0.f);
        const float a0 = __shfl_sync(0xffffffffu, scl, src0), a1 = __shfl_sync(0xffffffffu, scl, src1);
        float v[8], u[8];
#pragma unroll
        for (int c = 0; c < 8; c++) {
            v[c] = a0 * o[c][0] + a1 * o[c ^ 1][1];
            u[c] = a0 * o[c][2] + a1 * o[c ^ 1][3];
        }
#pragma unroll
        for (int c = 0; c < 8; c++) {
            if (!(c & 2)) {
                v[c] += __shfl_xor_sync(0xffffffffu, v[c ^ 2], 1);
                u[c] += __shfl_xor_sync(0xffffffffu, u[c ^ 2], 1);
            }
        }
#pragma unroll
        for (int c = 0; c < 2; c++) {
            v[c] += __shfl_xor_sync(0xffffffffu, v[c ^ 4], 2);
            u[c] += __shfl_xor_sync(0xffffffffu, u[c ^ 4], 2);
        }
        const uint32_t dst = sb + SC_OP + (warp * 128 + 16 * t4 + g) * 4;
        sts_f32(dst, v[0]); sts_f32(dst + 32, v[1]); sts_f32(dst + 256, u[0]); sts_f32(dst + 288, u[1]);
        if (lane == 0) sts_f32(sb + OFF_ML + 32 + warp * 4, lw);
        mbar_wait(bar_help, 0);
        bar_cons();
        const float4 l0 = lds_f32x4(sb + OFF_ML + 32), l1 = lds_f32x4(sb + OFF_ML + 48);
        rinv = rcp_fast(((l0.x + l0.y) + (l0.z + l0.w)) + ((l1.x + l1.y) + (l1.z + l1.w)));
#pragma unroll
        for (int i = 0; i < 4; i++) acc[i][0] = acc[i][1] = acc[i][2] = acc[i][3] = 0.f;
#pragma unroll
        for (int w = 0; w < 8; w++) {
            const float2 x0 = lds_f32x2(sb + SC_OP + (w * 128 + 16 * warp + 2 * t4) * 4), x1 = lds_f32x2(sb + SC_OP + (w * 128 + 16 * warp + 8 + 2 * t4) * 4);
            acc[2 * (w & 1)][0] += x0.x; acc[2 * (w & 1)][1] += x0.y;
            acc[2 * (w & 1) + 1][0] += x1.x; acc[2 * (w & 1) + 1][1] += x1.y;
        }
#pragma unroll
        for (int ks = 0; ks < 8; ks++) { pa[ks][0] = lds32(sb + SC_P + (8 * ks + t4) * 4); pa[ks][1] = lds32(sb + SC_P + (8 * ks + 4 + t4) * 4); }
    }
    PROF(20);
    const int mt = warp < 2 ? warp : warp + 2;
    {
        const uint32_t va = pin(sb + OFF_RING + 6 * TILE_BYTES + (warp >> 2) * (TILE_BYTES / 2) + (8 * (mi & 1) + r8) * 128 + (((2 * (warp & 3) + (mi >> 1)) ^ r8) << 4));
        const uint32_t vbar = pin(bar_v + (warp >> 2) * 8);
        uint32_t* const o_dst = pin(slot(SL_O + (cta >> 4), g) + (cta & 15) * 64 + warp * 8 + 2 * t4);
#pragma unroll
        for (int tl = 0; tl < 2; tl++) {
            mbar_wait(vbar + tl * 16, 0);
            uint32_t r[4][4];
#pragma unroll
            for (int ks = 0; ks < 4; ks++) ldsm4t(r[ks], va + tl * TILE_BYTES + ks * 2048);
#pragma unroll
            for (int ks = 0; ks < 4; ks++) {
                const uint32_t a[4] = {pa[4 * tl + ks][0], 0u, pa[4 * tl + ks][1], 0u};
                mma16816(acc[2 * (ks & 1)], a, r[ks][0], r[ks][1]);
                mma16816(acc[2 * (ks & 1) + 1], a, r[ks][2], r[ks][3]);
            }
        }
        stg_relaxed2_if(g < 2, o_dst, ~pack_bf((acc[0][0] + acc[2][0]) * rinv, (acc[0][1] + acc[2][1]) * rinv),
                        ~pack_bf((acc[1][0] + acc[3][0]) * rinv, (acc[1][1] + acc[3][1]) * rinv));
    }
    PROF(7);
    const int side = lds32(sb + OFF_SIDE);
    const uint32_t red_st = pin(sb + SC_E4 + ((warp * 4 + 2 * ((lane >> 3) & 1) + (lane >> 4)) * 8 + (lane & 7)) * 4);
    const uint32_t red_ld = pin(sb + SC_E4 + (lane & 15) * 8);
    const uint32_t* const in1 = pin(slot(SL_P1 + own, side) + tid * 4);
    const uint32_t* const in2a = pin(slot(SL_P2 + 2 * own, side) + tid * 4);
    const uint32_t* const in2b = pin(slot(SL_P2 + 2 * own + 1, side) + tid * 4);
    uint32_t* const x1_dst = pin(slot(SL_X1 + own / 30, lane >> 4) + (own % 30) * 32 + (lane & 15));
    const uint32_t xw = lds32(sb + OWN_X + (lane & 15) * 4), ga_w = lds32(sb + OWN_GA + (lane & 15) * 4);
    uint32_t cs[15];
    uint32_t* dst2[10];
    uint32_t w2a[5];
#pragma unroll
    for (int j = 0; j < 10; j++) cs[j] = lds32(sb + OFF_VA + ((g & 1) * 4 + (g >> 1)) * VEC_STRIDE + warp * 160 + t4 * 4 + j * 16);
#pragma unroll
    for (int i = 0; i < 5; i++) {
        cs[10 + i] = lds32(sb + OFF_VA + (g >> 1) * VEC_STRIDE + warp * 160 + (g & 1) * 16 + t4 * 4 + i * 32);
        const uint2 t = lds64(sb + OFF_TAB2 + warp * 40 + i * 8);
        dst2[2 * i] = slot_ptr(t.x + g * 16 + t4 * 8);
        dst2[2 * i + 1] = slot_ptr(t.y + g * 16 + t4 * 8);
        const int cc = 2 * (warp * 5 + i) + (mi & 1);
        w2a[i] = pin(sb + X_W2 + (cc >> 3) * 4096 + (r8 + 8 * (mi >> 1)) * 128 + (((cc & 7) ^ r8) << 4));
    }
    const uint32_t piv = lds32(sb + OFF_STAT + (g >> 1) * 8);
    const uint32_t* const xin = pin(slot(SL_X1 + warp / 3, side) + ((warp % 3) * 10 + (g & 1)) * 32 + (g >> 1) * 4 + t4);
    const uint32_t w1a = pin(sb + X_W1 + (warp * 80 + r8 + 8 * (mi >> 1)) * 64 + (((mi & 1) ^ ((r8 >> 1) & 3)) << 4));
    const uint32_t w1bar = pin(bar_w1 + (warp >> 1) * 8), w2bar = pin(bar_w2 + (warp + (warp >> 2)) * 8);
    const uint32_t wbar = pin(NB_O + warp);
    const uint32_t ab_st = pin(sb + SC_AB + warp * 1024 + lane * 16), y_st = pin(sb + SC_Y + warp * 512 + lane * 8), s_st = pin(sb + SC_ST + (t4 * 8 + warp) * 8);
    const uint32_t h_ld = pin(sb + SC_H1 + ((g & 3) ^ (2 * (f & 1) + ((f >> 1) & 1))) * 64 + t4 * 16);
    {
        const int kap = 2 * (head & 1) + ((head >> 1) & 1);
        const uint32_t wa = pin(sb + X_WO + (mt >> 1) * (DH * 64) + (r8 + 8 * (mi >> 1)) * 64 + ((((mt & 1) * 2 + (mi & 1)) ^ ((r8 >> 1) & 3)) << 4));
        const uint32_t oa = pin(sb + OFF_O + ((g & 3) ^ kap) * O_STRIDE + t4 * 8);
        uint32_t* dst[4];
#pragma unroll
        for (int i = 0; i < 2; i++) {
            const uint2 t = lds64(sb + OFF_TAB1 + (bown * 20 + 2 * mt + (warp < 2 ? 4 * i : 0)) * 4);
            dst[2 * i] = slot_ptr(t.x + g * 16 + t4 * 8);
            dst[2 * i + 1] = slot_ptr(t.y + g * 16 + t4 * 8);
        }
        PROF(6);
        uint32_t wf[8][4], wg[8][4];
        mbar_wait(bar_wo + (mt >> 1) * 8, 0);
#pragma unroll
        for (int ks = 0; ks < 8; ks++) ldsm4t(wf[ks], wa + ks * 1024);
        if (warp < 2) {
            mbar_wait(bar_wo + 8, 0);
#pragma unroll
            for (int ks = 0; ks < 8; ks++) ldsm4t(wg[ks], wa + DH * 64 + ks * 1024);
        }
        asm volatile("bar.sync %0, 64;" ::"r"(wbar) : "memory");
        PROF(8);
        uint2 ob[8];
#pragma unroll
        for (int ks = 0; ks < 8; ks++) ob[ks] = lds64(oa + ks * 32);
        float c0[4] = {0.f, 0.f, 0.f, 0.f}, c1[4] = {0.f, 0.f, 0.f, 0.f};
        if (warp < 2) {
            float c2[4] = {0.f, 0.f, 0.f, 0.f}, c3[4] = {0.f, 0.f, 0.f, 0.f};
#pragma unroll
            for (int ks = 0; ks < 8; ks += 2) {
                mma16816(c0, wf[ks], ob[ks].x, ob[ks].y);
                mma16816(c2, wg[ks], ob[ks].x, ob[ks].y);
                mma16816(c1, wf[ks + 1], ob[ks + 1].x, ob[ks + 1].y);
                mma16816(c3, wg[ks + 1], ob[ks + 1].x, ob[ks + 1].y);
            }
            stg_relaxed2_if(t4 < 2, dst[2], flag(c2[0] + c3[0]), flag(c2[1] + c3[1]));
            stg_relaxed2_if(t4 < 2, dst[3], flag(c2[2] + c3[2]), flag(c2[3] + c3[3]));
        } else {
#pragma unroll
            for (int ks = 0; ks < 8; ks += 2) {
                mma16816(c0, wf[ks], ob[ks].x, ob[ks].y);
                mma16816(c1, wf[ks + 1], ob[ks + 1].x, ob[ks + 1].y);
            }
        }
        stg_relaxed2_if(t4 < 2, dst[0], flag(c0[0] + c1[0]), flag(c0[1] + c1[1]));
        stg_relaxed2_if(t4 < 2, dst[1], flag(c0[2] + c1[2]), flag(c0[3] + c1[3]));
    }
    PROF(9);
    uint32_t x1w = 0;
    if (is_owner) {
        uint4 v;
        for (int it = 0;; it++) {
            v = ldg_relaxed(in1);
            if (__all_sync(0xffffffffu, and3(and3(v.x, v.y, v.z), v.w, 1u))) break;
            if (it > SPIN_LIMIT) __trap();
        }
        PROF(11);
        const float s0 = __uint_as_float(v.x) + __shfl_xor_sync(0xffffffffu, __uint_as_float(v.z), 8);
        const float s1 = __uint_as_float(v.y) + __shfl_xor_sync(0xffffffffu, __uint_as_float(v.w), 8);
        sts_f32(red_st, s0 + __shfl_xor_sync(0xffffffffu, s1, 16));
        if (warp == 0) {
            nbar_sync<NB_E4, 256>();
            float2 a[8];
#pragma unroll
            for (int w = 0; w < 8; w++) a[w] = lds_f32x2(red_ld + w * 128);
            const uint32_t aw = pack_bf(((a[0].x + a[1].x) + (a[2].x + a[3].x)) + ((a[4].x + a[5].x) + (a[6].x + a[7].x)),
                                        ((a[0].y + a[1].y) + (a[2].y + a[3].y)) + ((a[4].y + a[5].y) + (a[6].y + a[7].y)));
            x1w = bf2_add(xw, bf2_mul(ga_w, aw));
            stg_relaxed(x1_dst, x1w ^ 0x80008000u);
        } else if (warp == 1) {
            nbar_sync<NB_E4, 256>();
            if (lane < 24) stg_zero4(mod_slot(lane >> 2, own, lane & 3));
            if (own < 32 && lane == 24) stg_zero4(g_clr + own * 4);
            if (own < 16 && lane == 25) stg_relaxed(g_phase + own * 32, 0u);
        } else {
            nbar_arrive<NB_E4, 256>();
        }
    }
    PROF(12);
    if (is_f) {
        uint32_t f1[5][2][4], f2[5][2][4];
        uint32_t d[6];
        auto load_x1 = [&] {
#pragma unroll
            for (int i = 0; i < 5; i++) d[i] = ldg_relaxed32(xin + i * 64);
        };
        auto have_x1 = [&] { return __all_sync(0xffffffffu, __vimin3_u32(__vimin3_u32(d[0], d[1], d[2]), d[3], d[4]) != 0u); };
        mbar_wait(w1bar, 0);
        load_x1();
        {
#pragma unroll
            for (int i = 0; i < 5; i++) { ldsm4t(f1[i][0], w1a + i * 1024); ldsm4t(f1[i][1], (w1a ^ 32) + i * 1024); }
            float c[2][4];
#pragma unroll
            for (int m = 0; m < 2; m++) c[m][0] = c[m][1] = c[m][2] = c[m][3] = 0.f;
#pragma unroll
            for (int i = 0; i < 5; i++) { mma16816(c[0], f1[i][0], cs[2 * i], cs[2 * i + 1]); mma16816(c[1], f1[i][1], cs[2 * i], cs[2 * i + 1]); }
#pragma unroll
            for (int i = 0; i < 5; i++) { cs[2 * i] = pin(odd ? 0u : cs[10 + i]); cs[2 * i + 1] = pin(odd ? cs[10 + i] : 0u); }
#pragma unroll
            for (int m = 0; m < 2; m++) sts128(ab_st + m * 512, make_uint4(__float_as_uint(c[m][0]), __float_as_uint(c[m][1]), __float_as_uint(c[m][2]), __float_as_uint(c[m][3])));
            nbar_arrive<NB_AB, 320>();
            d[0] |= __float_as_uint(c[1][3]) & (side >> 1);
        }
        PROF(10);
#pragma unroll 1
        for (int it = 0; !have_x1(); it++) {
            load_x1();
            if (it > SPIN_LIMIT) __trap();
        }
        PROF(13);
        {
            float y[2][4], st[4] = {0.f, 0.f, 0.f, 0.f};
#pragma unroll
            for (int m = 0; m < 2; m++) y[m][0] = y[m][1] = y[m][2] = y[m][3] = 0.f;
#pragma unroll
            for (int i = 0; i < 5; i++) d[i] = bf2_add(d[i], piv);
            d[5] = 0u;
#pragma unroll
            for (int i = 0; i < 5; i++) {
                if (i < 3) {
                    const uint32_t a[4] = {d[2 * i], 0x3f803f80u, d[2 * i + 1], 0x3f803f80u};
                    mma16816(st, a, d[2 * i], d[2 * i + 1]);
                }
                const uint32_t y0 = bf2_mul(d[i], cs[2 * i]), y1 = bf2_mul(d[i], cs[2 * i + 1]);
                mma16816(y[0], f1[i][0], y0, y1);
                mma16816(y[1], f1[i][1], y0, y1);
            }
            const float q = odd ? st[1] : st[0];
            const float q2 = q + __shfl_xor_sync(0xffffffffu, q, 4);
            if (diag && !odd) sts_f32x2(s_st, q2, st[2] + st[3]);
#pragma unroll
            for (int m = 0; m < 2; m++) sts_f32x2(y_st + m * 256, y[m][0] + y[m][1], y[m][2] + y[m][3]);
        }
        nbar_arrive<NB_Y, 320>();
        PROF(14);
        mbar_wait(w2bar, 0);
        mbar_wait(w2bar + 8, 0);
#pragma unroll
        for (int i = 0; i < 5; i++) { ldsm4t(f2[i][0], w2a[i]); ldsm4t(f2[i][1], w2a[i] + 2048); }
        asm volatile("bar.sync %0, 96;" ::"r"(wbar) : "memory");
        PROF(15);
        {
            const uint4 hb = lds128(h_ld);
            float c[5][4];
#pragma unroll
            for (int i = 0; i < 7; i++) {
                if (i < 5) { c[i][0] = c[i][1] = c[i][2] = c[i][3] = 0.f; mma16816(c[i], f2[i][0], hb.x, hb.y); }
                if (i > 0 && i < 6) mma16816(c[i - 1], f2[i - 1][1], hb.z, hb.w);
                if (i > 1) {
                    stg_relaxed2_if(t4 < 2, dst2[2 * i - 4], flag(c[i - 2][0]), flag(c[i - 2][1]));
                    stg_relaxed2_if(t4 < 2, dst2[2 * i - 3], flag(c[i - 2][2]), flag(c[i - 2][3]));
                }
            }
        }
    }
    PROF(16);
    if (is_owner) {
        uint32_t* const dst = pin((uint32_t*)(p.out + ((lane >> 2) & 3) * D + 8 * own) + t4);
        const uint32_t b2w = lds32(sb + OWN_B2 + (lane & 15) * 4), gb_w = lds32(sb + OWN_GB + (lane & 15) * 4);
        const bool two = tid < NF * 8 - 256;
        uint4 v, w = make_uint4(1, 1, 1, 1);
        for (int it = 0;; it++) {
            ldg_relaxed_if(two, w, in2b);
            v = ldg_relaxed(in2a);
            if (__all_sync(0xffffffffu, and3(and3(v.x, v.y, v.z), and3(v.w, w.x, w.y), and3(w.z, w.w, 1u)))) break;
            if (it > SPIN_LIMIT) __trap();
        }
        PROF(17);
        const float s0 = (__uint_as_float(v.x) + __uint_as_float(w.x)) + __shfl_xor_sync(0xffffffffu, __uint_as_float(v.z) + __uint_as_float(w.z), 8);
        const float s1 = (__uint_as_float(v.y) + __uint_as_float(w.y)) + __shfl_xor_sync(0xffffffffu, __uint_as_float(v.w) + __uint_as_float(w.w), 8);
        sts_f32(red_st + (SC_E6 - SC_E4), s0 + __shfl_xor_sync(0xffffffffu, s1, 16));
        if (warp != 0) nbar_arrive<NB_E6, 256>();
        else nbar_sync<NB_E6, 256>();
        if (warp == 0) {
            float2 a[8];
#pragma unroll
            for (int i = 0; i < 8; i++) a[i] = lds_f32x2(red_ld + (SC_E6 - SC_E4) + i * 128);
            const uint32_t aw = pack_bf(((a[0].x + a[1].x) + (a[2].x + a[3].x)) + ((a[4].x + a[5].x) + (a[6].x + a[7].x)),
                                        ((a[0].y + a[1].y) + (a[2].y + a[3].y)) + ((a[4].y + a[5].y) + (a[6].y + a[7].y)));
            const uint32_t r = bf2_add(x1w, bf2_mul(gb_w, bf2_add(aw, b2w)));
            if (lane < 16) asm volatile("st.global.u32 [%0], %1;" ::"l"(dst), "r"(r) : "memory");
        }
    }
    PROF(18);
    PROF_DUMP;
}

typedef CUresult (*EncodeFn)(CUtensorMap*, CUtensorMapDataType, cuuint32_t, void*, const cuuint64_t*, const cuuint64_t*, const cuuint32_t*,
                             const cuuint32_t*, CUtensorMapInterleave, CUtensorMapSwizzle, CUtensorMapL2promotion, CUtensorMapFloatOOBfill);

static CUtensorMap make_map(EncodeFn enc, const void* ptr, int cols, int rows, int box_cols, int box_rows, CUtensorMapSwizzle sw) {
    CUtensorMap m;
    cuuint64_t dims[2] = {(cuuint64_t)cols, (cuuint64_t)rows};
    cuuint64_t strides[1] = {(cuuint64_t)cols * 2};
    cuuint32_t box[2] = {(cuuint32_t)box_cols, (cuuint32_t)box_rows};
    cuuint32_t es[2] = {1, 1};
    enc(&m, CU_TENSOR_MAP_DATA_TYPE_BFLOAT16, 2, const_cast<void*>(ptr), dims, strides, box, es, CU_TENSOR_MAP_INTERLEAVE_NONE, sw,
        CU_TENSOR_MAP_L2_PROMOTION_NONE, CU_TENSOR_MAP_FLOAT_OOB_FILL_NONE);
    return m;
}

}

extern "C" void kernel_launch(void* const* d_in, const int* in_sizes, int n_in, void* d_out, int out_size) {
    (void)in_sizes; (void)n_in; (void)out_size;
    static EncodeFn enc = nullptr;
    if (!enc) {
        void* fn = nullptr;
        cudaDriverEntryPointQueryResult qr;
        cudaGetDriverEntryPoint("cuTensorMapEncodeTiled", &fn, cudaEnableDefault, &qr);
        enc = (EncodeFn)fn;
        cudaFuncSetAttribute(fused_kernel, cudaFuncAttributeMaxDynamicSharedMemorySize, SMEM_BYTES);
    }
    Params p;
    p.x = (const __nv_bfloat16*)d_in[0];
    p.kc = (const __nv_bfloat16*)d_in[1];
    p.vc = (const __nv_bfloat16*)d_in[2];
    p.b1 = (const __nv_bfloat16*)d_in[7];
    p.b2 = (const __nv_bfloat16*)d_in[9];
    p.c = (const __nv_bfloat16*)d_in[10];
    p.out = (__nv_bfloat16*)d_out;
    CUtensorMap tm_wmod = make_map(enc, d_in[11], NMOD, D, 32, 160, CU_TENSOR_MAP_SWIZZLE_64B);
    CUtensorMap tm_wq = make_map(enc, d_in[3], NH * DH, D, 32, 160, CU_TENSOR_MAP_SWIZZLE_64B);
    CUtensorMap tm_wo = make_map(enc, d_in[4], D, NH * DH, 32, 128, CU_TENSOR_MAP_SWIZZLE_64B);
    CUtensorMap tm_w1 = make_map(enc, d_in[6], FF, D, 32, 160, CU_TENSOR_MAP_SWIZZLE_64B);
    CUtensorMap tm_w2 = make_map(enc, d_in[8], D, FF, 64, 32, CU_TENSOR_MAP_SWIZZLE_128B);
    CUtensorMap tm_v = make_map(enc, d_in[2], DH, NB * NH * SK, 64, TILE_KEYS, CU_TENSOR_MAP_SWIZZLE_128B);
    fused_kernel<<<NCTA, NTHREADS, SMEM_BYTES>>>(p, tm_wmod, tm_wq, tm_wo, tm_w1, tm_w2, tm_v);
}
```

```cpp
#include <cuda_runtime.h>
#include <cuda.h>
#include <cuda_bf16.h>
#include <stdint.h>

namespace {

constexpr int NB = 4, D = 640, NH = 32, DH = 128, SK = 8192, WIN = 2048, FF = 1728, NMOD = 6 * D;
constexpr int NCTA = 128;
constexpr int NOWN = 80;
constexpr int NF = 54;
constexpr int NTHREADS = 320;
constexpr int TILE_KEYS = 64;
constexpr int TILE_BYTES = TILE_KEYS * DH * 2;
constexpr int NITEM = 2 * WIN / TILE_KEYS;
constexpr int NS = 8;
constexpr int NMODC = 120;
constexpr int SPIN_LIMIT = 1 << 18;
#define INFLIGHT 3
#define WQ_DELAY 400
#define PACE_A 7800
#define PACE_TAU 635
#define PF_END 14
#define PH_FIRST 20
#define PH_LAG 5
#define LAT_T 2100
#define WO_T -1100
#define WO_S 200
#define W1_T 1000
#define W2_T 1700
#define GB_T 2550
#define CLR_CHECK 28000
constexpr int NPROBE = 8, PROBE_END = 10000;
constexpr int SEG_J = 8;

constexpr int OFF_RING = 0;
constexpr int OFF_X = OFF_RING + NS * TILE_BYTES;
constexpr int X_WM = OFF_X;
constexpr int X_WQ = OFF_X + D * 64;
constexpr int X_WO = OFF_X;
constexpr int X_W1 = X_WO + 5 * DH * 64;
constexpr int X_END = X_W1 + D * 64;
constexpr int X_W2 = OFF_RING;
constexpr int X_GB = OFF_RING + 3 * TILE_BYTES;
static_assert(X_WQ + D * 64 <= X_END, "prologue weights must fit");
constexpr int VEC_STRIDE = 1296;
constexpr int OFF_VA = X_END;
constexpr int OFF_VB = OFF_VA + 4 * VEC_STRIDE;
constexpr int OFF_RED = OFF_VB + 4 * VEC_STRIDE;
constexpr int OFF_ML = OFF_RED + 4 * VEC_STRIDE;
constexpr int O_STRIDE = 288;
constexpr int OFF_O = OFF_ML + 64;
constexpr int OFF_Q = OFF_O + 4 * O_STRIDE;
constexpr int OFF_OWN = OFF_Q + 256;
constexpr int OWN_X = OFF_OWN, OWN_B2 = OWN_X + 64, OWN_GA = OWN_B2 + 64, OWN_GB = OWN_GA + 64, OWN_B1 = OWN_GB + 64;
constexpr int OFF_STAT = OWN_B1 + 128;
constexpr int OFF_TAB1 = OFF_STAT + 32;
constexpr int OFF_TAB2 = OFF_TAB1 + NOWN * 4;
constexpr int OFF_SIDE = OFF_TAB2 + NOWN * 4;
constexpr int OFF_BAR = OFF_SIDE + 8;
constexpr int NBAR = 2 * NS + 31;
constexpr int SMEM_BYTES = OFF_BAR + NBAR * 8;
constexpr int SC_OP = OFF_RING + 4 * TILE_BYTES;
constexpr int SC_AB = SC_OP + 4096;
constexpr int SC_Y = SC_AB + 8192;
constexpr int SC_ST = SC_Y + 4096;
constexpr int SC_E4 = SC_ST + 256;
constexpr int SC_E6 = SC_E4 + 1024;
constexpr int SC_P = SC_E6 + 1024;
constexpr int SC_H1 = SC_P + 256;
static_assert(SMEM_BYTES <= 232448, "smem");
static_assert(OFF_BAR % 8 == 0 && OFF_X % 1024 == 0 && X_WQ % 512 == 0 && X_W1 % 512 == 0 && OFF_VA % 16 == 0 && OFF_RED % 16 == 0 && OFF_ML % 16 == 0 && OFF_O % 16 == 0 && OFF_Q % 16 == 0, "align");
constexpr int NB_O = 2  , NB_E4 = 10, NB_E6 = 11, NB_AB = 12, NB_Y = 13;

__device__ uint32_t g_mod[NMODC * 64];
__device__ uint32_t g_q[NCTA * 64];
__device__ uint32_t g_clr[NCTA];
__device__ uint32_t g_phase[16 * 32];
constexpr int SL_P1 = 0;
constexpr int SL_P2 = SL_P1 + NOWN;
constexpr int SL_O = SL_P2 + 2 * NOWN;
constexpr int SL_X1 = SL_O + 8;
constexpr int SL_SIDE = SL_X1 + 3;
static_assert(SL_SIDE < 256, "one 2 MB page");
__device__ uint32_t g_slots[2 * 256 * 2048];
__device__ __forceinline__ uint32_t* slot(int i, int side) {
    const size_t base = ((size_t)g_slots + 0x1fffff) & ~(size_t)0x1fffff;
    return (uint32_t*)base + i * 2048 + (((__popc(i & 0x59) ^ side) & 1) << 10);
}
#define PROF_DECL
#define HPROF(i) do { } while (0)
#define PROF(i) do { } while (0)
#define PROF_DUMP do { } while (0)

__device__ __forceinline__ uint32_t smem_u32(const void* p) { return (uint32_t)__cvta_generic_to_shared(p); }
__device__ __forceinline__ void mbar_init(uint32_t bar, uint32_t cnt) { asm volatile("mbarrier.init.shared::cta.b64 [%0], %1;" ::"r"(bar), "r"(cnt) : "memory"); }
__device__ __forceinline__ void mbar_expect_tx(uint32_t bar, uint32_t bytes) { asm volatile("mbarrier.arrive.expect_tx.shared::cta.b64 _, [%0], %1;" ::"r"(bar), "r"(bytes) : "memory"); }
__device__ __forceinline__ void mbar_arrive(uint32_t bar) { asm volatile("mbarrier.arrive.shared::cta.b64 _, [%0];" ::"r"(bar) : "memory"); }
__device__ __forceinline__ void mbar_wait(uint32_t bar, uint32_t parity) {
    uint32_t ok;
    int it = 0;
    while (true) {
        asm volatile("{\n.reg .pred p;\nmbarrier.try_wait.parity.shared::cta.b64 p, [%1], %2;\nselp.u32 %0, 1, 0, p;\n}" : "=r"(ok) : "r"(bar), "r"(parity) : "memory");
        if (ok) break;
        if (++it > SPIN_LIMIT) __trap();
    }
}
__device__ __forceinline__ void bulk_load(uint32_t dst, const void* src, uint32_t bytes, uint32_t bar, uint64_t pol) {
    asm volatile("cp.async.bulk.shared::cluster.global.mbarrier::complete_tx::bytes.L2::cache_hint [%0], [%1], %2, [%3], %4;"
                 ::"r"(dst), "l"(src), "r"(bytes), "r"(bar), "l"(pol) : "memory");
}
__device__ __forceinline__ void bar_cons() { asm volatile("bar.sync 1, 256;" ::: "memory"); }
template <int ID, int N> __device__ __forceinline__ void nbar_sync() { asm volatile("bar.sync %0, %1;" ::"n"(ID), "n"(N) : "memory"); }
template <int ID, int N> __device__ __forceinline__ void nbar_arrive() { asm volatile("bar.arrive %0, %1;" ::"n"(ID), "n"(N) : "memory"); }
__device__ __forceinline__ bool mbar_test(uint32_t bar, uint32_t parity) {
    uint32_t ok;
    asm volatile("{\n.reg .pred p;\nmbarrier.test_wait.parity.shared::cta.b64 p, [%1], %2;\nselp.u32 %0, 1, 0, p;\n}" : "=r"(ok) : "r"(bar), "r"(parity) : "memory");
    return ok;
}
__device__ __forceinline__ uint32_t pin(uint32_t v) { asm volatile("" : "+r"(v)); return v; }
template <class T> __device__ __forceinline__ T pin_hard(T v) { return __shfl_sync(0xffffffffu, v, threadIdx.x & 31); }
template <class T> __device__ __forceinline__ T* pin(T* v) { asm volatile("" : "+l"(v)); return v; }
__device__ __forceinline__ void ldsm4(uint32_t (&a)[4], uint32_t addr) {
    asm volatile("ldmatrix.sync.aligned.m8n8.x4.shared.b16 {%0,%1,%2,%3}, [%4];" : "=r"(a[0]), "=r"(a[1]), "=r"(a[2]), "=r"(a[3]) : "r"(addr) : "memory");
}
__device__ __forceinline__ void ldsm4t(uint32_t (&a)[4], uint32_t addr) {
    asm volatile("ldmatrix.sync.aligned.m8n8.x4.trans.shared.b16 {%0,%1,%2,%3}, [%4];" : "=r"(a[0]), "=r"(a[1]), "=r"(a[2]), "=r"(a[3]) : "r"(addr) : "memory");
}
__device__ __forceinline__ void mma16816(float (&c)[4], const uint32_t (&a)[4], uint32_t b0, uint32_t b1) {
    asm volatile("mma.sync.aligned.m16n8k16.row.col.f32.bf16.bf16.f32 {%0,%1,%2,%3}, {%4,%5,%6,%7}, {%8,%9}, {%0,%1,%2,%3};"
                 : "+f"(c[0]), "+f"(c[1]), "+f"(c[2]), "+f"(c[3]) : "r"(a[0]), "r"(a[1]), "r"(a[2]), "r"(a[3]), "r"(b0), "r"(b1));
}
__device__ __forceinline__ uint32_t lds32(uint32_t addr) { uint32_t v; asm volatile("ld.shared.u32 %0, [%1];" : "=r"(v) : "r"(addr) : "memory"); return v; }
__device__ __forceinline__ float lds_f32(uint32_t addr) { float v; asm volatile("ld.shared.f32 %0, [%1];" : "=f"(v) : "r"(addr) : "memory"); return v; }
__device__ __forceinline__ float2 lds_f32x2(uint32_t addr) { float2 v; asm volatile("ld.shared.v2.f32 {%0,%1}, [%2];" : "=f"(v.x), "=f"(v.y) : "r"(addr) : "memory"); return v; }
__device__ __forceinline__ float4 lds_f32x4(uint32_t addr) { float4 v; asm volatile("ld.shared.v4.f32 {%0,%1,%2,%3}, [%4];" : "=f"(v.x), "=f"(v.y), "=f"(v.z), "=f"(v.w) : "r"(addr) : "memory"); return v; }
__device__ __forceinline__ uint2 lds64(uint32_t addr) { uint2 v; asm volatile("ld.shared.v2.u32 {%0,%1}, [%2];" : "=r"(v.x), "=r"(v.y) : "r"(addr) : "memory"); return v; }
__device__ __forceinline__ uint4 lds128(uint32_t addr) { uint4 v; asm volatile("ld.shared.v4.u32 {%0,%1,%2,%3}, [%4];" : "=r"(v.x), "=r"(v.y), "=r"(v.z), "=r"(v.w) : "r"(addr) : "memory"); return v; }
__device__ __forceinline__ void sts16(uint32_t addr, uint32_t v) { asm volatile("st.shared.b16 [%0], %1;" ::"r"(addr), "h"((unsigned short)v) : "memory"); }
__device__ __forceinline__ void sts32(uint32_t addr, uint32_t v) { asm volatile("st.shared.u32 [%0], %1;" ::"r"(addr), "r"(v) : "memory"); }
__device__ __forceinline__ void sts_f32(uint32_t addr, float v) { asm volatile("st.shared.f32 [%0], %1;" ::"r"(addr), "f"(v) : "memory"); }
__device__ __forceinline__ void sts_f32x2(uint32_t addr, float a, float b) { asm volatile("st.shared.v2.f32 [%0], {%1,%2};" ::"r"(addr), "f"(a), "f"(b) : "memory"); }
__device__ __forceinline__ void sts128(uint32_t addr, uint4 v) { asm volatile("st.shared.v4.u32 [%0], {%1,%2,%3,%4};" ::"r"(addr), "r"(v.x), "r"(v.y), "r"(v.z), "r"(v.w) : "memory"); }
__device__ __forceinline__ uint4 ldg_relaxed(const uint32_t* p) {
    uint4 v;
    asm volatile("ld.relaxed.gpu.global.v4.u32 {%0,%1,%2,%3}, [%4];" : "=r"(v.x), "=r"(v.y), "=r"(v.z), "=r"(v.w) : "l"(p) : "memory");
    return v;
}
__device__ __forceinline__ void ldg_relaxed_if(bool on, uint4& v, const uint32_t* p) {
    asm volatile("{\n.reg .pred q;\nsetp.ne.u32 q, %5, 0;\n@q ld.relaxed.gpu.global.v4.u32 {%0,%1,%2,%3}, [%4];\n}"
                 : "+r"(v.x), "+r"(v.y), "+r"(v.z), "+r"(v.w) : "l"(p), "r"((uint32_t)on) : "memory");
}
__device__ __forceinline__ void stg_relaxed2_if(bool on, uint32_t* p, uint32_t a, uint32_t b) {
    asm volatile("{\n.reg .pred q;\nsetp.ne.u32 q, %3, 0;\n@q st.relaxed.gpu.global.v2.u32 [%0], {%1,%2};\n}" ::"l"(p), "r"(a), "r"(b), "r"((uint32_t)on) : "memory");
}
__device__ __forceinline__ uint32_t ldg_relaxed32(const uint32_t* p) { uint32_t v; asm volatile("ld.relaxed.gpu.global.u32 %0, [%1];" : "=r"(v) : "l"(p) : "memory"); return v; }
__device__ __forceinline__ void stg_relaxed(uint32_t* p, uint32_t v) { asm volatile("st.relaxed.gpu.global.u32 [%0], %1;" ::"l"(p), "r"(v) : "memory"); }
__device__ __forceinline__ void stg_zero4(uint32_t* p) { asm volatile("st.relaxed.gpu.global.v4.u32 [%0], {%1,%1,%1,%1};" ::"l"(p), "r"(0u) : "memory"); }
__device__ __forceinline__ bool ready(const uint4& v) { return (v.x != 0u) & (v.y != 0u) & (v.z != 0u) & (v.w != 0u); }
__device__ __forceinline__ uint4 inv4(const uint4& v) { return make_uint4(~v.x, ~v.y, ~v.z, ~v.w); }
__device__ __forceinline__ uint32_t pack_bf(float lo, float hi) {
    uint32_t r;
    asm("cvt.rn.bf16x2.f32 %0, %1, %2;" : "=r"(r) : "f"(hi), "f"(lo));
    return r;
}
__device__ __forceinline__ float bfr(float x) { return __uint_as_float(pack_bf(0.f, x) & 0xffff0000u); }
__device__ __forceinline__ float bf_lo(uint32_t w) { return __uint_as_float(w << 16); }
__device__ __forceinline__ float bf_hi(uint32_t w) { return __uint_as_float(w & 0xffff0000u); }
__device__ __forceinline__ float bf2f(__nv_bfloat16 v) { return __bfloat162float(v); }
__device__ __forceinline__ float ex2(float x) { float y; asm("ex2.approx.ftz.f32 %0, %1;" : "=f"(y) : "f"(x)); return y; }
__device__ __forceinline__ float rcp_fast(float x) { float y; asm("rcp.approx.ftz.f32 %0, %1;" : "=f"(y) : "f"(x)); return y; }
__device__ __forceinline__ float rsqrt_fast(float x) { float y; asm("rsqrt.approx.ftz.f32 %0, %1;" : "=f"(y) : "f"(x)); return y; }
__device__ __forceinline__ float sqrt_fast(float x) { float y; asm("sqrt.approx.f32 %0, %1;" : "=f"(y) : "f"(x)); return y; }
__device__ __forceinline__ uint32_t bf2_add(uint32_t a, uint32_t b) { uint32_t r; asm("add.rn.bf16x2 %0, %1, %2;" : "=r"(r) : "r"(a), "r"(b)); return r; }
__device__ __forceinline__ uint32_t bf2_sub(uint32_t a, uint32_t b) { uint32_t r; asm("sub.rn.bf16x2 %0, %1, %2;" : "=r"(r) : "r"(a), "r"(b)); return r; }
__device__ __forceinline__ uint32_t bf2_mul(uint32_t a, uint32_t b) { uint32_t r; asm("mul.rn.bf16x2 %0, %1, %2;" : "=r"(r) : "r"(a), "r"(b)); return r; }
__device__ __forceinline__ uint32_t gtime32() { uint32_t c; asm volatile("mov.u32 %0, %%globaltimer_lo;" : "=r"(c)); return c; }
__device__ __forceinline__ uint32_t clock32() { uint32_t c; asm volatile("mov.u32 %0, %%clock;" : "=r"(c)); return c; }

__device__ __forceinline__ float warp_sum(float v) {
#pragma unroll
    for (int o = 16; o > 0; o >>= 1) v += __shfl_xor_sync(0xffffffffu, v, o);
    return v;
}

struct Params {
    const __nv_bfloat16 *x, *kc, *vc, *b1, *b2, *c;
    __nv_bfloat16* out;
};

__device__ __forceinline__ void tma2d(uint32_t dst, const CUtensorMap* tm, int x, int y, uint32_t bar) {
    asm volatile("cp.async.bulk.tensor.2d.shared::cluster.global.mbarrier::complete_tx::bytes [%0], [%1, {%2, %3}], [%4];"
                 ::"r"(dst), "l"(tm), "r"(x), "r"(y), "r"(bar) : "memory");
}

__device__ __forceinline__ void tma2d_hint(uint32_t dst, const CUtensorMap* tm, int x, int y, uint32_t bar, uint64_t pol) {
    asm volatile("cp.async.bulk.tensor.2d.shared::cluster.global.mbarrier::complete_tx::bytes.L2::cache_hint [%0], [%1, {%2, %3}], [%4], %5;"
                 ::"r"(dst), "l"(tm), "r"(x), "r"(y), "r"(bar), "l"(pol) : "memory");
}
__device__ __forceinline__ uint32_t flag(float v) { return __float_as_uint(v) | 1u; }
__device__ __forceinline__ uint32_t and3(uint32_t a, uint32_t b, uint32_t c) { uint32_t r; asm("lop3.b32 %0, %1, %2, %3, 0x80;" : "=r"(r) : "r"(a), "r"(b), "r"(c)); return r; }
__device__ __forceinline__ uint32_t* slot_ptr(uint32_t lo) {
    uint32_t* r;
    asm volatile("mov.b64 %0, {%1, %2};" : "=l"(r) : "r"(lo), "r"((uint32_t)((size_t)slot(0, 0) >> 32)));
    return r;
}

__device__ __forceinline__ void load_bfrag(uint32_t vec, int stride, int k0, int g, int t, uint32_t& b0, uint32_t& b1) {
    uint32_t a = vec + (g & 3) * stride + (k0 + 2 * t) * 2;
    b0 = lds32(a);
    b1 = lds32(a + 16);
}

__device__ __forceinline__ void ln_finish(float pivot, float sum, float sumsq, uint32_t& m2, float& rden) {
    float dm = sum * (1.f / D);
    float var = fmaxf(sumsq * (1.f / D) - dm * dm, 0.f);
    float mean = pivot + dm;
    m2 = pack_bf(mean, mean);
    rden = rcp_fast(bfr(sqrt_fast(bfr(bfr(var) + 1e-5f))));
}
__device__ __forceinline__ uint32_t ln_mod_pair(uint32_t xw, uint32_t cw, uint32_t sw, uint32_t m2, float rden) {
    uint32_t d = bf2_sub(xw, m2);
    uint32_t ln = pack_bf(bf_lo(d) * rden, bf_hi(d) * rden);
    return bf2_add(bf2_mul(ln, bf2_add(cw, 0x3f803f80u)), sw);
}
__device__ __forceinline__ uint4 ln_mod4(const uint4& x, const uint4& c, const uint4& s, uint32_t m2, float rden) {
    return make_uint4(ln_mod_pair(x.x, c.x, s.x, m2, rden), ln_mod_pair(x.y, c.y, s.y, m2, rden),
                      ln_mod_pair(x.z, c.z, s.z, m2, rden), ln_mod_pair(x.w, c.w, s.w, m2, rden));
}
__device__ __forceinline__ void acc_stats(const uint4& v, float pv, float& s, float& q) {
    const float a0 = bf_lo(v.x) - pv, a1 = bf_hi(v.x) - pv, a2 = bf_lo(v.y) - pv, a3 = bf_hi(v.y) - pv;
    const float a4 = bf_lo(v.z) - pv, a5 = bf_hi(v.z) - pv, a6 = bf_lo(v.w) - pv, a7 = bf_hi(v.w) - pv;
    s += ((a0 + a1) + (a2 + a3)) + ((a4 + a5) + (a6 + a7));
    q += (fmaf(a0, a0, a1 * a1) + fmaf(a2, a2, a3 * a3)) + (fmaf(a4, a4, a5 * a5) + fmaf(a6, a6, a7 * a7));
}
__device__ __forceinline__ uint32_t* mod_slot(int kind, int j, int b) { return g_mod + (kind * 20 + (j >> 2)) * 64 + b * 16 + (j & 3) * 4; }

template <int N>
__device__ __forceinline__ void poll_n(uint4 (&v)[N], const uint32_t* const* ptr, const bool* on) {
    bool pend[N];
#pragma unroll
    for (int i = 0; i < N; i++) pend[i] = on[i];
    int it = 0;
    while (true) {
#pragma unroll
        for (int i = 0; i < N; i++) if (pend[i]) v[i] = ldg_relaxed(ptr[i]);
        bool any = false;
#pragma unroll
        for (int i = 0; i < N; i++) { pend[i] = pend[i] && !ready(v[i]); any |= pend[i]; }
        if (!__any_sync(0xffffffffu, any)) break;
        if (++it > SPIN_LIMIT) __trap();
    }
#pragma unroll
    for (int i = 0; i < N; i++) v[i] = inv4(v[i]);
}
__device__ __forceinline__ uint4 poll1(const uint32_t* p, bool on) {
    uint4 v[1] = {make_uint4(0, 0, 0, 0)};
    const uint32_t* const ptr[1] = {p};
    const bool o[1] = {on};
    poll_n<1>(v, ptr, o);
    return v[0];
}

__device__ __forceinline__ void gelu_stage(uint32_t sb, int m, int lane) {
    const int g = lane >> 2, b = lane & 3;
    const uint32_t y_ld = pin_hard(sb + SC_Y + m * 256 + lane * 8), s_ld = pin_hard(sb + SC_ST + b * 64);
    const uint32_t h_st = pin_hard(sb + SC_H1 + b * 64 + (g >> 1) * 16 + m * 8 + (g & 1) * 2);
    float a0 = 0.f, b0 = lds_f32(sb + OWN_B1 + (16 * m + g) * 4), a1 = 0.f, b1 = lds_f32(sb + OWN_B1 + (16 * m + g + 8) * 4);
    nbar_sync<NB_AB, 320>();
#pragma unroll
    for (int w = 0; w < 8; w++) {
        const float4 t = lds_f32x4(sb + SC_AB + w * 1024 + m * 512 + lane * 16);
        a0 += t.x; b0 += t.y; a1 += t.z; b1 += t.w;
    }
    sts128(sb + SC_AB + m * 512 + lane * 16, make_uint4(__float_as_uint(a0), __float_as_uint(b0), __float_as_uint(a1), __float_as_uint(b1)));
    nbar_sync<NB_Y, 320>();
    float4 q[4];
    float2 y[8];
#pragma unroll
    for (int i = 0; i < 4; i++) q[i] = lds_f32x4(s_ld + i * 16);
#pragma unroll
    for (int w = 0; w < 8; w++) y[w] = lds_f32x2(y_ld + w * 512);
    const float dm = (((q[0].y + q[0].w) + (q[1].y + q[1].w)) + ((q[2].y + q[2].w) + (q[3].y + q[3].w))) * (1.f / D);
    const float sq = ((q[0].x + q[0].z) + (q[1].x + q[1].z)) + ((q[2].x + q[2].z) + (q[3].x + q[3].z));
    const float r = rsqrt_fast(fmaxf(fmaf(-dm, dm, fmaf(sq, 1.f / D, 1e-5f)), 1e-5f));
    const float y0 = ((y[0].x + y[1].x) + (y[2].x + y[3].x)) + ((y[4].x + y[5].x) + (y[6].x + y[7].x));
    const float y1 = ((y[0].y + y[1].y) + (y[2].y + y[3].y)) + ((y[4].y + y[5].y) + (y[6].y + y[7].y));
    const float u0 = fmaf(r, fmaf(dm, a0, -y0), b0), u1 = fmaf(r, fmaf(dm, a1, -y1), b1);
    const float e0 = ex2(u0 * fmaf(u0 * u0, -0.044715f * 2.302208198144325f, -2.302208198144325f));
    const float e1 = ex2(u1 * fmaf(u1 * u1, -0.044715f * 2.302208198144325f, -2.302208198144325f));
    sts16(h_st, pack_bf(u0 * rcp_fast(1.f + e0), 0.f));
    sts16(h_st + 4, pack_bf(u1 * rcp_fast(1.f + e1), 0.f));
#pragma unroll
    for (int w = 0; w < 8; w++) asm volatile("bar.arrive %0, 96;" ::"r"(NB_O + w) : "memory");
}

struct Roles { bool is_f, is_owner; int f, own; };
__device__ __forceinline__ Roles roles(int cta) {
    Roles r;
    r.f = (cta * 27) >> 6;
    r.is_f = (((cta + 1) * 27) >> 6) != r.f;
    r.is_owner = !r.is_f || r.f % 9 == 4;
    r.own = r.is_f ? 74 + r.f / 9 : cta - r.f;
    return r;
}

__global__ void __launch_bounds__(NTHREADS, 1)
fused_kernel(const Params p, const __grid_constant__ CUtensorMap tm_wmod, const __grid_constant__ CUtensorMap tm_wq,
             const __grid_constant__ CUtensorMap tm_wo, const __grid_constant__ CUtensorMap tm_w1, const __grid_constant__ CUtensorMap tm_w2,
             const __grid_constant__ CUtensorMap tm_v, const __grid_constant__ CUtensorMap tm_gb) {
    extern __shared__ __align__(1024) unsigned char smem[];
    const uint32_t t_start = gtime32();
    const uint32_t sb = smem_u32(smem);
    const int cta = blockIdx.x;
    const int head = cta >> 2, bown = cta & 3;
    const int rot = (8 * head) & (NITEM / 2 - 1);
    const char* const kb = (const char*)(p.kc + ((size_t)(bown * NH + head) * SK + (SK - WIN)) * DH);
    uint64_t pol = 0;
    if (threadIdx.x == 256) {
        mbar_init(sb + OFF_BAR, 1);
        asm volatile("fence.mbarrier_init.release.cluster;" ::: "memory");
        asm volatile("createpolicy.fractional.L2::evict_first.b64 %0, 1.0;" : "=l"(pol));
        mbar_expect_tx(sb + OFF_BAR, TILE_BYTES);
        bulk_load(sb + OFF_RING, kb + (size_t)rot * TILE_BYTES, TILE_BYTES, sb + OFF_BAR, pol);
        if ((((cta + 1) * 5) >> 4) != ((cta * 5) >> 4)) {
            const uint32_t bar = sb + OFF_BAR + 2 * NS * 8;
            mbar_init(bar, 1);
            asm volatile("fence.mbarrier_init.release.cluster;" ::: "memory");
            mbar_expect_tx(bar, D * 64);
#pragma unroll 1
            for (int r = 0; r < D; r += 160) tma2d(sb + X_WM + r * 64, &tm_wmod, 32 * ((cta * 5) >> 4), r, bar);
        }
    }
    const uint32_t bar_full = sb + OFF_BAR, bar_empty = bar_full + NS * 8;
    const uint32_t bar_wm = bar_empty + NS * 8, bar_wq = bar_wm + 8, bar_xfree = bar_wq + 8, bar_wo = bar_xfree + 8  ;
    const uint32_t bar_w1 = bar_wo + 40  , bar_w2 = bar_w1 + 32  , bar_help = bar_w2 + 80, bar_v = bar_help + 8  ;
    const uint32_t bar_gb = bar_v + 32;
    const int tid = threadIdx.x, warp = tid >> 5, lane = tid & 31;
    const Roles role = roles(cta);
    const bool is_f = role.is_f, is_owner = role.is_owner;
    const int f = role.f, own = role.own;
    const bool crit = (((cta + 1) * 5) >> 4) != ((cta * 5) >> 4);
    const int mr = cta - ((cta * 5) >> 4);
    const int ml = mr * 31 / 44;
    const bool late = !crit && (mr + 1) * 31 / 44 != ml;
    const int mc = crit ? (cta * 5) >> 4 : ml < 60 ? 40 + ml : 58 + ml;
    const bool gb_own = is_owner && own < 72;

    PROF_DECL
    PROF(0);
    uint4 xa = make_uint4(0, 0, 0, 0), xb = xa, ca0 = xa, ca1 = xa, xs[3] = {xa, xa, xa};
    uint32_t own0 = 0;
    __nv_bfloat16 own2 = __float2bfloat16(0.f);
    if (warp < 8) {
        xa = *(const uint4*)(p.x + (tid & 3) * D + (tid >> 2) * 8);
        ca0 = ((const uint4*)p.c)[tid];
        if (tid < 64) { xb = *(const uint4*)(p.x + (tid & 3) * D + (64 + (tid >> 2)) * 8); ca1 = ((const uint4*)p.c)[256 + tid]; }
        if (warp < 4) {
#pragma unroll
            for (int i = 0; i < 3; i++) if (lane + 32 * i < 80) xs[i] = ((const uint4*)p.x)[warp * 80 + lane + 32 * i];
        } else if (warp == 4) {
            if (is_owner) own0 = *(const uint32_t*)((lane < 16 ? p.x + (lane >> 2) * D : p.b2) + 8 * own + 2 * (lane & 3));
            if (is_f) own2 = p.b1[32 * f + lane];
        }
    }
    const char* const vb = (const char*)(p.vc + ((size_t)(bown * NH + head) * SK + (SK - WIN)) * DH);
    const uint32_t bar_first = crit ? bar_wm : bar_wq;
    if (threadIdx.x == 256) {
        if (!crit) {
            mbar_init(bar_wq, 1);
            asm volatile("fence.mbarrier_init.release.cluster;" ::: "memory");
            mbar_expect_tx(bar_wq, D * 64);
            const uint32_t c0 = clock32();
            while (clock32() - c0 < WQ_DELAY) { }
#pragma unroll
            for (int r = 0; r < D; r += 160) tma2d(sb + X_WQ + r * 64, &tm_wq, 32 * cta, r, bar_wq);
        }
    } else if (threadIdx.x == 0) {
#pragma unroll
        for (int s = 0; s < NS; s++) { if (s) mbar_init(bar_full + s * 8, 1); mbar_init(bar_empty + s * 8, 4); }
        mbar_init(crit ? bar_wq : bar_wm, 1);
        mbar_init(bar_xfree, 1);
#pragma unroll
        for (int i = 0; i < 5; i++) { mbar_init(bar_wo + i * 8, 1); mbar_init(bar_w2 + i * 16, 1); mbar_init(bar_w2 + i * 16 + 8, 1); }
        mbar_init(bar_help, 1);
#pragma unroll
        for (int i = 0; i < 4; i++) { mbar_init(bar_v + i * 8, 1); mbar_init(bar_w1 + i * 8, 1); mbar_init(bar_gb + i * 8, 1); }
        asm volatile("fence.mbarrier_init.release.cluster;" ::: "memory");
    }
    __syncthreads();

    if (warp == 8) {
        if (lane == 0) {
            int tp = NS;
            int sched = PACE_A - NS * PACE_TAU;
#pragma unroll 1
            for (int t = 1; t <= NITEM; t++) {
                if (t == 1) mbar_wait(bar_full, 0);
                if (t == 2) {
                    mbar_wait(bar_first, 0);
                    if (crit) {
                        mbar_expect_tx(bar_wq, D * 64);
#pragma unroll 1
                        for (int r = 0; r < D; r += 160) tma2d(sb + X_WQ + r * 64, &tm_wq, 32 * cta, r, bar_wq);
                    }
                }
                if (t == 3) {
                    asm volatile("prefetch.tensormap [%0];" ::"l"(&tm_v) : "memory");
                    asm volatile("prefetch.tensormap [%0];" ::"l"(&tm_wo) : "memory");
                    asm volatile("prefetch.tensormap [%0];" ::"l"(&tm_w1) : "memory");
                    asm volatile("prefetch.tensormap [%0];" ::"l"(&tm_w2) : "memory");
                    asm volatile("prefetch.tensormap [%0];" ::"l"(&tm_gb) : "memory");
                }
                if (t == NS && late) {
                    mbar_wait(bar_full + (NS - INFLIGHT) * 8, 0);
                    mbar_expect_tx(bar_wm, D * 64);
#pragma unroll 1
                    for (int r = 0; r < D; r += 160) tma2d(sb + X_WM + r * 64, &tm_wmod, 32 * mc, r, bar_wm);
                }
                if (t >= NS && t < PF_END) {
                    int it = 0;
                    while (!mbar_test(bar_empty + (t & (NS - 1)) * 8, ((t >> 3) - 1) & 1)) {
                        if (tp < PF_END && (int)(gtime32() - t_start) >= PACE_A + (tp - NS) * PACE_TAU) {
                            asm volatile("cp.async.bulk.prefetch.L2.global.L2::cache_hint [%0], %1, %2;"
                                         ::"l"(((tp & 1) ? vb : kb) + (size_t)(((tp >> 1) + rot) & (NITEM / 2 - 1)) * TILE_BYTES), "r"(TILE_BYTES), "l"(pol) : "memory");
                            tp++;
                        }
                        if (++it > 16 * SPIN_LIMIT) __trap();
                    }
                    if (tp <= t) tp = t + 1;
                }
                if (t == NITEM) {
                    mbar_wait(bar_xfree, 0);
                    const uint32_t t_ref = t_start + sched + LAT_T + (NITEM - 1) * PACE_TAU;
#pragma unroll 1
                    for (int i = 0; i < 5; i++) {
                        while ((int)(gtime32() - t_ref) < WO_T + i * WO_S) { }
                        mbar_expect_tx(bar_wo + i * 8, DH * 64);
                        tma2d(sb + X_WO + i * (DH * 64), &tm_wo, bown * 160 + i * 32, head * DH, bar_wo + i * 8);
                    }
                    if (gb_own) {
                        mbar_wait(bar_empty + 3 * 8, ((NITEM >> 3) - 1) & 1);
                        while ((int)(gtime32() - t_ref) < GB_T) { }
#pragma unroll 1
                        for (int i = 0; i < 4; i++) {
                            mbar_expect_tx(bar_gb + i * 8, 160 * 16);
                            tma2d(sb + X_GB + i * (160 * 16), &tm_gb, 5 * D + 8 * own, 160 * i, bar_gb + i * 8);
                        }
                    }
                    if (is_f) {
#pragma unroll 1
                        for (int i = 0; i < 3; i++) mbar_wait(bar_empty + i * 8, ((NITEM >> 3) - 1) & 1);
                        while ((int)(gtime32() - t_ref) < W1_T) { }
#pragma unroll 1
                        for (int i = 0; i < 4; i++) {
                            mbar_expect_tx(bar_w1 + i * 8, 160 * 64);
                            tma2d(sb + X_W1 + i * (160 * 64), &tm_w1, 32 * f, 160 * i, bar_w1 + i * 8);
                        }
                        while ((int)(gtime32() - t_ref) < W2_T) { }
#pragma unroll 1
                        for (int i = 0; i < 10; i++) {
                            mbar_expect_tx(bar_w2 + i * 8, 4096);
                            tma2d(sb + X_W2 + i * 4096, &tm_w2, 64 * i, 32 * f, bar_w2 + i * 8);
                        }
                    }
                    break;
                }
                const int s = t & (NS - 1);
                if (t >= NS) {
                    mbar_wait(bar_empty + s * 8, ((t >> 3) - 1) & 1);
                    while ((int)(gtime32() - t_start) < sched + t * PACE_TAU) { }
                } else if (t >= INFLIGHT) {
                    mbar_wait(bar_full + (t - INFLIGHT) * 8, 0);
                }
                if (t < NITEM - 2) {
                    const int pair = t == NITEM - 3 ? NITEM / 2 - 1 : t >> 1;
                    mbar_expect_tx(bar_full + s * 8, TILE_BYTES);
                    bulk_load(sb + OFF_RING + s * TILE_BYTES, ((t & 1) && t != NITEM - 3 ? vb : kb) + (size_t)((pair + rot) & (NITEM / 2 - 1)) * TILE_BYTES, TILE_BYTES, bar_full + s * 8, pol);
                } else {
                    const int row = (bown * NH + head) * SK + (SK - WIN) + ((t - NITEM / 2 + rot) & (NITEM / 2 - 1)) * TILE_KEYS;
#pragma unroll 1
                    for (int i = 0; i < 2; i++) {
                        const uint32_t bar = bar_v + (2 * (t - (NITEM - 2)) + i) * 8;
                        mbar_expect_tx(bar, TILE_BYTES / 2);
                        tma2d_hint(sb + OFF_RING + s * TILE_BYTES + i * (TILE_BYTES / 2), &tm_v, 64 * i, row, bar, pol);
                    }
                }
                if (t >= PH_FIRST + PH_LAG && (t & 3) == (PH_LAG & 3)) {
                    const int now = (int)(gtime32() - t_start) - (t - PH_LAG) * PACE_TAU;
                    uint32_t ph;
                    asm volatile("atom.relaxed.gpu.global.add.u32 %0, [%1], 0;" : "=r"(ph) : "l"(g_phase + ((t - PH_LAG) >> 2) * 32) : "memory");
                    sched = (int)min(((ph & 0xffffffu) * 4 + (NCTA - (ph >> 24)) * now) >> 7, 65535u) - LAT_T;
                }
            }
        }
        __syncwarp();
    }

    if (warp == 9) {
        int side = 0;
        if (lane == 0) {
            uint32_t best[2] = {~0u, ~0u};
#pragma unroll 1
            for (int i = 0; i < 2 * NPROBE && ((i & 1) || (int)(gtime32() - t_start) < PROBE_END); i++) {
                uint32_t t0 = clock32(), v, t1;
                asm volatile("atom.relaxed.gpu.global.exch.b32 %0, [%1], %2;" : "=r"(v) : "l"(slot(SL_SIDE, i & 1) + cta * 8), "r"(0u) : "memory");
                asm volatile("{\n.reg .pred p;\nsetp.ne.u32 p, %1, 0xffffffff;\nmov.u32 %0, 0;\n@p mov.u32 %0, %%clock;\n}" : "=r"(t1) : "r"(v) : "memory");
                if (i & 1) best[1] = min(best[1], t1 - t0); else best[0] = min(best[0], t1 - t0);
            }
            side = best[1] < best[0];
        }
        side = __shfl_sync(0xffffffffu, side, 0);
        HPROF(1);
        mbar_wait(bar_full + (NS - 1) * 8, 0);
        stg_zero4(slot(SL_O + (cta >> 4), lane >> 4) + (cta & 15) * 64 + (lane & 15) * 4);
        if (is_owner) {
#pragma unroll 1
            for (int i = lane; i < NH * 8; i += 32) stg_zero4(slot(SL_P1 + own, side) + i * 4);
#pragma unroll 1
            for (int i = lane; i < NF * 8; i += 32) stg_zero4(slot(SL_P2 + 2 * own + (i >> 8), side) + (i & 255) * 4);
            if (lane < 8) stg_zero4(slot(SL_X1 + own / 30, lane >> 2) + (own % 30) * 32 + (lane & 3) * 4);
        }
        __threadfence();
        __syncwarp();
        if (lane == 0) stg_relaxed(g_clr + cta, 1u + side);
        HPROF(0);
        HPROF(2);
        while ((int)(gtime32() - t_start) < CLR_CHECK) __nanosleep(1000);
        mbar_wait(bar_xfree, 0);
        {
            uint4 v = make_uint4(1, 1, 1, 1), gv = v, mv[20];
#pragma unroll
            for (int i = 0; i < 20; i++) mv[i] = v;
#pragma unroll 1
            for (int it = 0;; it++) {
                v = ldg_relaxed(g_clr + lane * 4);

                ldg_relaxed_if(is_owner && lane < (gb_own ? 4 : 8), gv, mod_slot(lane < 4 ? 2 : 5, own, lane & 3));
#pragma unroll
                for (int i = 0; i < 20; i++) ldg_relaxed_if(is_f, mv[i], mod_slot(3, 8 * i + (lane >> 2), lane & 3));
                bool ok = ready(v) && ready(gv);
#pragma unroll
                for (int i = 0; i < 20; i++) ok = ok && ready(mv[i]);
                if (__all_sync(0xffffffffu, ok)) break;
                if (it > SPIN_LIMIT) __trap();
                __nanosleep(2000);
            }
            const uint32_t w[4] = {v.x, v.y, v.z, v.w};
#pragma unroll
            for (int i = 0; i < 4; i++) {
                const Roles r = roles(4 * lane + i);
                if (r.is_owner) {
                    sts32(sb + OFF_TAB1 + r.own * 4, (uint32_t)(size_t)(slot(SL_P1 + r.own, w[i] - 1) + head * 32));
                    sts32(sb + OFF_TAB2 + r.own * 4, (uint32_t)(size_t)(slot(SL_P2 + 2 * r.own + (f >> 5), w[i] - 1) + (f & 31) * 32));
                }
            }
            if (lane == 0) sts32(sb + OFF_SIDE, side);
            if (lane < 8) sts128(sb + OWN_GA + lane * 16, inv4(gv));
            const uint32_t dst = sb + OFF_VB + (lane & 3) * VEC_STRIDE + (lane >> 2) * 16;
#pragma unroll
            for (int i = 0; i < 10; i++) {
                const uint4 c = inv4(mv[10 + i]);
                sts128(dst + i * 128, make_uint4(bf2_add(c.x, 0x3f803f80u), bf2_add(c.y, 0x3f803f80u), bf2_add(c.z, 0x3f803f80u), bf2_add(c.w, 0x3f803f80u)));
                sts128(dst + (OFF_RED - OFF_VB) + i * 128, inv4(mv[i]));
            }
        }
        asm volatile("fence.acq_rel.gpu;" ::: "memory");
        __syncwarp();
        HPROF(3);
        if (lane == 0) mbar_arrive(bar_help);
        {
            const uint32_t* const src = pin(slot(SL_O + (cta >> 4), side) + (cta & 12) * 64 + lane * 4);
            const uint32_t dst = pin(sb + OFF_O + (lane >> 4) * O_STRIDE + (lane & 15) * 16);
            mbar_wait(bar_v + 16, 0);
            mbar_wait(bar_v + 24, 0);
            uint4 v[2];
            const uint32_t* const ptr[2] = {src, src + 128};
            const bool on[2] = {true, true};
            poll_n<2>(v, ptr, on);
            sts128(dst, v[0]);
            sts128(dst + 2 * O_STRIDE, v[1]);
#pragma unroll
            for (int w = 0; w < 8; w++) asm volatile("bar.arrive %0, 64;" ::"r"(NB_O + w) : "memory");
        }
        HPROF(4);
    }
    if (warp >= 8) {
        if (gb_own && warp == 9) {
            uint32_t a[20][4];
#pragma unroll
            for (int i = 0; i < 20; i++) ldsm4(a[i], sb + OFF_VA + (lane & 3) * VEC_STRIDE + (4 * i + (lane >> 3)) * 16);
            float c[4][4];
#pragma unroll
            for (int i = 0; i < 4; i++) c[i][0] = c[i][1] = c[i][2] = c[i][3] = 0.f;
#pragma unroll
            for (int bx = 0; bx < 4; bx++) {
                mbar_wait(bar_gb + bx * 8, 0);
#pragma unroll
                for (int i = 5 * bx; i < 5 * bx + 5; i++) {
                    uint32_t w[4];
                    ldsm4t(w, sb + X_GB + (32 * i + lane) * 16);
                    const uint32_t a0[4] = {a[i][0], 0u, a[i][1], 0u}, a1[4] = {a[i][2], 0u, a[i][3], 0u};
                    mma16816(c[(2 * i) & 3], a0, w[0], w[1]);
                    mma16816(c[(2 * i + 1) & 3], a1, w[2], w[3]);
                }
            }
            if (lane < 16) sts32(sb + OWN_GB + lane * 4, pack_bf((c[0][0] + c[1][0]) + (c[2][0] + c[3][0]), (c[0][1] + c[1][1]) + (c[2][1] + c[3][1])));
            HPROF(6);
        }
        if (is_owner && warp == 9) nbar_arrive<NB_E6, 288>();
        if (is_f) gelu_stage(sb, warp - 8, lane);
        return;
    }

    const int g = lane >> 2, t4 = lane & 3;
    const int mi = lane >> 3, r8 = lane & 7;

    {
        auto silu4 = [&](const uint4& cv) {
            uint32_t w4[4] = {cv.x, cv.y, cv.z, cv.w};
#pragma unroll
            for (int e = 0; e < 4; e++) {
                float c0 = bf_lo(w4[e]), c1 = bf_hi(w4[e]);
                w4[e] = pack_bf(c0 * rcp_fast(1.f + ex2(-1.4426950408889634f * c0)), c1 * rcp_fast(1.f + ex2(-1.4426950408889634f * c1)));
            }
            return make_uint4(w4[0], w4[1], w4[2], w4[3]);
        };
        {
            uint4 v = silu4(ca0);
            sts128(sb + OFF_VA + (tid / 80) * VEC_STRIDE + (tid % 80) * 16, v);
            if (tid < 64) { v = silu4(ca1); sts128(sb + OFF_VA + 3 * VEC_STRIDE + (16 + tid) * 16, v); }
        }
        if (warp < 4) {
            float s = 0.f, q = 0.f;
            const float pv = __shfl_sync(0xffffffffu, bf_lo(xs[0].x), 0);
#pragma unroll
            for (int i = 0; i < 3; i++) if (i < 2 || lane < 16) acc_stats(xs[i], pv, s, q);
#pragma unroll
            for (int of = 16; of > 0; of >>= 1) { s += __shfl_xor_sync(0xffffffffu, s, of); q += __shfl_xor_sync(0xffffffffu, q, of); }
            uint32_t m2; float rden;
            ln_finish(pv, s, q, m2, rden);
            if (lane == 0) { sts32(sb + OFF_STAT + warp * 8, m2); sts_f32(sb + OFF_STAT + warp * 8 + 4, rden); }
        } else if (warp == 4) {
            sts32(sb + OWN_X + lane * 4, bf2_add(own0, 0u));
            sts_f32(sb + OWN_B1 + lane * 4, bf2f(own2));
        }
    }
    bar_cons();
    PROF(24);
    uint32_t qf[8][2];
    float o[8][4];
#pragma unroll
    for (int c = 0; c < 8; c++) { o[c][0] = o[c][1] = o[c][2] = o[c][3] = 0.f; }
    float m_run = -INFINITY, l_run = 0.f;
    const bool diag = (t4 == (g >> 1));
    const bool odd = g & 1;
    const uint32_t koff = (warp & 3) * 4096 + (r8 + 8 * (mi & 1)) * 256 + (mi >> 1) * 128 + (r8 << 4);
    const uint32_t voff = TILE_BYTES + (warp & 3) * 4096 + (r8 + 8 * (mi >> 1)) * 256 + (mi & 1) * 128 + (r8 << 4);
    const int src0 = (2 * t4) * 4 + t4, src1 = (2 * t4 + 1) * 4 + t4;
#pragma unroll 1
    for (int step = crit ? 0 : 1; step < 3; step++) {
        if (step < 2 || late) {
            if (step == 1) {
                if (!crit) mbar_wait(bar_wq, 0);
                const uint32_t m2 = lds32(sb + OFF_STAT + (tid & 3) * 8);
                const float rden = lds_f32(sb + OFF_STAT + (tid & 3) * 8 + 4);
                uint4 v[4] = {xa, xa, xa, xa};
                const uint32_t* const ptr[4] = {mod_slot(0, tid >> 2, tid & 3), mod_slot(1, tid >> 2, tid & 3),
                                                mod_slot(0, 64 + ((tid & 63) >> 2), tid & 3), mod_slot(1, 64 + ((tid & 63) >> 2), tid & 3)};
                const bool on[4] = {true, true, tid < 64, tid < 64};
                poll_n<4>(v, ptr, on);
                uint4 h0 = ln_mod4(xa, v[1], v[0], m2, rden);
                sts128(sb + OFF_VB + (tid & 3) * VEC_STRIDE + (tid >> 2) * 16, h0);
                if (tid < 64) {
                    h0 = ln_mod4(xb, v[3], v[2], m2, rden);
                    sts128(sb + OFF_VB + (tid & 3) * VEC_STRIDE + (64 + (tid >> 2)) * 16, h0);
                }
            }
            mbar_wait(step == 1 ? bar_wq : bar_wm, 0);
            bar_cons();
            const uint32_t strip = sb + (step == 1 ? X_WQ : X_WM), vec = sb + (step == 1 ? OFF_VB : OFF_VA);
            float acc[2][4];
#pragma unroll
            for (int m = 0; m < 2; m++) { acc[m][0] = acc[m][1] = acc[m][2] = acc[m][3] = 0.f; }
#pragma unroll
            for (int i = 0; i < 5; i++) {
                int k0 = (warp * 5 + i) * 16;
                uint32_t b0, b1;
                load_bfrag(vec, VEC_STRIDE, k0, g, t4, b0, b1);
                int krow = k0 + r8 + 8 * (mi >> 1);
#pragma unroll
                for (int m = 0; m < 2; m++) {
                    uint32_t a[4];
                    int ch = 2 * m + (mi & 1);
                    ldsm4t(a, strip + krow * 64 + ((ch ^ ((krow >> 1) & 3)) << 4));
                    mma16816(acc[m], a, b0, b1);
                }
            }
            if (t4 < 2) {
#pragma unroll
                for (int m = 0; m < 2; m++) {
                    sts_f32x2(sb + OFF_RED + ((warp * 32 + m * 16 + g) * 4 + 2 * t4) * 4, acc[m][0], acc[m][1]);
                    sts_f32x2(sb + OFF_RED + ((warp * 32 + m * 16 + g + 8) * 4 + 2 * t4) * 4, acc[m][2], acc[m][3]);
                }
            }
            bar_cons();
            if (tid < 128) {
                float v = 0.f;
#pragma unroll
                for (int w = 0; w < 8; w++) v += lds_f32(sb + OFF_RED + (w * 128 + tid) * 4);
                float vn = __shfl_down_sync(0xffffffffu, v, 4);
                uint32_t* dst = step == 1 ? g_q + ((cta & ~3) + (tid & 3)) * 64 + bown * 16 + (tid >> 3) : g_mod + mc * 64 + (tid & 3) * 16 + (tid >> 3);
                if (!((tid >> 2) & 1)) stg_relaxed(dst, ~pack_bf(v, vn));
            }
        }
        if (step == 0) continue;
        if (step == 1) {
            if (warp == 0) {
                uint4 v = poll1(g_q + cta * 64 + (lane & 15) * 4, lane < 16);
                if (lane < 16) {
                    sts128(sb + OFF_Q + lane * 16, v);
                    stg_zero4(g_q + cta * 64 + lane * 4);
                }
            }
            bar_cons();
            PROF(4);

#pragma unroll
            for (int c = 0; c < 8; c++) {
                qf[c][0] = lds32(sb + OFF_Q + (((c ^ g) * 4 + t4) << 2));
                qf[c][1] = lds32(sb + OFF_Q + 128 + (((c ^ g) * 4 + t4) << 2));
            }
        } else {
            bar_cons();
            if (tid == 0) mbar_arrive(bar_xfree);
        }
#pragma unroll 1
        for (int j = (step == 1 ? 0 : SEG_J) + (warp >> 2); j < (step == 1 ? SEG_J : NITEM / 2 - 2); j += 2) {
            const int s = (2 * j) & (NS - 1);
            const uint32_t par = (j >> 2) & 1;
            mbar_wait(bar_full + s * 8, par);
            if (tid == 0 && 2 * j >= PH_FIRST) {
                const int x = min(max((int)(gtime32() - t_start) - 2 * j * PACE_TAU, 0), 65535);
                asm volatile("red.relaxed.gpu.global.add.u32 [%0], %1;" ::"l"(g_phase + (j >> 1) * 32), "r"((1u << 24) + (x >> 2)) : "memory");
            }
            const uint32_t base = sb + OFF_RING + s * TILE_BYTES;
            float sa[4] = {0.f, 0.f, 0.f, 0.f}, sb2[4] = {0.f, 0.f, 0.f, 0.f};
#pragma unroll
            for (int c = 0; c < 8; c += 2) {
                uint32_t a[4], a2[4];
                ldsm4(a, (base + koff) ^ (c << 4));
                ldsm4(a2, (base + koff) ^ ((c + 1) << 4));
                mma16816(sa, a, qf[c][0], qf[c][1]);
                mma16816(sb2, a2, qf[c + 1][0], qf[c + 1][1]);
            }
            const uint32_t sw = pack_bf(odd ? sa[1] + sb2[1] : sa[0] + sb2[0], odd ? sa[3] + sb2[3] : sa[2] + sb2[2]);
            const uint32_t sv = pack_bf(bf_lo(sw) * 0.08838834764831845f, bf_hi(sw) * 0.08838834764831845f);
            const float s0 = bf_lo(sv) * 1.4426950408889634f, s1 = bf_hi(sv) * 1.4426950408889634f;
            float m_new = fmaxf(m_run, fmaxf(s0, s1));
            const bool grow = __any_sync(0xffffffffu, (diag && (m_new > m_run)));
            if (lane == 0) mbar_arrive(bar_empty + s * 8);
            if (grow) {
                float al = ex2(m_run - m_new);
                float a0 = __shfl_sync(0xffffffffu, al, src0), a1 = __shfl_sync(0xffffffffu, al, src1);
#pragma unroll
                for (int c = 0; c < 8; c++) { o[c][0] *= a0; o[c][1] *= a1; o[c][2] *= a0; o[c][3] *= a1; }
                l_run *= al;
                m_run = m_new;
            }
            uint32_t pw = pack_bf(ex2(s0 - m_run), ex2(s1 - m_run));
            l_run += bf_lo(pw) + bf_hi(pw);
            uint32_t b0 = odd ? (pw << 16) : (pw & 0xffffu);
            uint32_t b1 = odd ? (pw & 0xffff0000u) : (pw >> 16);
            if (!diag) { b0 = 0u; b1 = 0u; }
            mbar_wait(bar_full + (s + 1) * 8, par);
#pragma unroll
            for (int c = 0; c < 8; c++) {
                uint32_t a[4];
                ldsm4t(a, (base + voff) ^ (c << 4));
                mma16816(o[c], a, b0, b1);
            }
            __syncwarp();
            if (lane == 0) mbar_arrive(bar_empty + (s + 1) * 8);
        }
    }
    PROF(5);
    float acc[4][4];
    uint32_t pa[8][2];
    float rinv;
    {
        const int s = 4 + (warp >> 2);
        mbar_wait(bar_full + s * 8, 1);
        const uint32_t base = sb + OFF_RING + s * TILE_BYTES;
        float sa[4] = {0.f, 0.f, 0.f, 0.f}, sb2[4] = {0.f, 0.f, 0.f, 0.f};
#pragma unroll
        for (int c = 0; c < 8; c += 2) {
            uint32_t a[4], a2[4];
            ldsm4(a, (base + koff) ^ (c << 4));
            ldsm4(a2, (base + koff) ^ ((c + 1) << 4));
            mma16816(sa, a, qf[c][0], qf[c][1]);
            mma16816(sb2, a2, qf[c + 1][0], qf[c + 1][1]);
        }
        const uint32_t sw = pack_bf(odd ? sa[1] + sb2[1] : sa[0] + sb2[0], odd ? sa[3] + sb2[3] : sa[2] + sb2[2]);
        const uint32_t sv = pack_bf(bf_lo(sw) * 0.08838834764831845f, bf_hi(sw) * 0.08838834764831845f);
        const float s0 = bf_lo(sv) * 1.4426950408889634f, s1 = bf_hi(sv) * 1.4426950408889634f;
        int mi_ = __float_as_int(diag ? fmaxf(m_run, fmaxf(s0, s1)) : -INFINITY);
        mi_ ^= (mi_ >> 31) & 0x7fffffff;
        mi_ = __reduce_max_sync(0xffffffffu, mi_);
        mi_ ^= (mi_ >> 31) & 0x7fffffff;
        if (lane == 0) sts32(sb + OFF_ML + warp * 4, mi_);
        bar_cons();
        const float4 m0 = lds_f32x4(sb + OFF_ML), m1 = lds_f32x4(sb + OFF_ML + 16);
        const float mx = fmaxf(fmaxf(fmaxf(m0.x, m0.y), fmaxf(m0.z, m0.w)), fmaxf(fmaxf(m1.x, m1.y), fmaxf(m1.z, m1.w)));
        const float scl = ex2(m_run - mx);
        const uint32_t pw = pack_bf(ex2(s0 - mx), ex2(s1 - mx));
        if (diag) { sts16(sb + SC_P + (warp * 16 + g) * 2, pw); sts16(sb + SC_P + (warp * 16 + g + 8) * 2, pw >> 16); }
        const float lw = warp_sum(diag ? fmaf(l_run, scl, bf_lo(pw) + bf_hi(pw)) : 0.f);
        const float a0 = __shfl_sync(0xffffffffu, scl, src0), a1 = __shfl_sync(0xffffffffu, scl, src1);
        float v[8], u[8];
#pragma unroll
        for (int c = 0; c < 8; c++) {
            v[c] = a0 * o[c][0] + a1 * o[c ^ 1][1];
            u[c] = a0 * o[c][2] + a1 * o[c ^ 1][3];
        }
#pragma unroll
        for (int c = 0; c < 8; c++) {
            if (!(c & 2)) {
                v[c] += __shfl_xor_sync(0xffffffffu, v[c ^ 2], 1);
                u[c] += __shfl_xor_sync(0xffffffffu, u[c ^ 2], 1);
            }
        }
#pragma unroll
        for (int c = 0; c < 2; c++) {
            v[c] += __shfl_xor_sync(0xffffffffu, v[c ^ 4], 2);
            u[c] += __shfl_xor_sync(0xffffffffu, u[c ^ 4], 2);
        }
        const uint32_t dst = sb + SC_OP + (warp * 128 + 16 * t4 + g) * 4;
        sts_f32(dst, v[0]); sts_f32(dst + 32, v[1]); sts_f32(dst + 256, u[0]); sts_f32(dst + 288, u[1]);
        if (lane == 0) sts_f32(sb + OFF_ML + 32 + warp * 4, lw);
        mbar_wait(bar_help, 0);
        bar_cons();
        const float4 l0 = lds_f32x4(sb + OFF_ML + 32), l1 = lds_f32x4(sb + OFF_ML + 48);
        rinv = rcp_fast(((l0.x + l0.y) + (l0.z + l0.w)) + ((l1.x + l1.y) + (l1.z + l1.w)));
#pragma unroll
        for (int i = 0; i < 4; i++) acc[i][0] = acc[i][1] = acc[i][2] = acc[i][3] = 0.f;
#pragma unroll
        for (int w = 0; w < 8; w++) {
            const float2 x0 = lds_f32x2(sb + SC_OP + (w * 128 + 16 * warp + 2 * t4) * 4), x1 = lds_f32x2(sb + SC_OP + (w * 128 + 16 * warp + 8 + 2 * t4) * 4);
            acc[2 * (w & 1)][0] += x0.x; acc[2 * (w & 1)][1] += x0.y;
            acc[2 * (w & 1) + 1][0] += x1.x; acc[2 * (w & 1) + 1][1] += x1.y;
        }
#pragma unroll
        for (int ks = 0; ks < 8; ks++) { pa[ks][0] = lds32(sb + SC_P + (8 * ks + t4) * 4); pa[ks][1] = lds32(sb + SC_P + (8 * ks + 4 + t4) * 4); }
    }
    PROF(20);
    const int mt = warp < 2 ? warp : warp + 2;
    {
        const uint32_t va = pin(sb + OFF_RING + 6 * TILE_BYTES + (warp >> 2) * (TILE_BYTES / 2) + (8 * (mi & 1) + r8) * 128 + (((2 * (warp & 3) + (mi >> 1)) ^ r8) << 4));
        const uint32_t vbar = pin(bar_v + (warp >> 2) * 8);
        uint32_t* const o_dst = pin(slot(SL_O + (cta >> 4), g) + (cta & 15) * 64 + warp * 8 + 2 * t4);
#pragma unroll
        for (int tl = 0; tl < 2; tl++) {
            mbar_wait(vbar + tl * 16, 0);
            uint32_t r[4][4];
#pragma unroll
            for (int ks = 0; ks < 4; ks++) ldsm4t(r[ks], va + tl * TILE_BYTES + ks * 2048);
#pragma unroll
            for (int ks = 0; ks < 4; ks++) {
                const uint32_t a[4] = {pa[4 * tl + ks][0], 0u, pa[4 * tl + ks][1], 0u};
                mma16816(acc[2 * (ks & 1)], a, r[ks][0], r[ks][1]);
                mma16816(acc[2 * (ks & 1) + 1], a, r[ks][2], r[ks][3]);
            }
        }
        stg_relaxed2_if(g < 2, o_dst, ~pack_bf((acc[0][0] + acc[2][0]) * rinv, (acc[0][1] + acc[2][1]) * rinv),
                        ~pack_bf((acc[1][0] + acc[3][0]) * rinv, (acc[1][1] + acc[3][1]) * rinv));
    }
    PROF(7);
    const int side = lds32(sb + OFF_SIDE);
    const uint32_t red_st = pin(sb + SC_E4 + ((warp * 4 + 2 * ((lane >> 3) & 1) + (lane >> 4)) * 8 + (lane & 7)) * 4);
    const uint32_t red_ld = pin(sb + SC_E4 + (lane & 15) * 8);
    const uint32_t* const in1 = pin(slot(SL_P1 + own, side) + tid * 4);
    const uint32_t* const in2a = pin(slot(SL_P2 + 2 * own, side) + tid * 4);
    const uint32_t* const in2b = pin(slot(SL_P2 + 2 * own + 1, side) + tid * 4);
    uint32_t* const out_dst = pin((uint32_t*)(p.out + ((lane >> 2) & 3) * D + 8 * own) + t4);
    uint32_t* const x1_dst = pin(slot(SL_X1 + own / 30, lane >> 4) + (own % 30) * 32 + (lane & 15));
    uint32_t* const rst = pin(tid >= 32 && tid < 56 ? mod_slot(lane >> 2, own, lane & 3) : own < 32 && tid == 64 ? g_clr + own * 4 : own < 16 && tid == 96 ? g_phase + own * 32 : nullptr);
    const uint32_t xw = lds32(sb + OWN_X + (lane & 15) * 4), ga_w = lds32(sb + OWN_GA + (lane & 15) * 4);
    uint32_t cs[15];
    uint32_t* dst2[10];
    uint32_t w2a[5];
#pragma unroll
    for (int j = 0; j < 10; j++) cs[j] = lds32(sb + OFF_VB + ((g & 1) * 4 + (g >> 1)) * VEC_STRIDE + warp * 160 + t4 * 4 + j * 16);
#pragma unroll
    for (int i = 0; i < 5; i++) {
        cs[10 + i] = lds32(sb + OFF_VB + (g >> 1) * VEC_STRIDE + warp * 160 + (g & 1) * 16 + t4 * 4 + i * 32);
        const uint2 t = lds64(sb + OFF_TAB2 + warp * 40 + i * 8);
        dst2[2 * i] = slot_ptr(t.x + g * 16 + t4 * 8);
        dst2[2 * i + 1] = slot_ptr(t.y + g * 16 + t4 * 8);
        const int cc = 2 * (warp * 5 + i) + (mi & 1);
        w2a[i] = pin(sb + X_W2 + (cc >> 3) * 4096 + (r8 + 8 * (mi >> 1)) * 128 + (((cc & 7) ^ r8) << 4));
    }
    const uint32_t piv = lds32(sb + OFF_STAT + (g >> 1) * 8);
    const uint32_t* const xin = pin(slot(SL_X1 + warp / 3, side) + ((warp % 3) * 10 + (g & 1)) * 32 + (g >> 1) * 4 + t4);
    const uint32_t w1a = pin(sb + X_W1 + (warp * 80 + r8 + 8 * (mi >> 1)) * 64 + (((mi & 1) ^ ((r8 >> 1) & 3)) << 4));
    const uint32_t w1bar = pin(bar_w1 + (warp >> 1) * 8), w2bar = pin(bar_w2 + (warp + (warp >> 2)) * 8);
    const uint32_t wbar = pin(NB_O + warp);
    const uint32_t ab_st = pin(sb + SC_AB + warp * 1024 + lane * 16), y_st = pin(sb + SC_Y + warp * 512 + lane * 8), s_st = pin(sb + SC_ST + (t4 * 8 + warp) * 8);
    const uint32_t h_ld = pin(sb + SC_H1 + ((g & 3) ^ (2 * (f & 1) + ((f >> 1) & 1))) * 64 + t4 * 16);
    {
        const int kap = 2 * (head & 1) + ((head >> 1) & 1);
        const uint32_t wa = pin(sb + X_WO + (mt >> 1) * (DH * 64) + (r8 + 8 * (mi >> 1)) * 64 + ((((mt & 1) * 2 + (mi & 1)) ^ ((r8 >> 1) & 3)) << 4));
        const uint32_t oa = pin(sb + OFF_O + ((g & 3) ^ kap) * O_STRIDE + t4 * 8);
        uint32_t* dst[4];
#pragma unroll
        for (int i = 0; i < 2; i++) {
            const uint2 t = lds64(sb + OFF_TAB1 + (bown * 20 + 2 * mt + (warp < 2 ? 4 * i : 0)) * 4);
            dst[2 * i] = slot_ptr(t.x + g * 16 + t4 * 8);
            dst[2 * i + 1] = slot_ptr(t.y + g * 16 + t4 * 8);
        }
        PROF(6);
        uint32_t wf[8][4], wg[8][4];
        mbar_wait(bar_wo + (mt >> 1) * 8, 0);
#pragma unroll
        for (int ks = 0; ks < 8; ks++) ldsm4t(wf[ks], wa + ks * 1024);
        if (warp < 2) {
            mbar_wait(bar_wo + 8, 0);
#pragma unroll
            for (int ks = 0; ks < 8; ks++) ldsm4t(wg[ks], wa + DH * 64 + ks * 1024);
        }
        asm volatile("bar.sync %0, 64;" ::"r"(wbar) : "memory");
        PROF(8);
        uint2 ob[8];
#pragma unroll
        for (int ks = 0; ks < 8; ks++) ob[ks] = lds64(oa + ks * 32);
        float c0[4] = {0.f, 0.f, 0.f, 0.f}, c1[4] = {0.f, 0.f, 0.f, 0.f};
        if (warp < 2) {
            float c2[4] = {0.f, 0.f, 0.f, 0.f}, c3[4] = {0.f, 0.f, 0.f, 0.f};
#pragma unroll
            for (int ks = 0; ks < 8; ks += 2) {
                mma16816(c0, wf[ks], ob[ks].x, ob[ks].y);
                mma16816(c2, wg[ks], ob[ks].x, ob[ks].y);
                mma16816(c1, wf[ks + 1], ob[ks + 1].x, ob[ks + 1].y);
                mma16816(c3, wg[ks + 1], ob[ks + 1].x, ob[ks + 1].y);
            }
            stg_relaxed2_if(t4 < 2, dst[2], flag(c2[0] + c3[0]), flag(c2[1] + c3[1]));
            stg_relaxed2_if(t4 < 2, dst[3], flag(c2[2] + c3[2]), flag(c2[3] + c3[3]));
        } else {
#pragma unroll
            for (int ks = 0; ks < 8; ks += 2) {
                mma16816(c0, wf[ks], ob[ks].x, ob[ks].y);
                mma16816(c1, wf[ks + 1], ob[ks + 1].x, ob[ks + 1].y);
            }
        }
        stg_relaxed2_if(t4 < 2, dst[0], flag(c0[0] + c1[0]), flag(c0[1] + c1[1]));
        stg_relaxed2_if(t4 < 2, dst[1], flag(c0[2] + c1[2]), flag(c0[3] + c1[3]));
    }
    PROF(9);
    uint32_t x1w = 0;
    if (is_owner) {
        uint4 v;
        for (int it = 0;; it++) {
            v = ldg_relaxed(in1);
            if (__all_sync(0xffffffffu, and3(and3(v.x, v.y, v.z), v.w, 1u))) break;
            if (it > SPIN_LIMIT) __trap();
        }
        PROF(11);
        const float s0 = __uint_as_float(v.x) + __shfl_xor_sync(0xffffffffu, __uint_as_float(v.z), 8);
        const float s1 = __uint_as_float(v.y) + __shfl_xor_sync(0xffffffffu, __uint_as_float(v.w), 8);
        sts_f32(red_st, s0 + __shfl_xor_sync(0xffffffffu, s1, 16));
        nbar_sync<NB_E4, 256>();
        if (warp == 0) {
            float2 a[8];
#pragma unroll
            for (int w = 0; w < 8; w++) a[w] = lds_f32x2(red_ld + w * 128);
            const uint32_t aw = pack_bf(((a[0].x + a[1].x) + (a[2].x + a[3].x)) + ((a[4].x + a[5].x) + (a[6].x + a[7].x)),
                                        ((a[0].y + a[1].y) + (a[2].y + a[3].y)) + ((a[4].y + a[5].y) + (a[6].y + a[7].y)));
            x1w = bf2_add(xw, bf2_mul(ga_w, aw));
            stg_relaxed(x1_dst, x1w ^ 0x80008000u);
        }
        if (rst) stg_zero4(rst);
    }
    PROF(12);
    if (is_f) {
        uint32_t f1[5][2][4], f2[5][2][4];
        uint32_t d[6];
        auto load_x1 = [&] {
#pragma unroll
            for (int i = 0; i < 5; i++) d[i] = ldg_relaxed32(xin + i * 64);
        };
        auto have_x1 = [&] { return __all_sync(0xffffffffu, __vimin3_u32(__vimin3_u32(d[0], d[1], d[2]), d[3], d[4]) != 0u); };
        mbar_wait(w1bar, 0);
        load_x1();
        {
#pragma unroll
            for (int i = 0; i < 5; i++) { ldsm4t(f1[i][0], w1a + i * 1024); ldsm4t(f1[i][1], (w1a ^ 32) + i * 1024); }
            float c[2][4];
#pragma unroll
            for (int m = 0; m < 2; m++) c[m][0] = c[m][1] = c[m][2] = c[m][3] = 0.f;
#pragma unroll
            for (int i = 0; i < 5; i++) { mma16816(c[0], f1[i][0], cs[2 * i], cs[2 * i + 1]); mma16816(c[1], f1[i][1], cs[2 * i], cs[2 * i + 1]); }
#pragma unroll
            for (int i = 0; i < 5; i++) { cs[2 * i] = pin(odd ? 0u : cs[10 + i]); cs[2 * i + 1] = pin(odd ? cs[10 + i] : 0u); }
#pragma unroll
            for (int m = 0; m < 2; m++) sts128(ab_st + m * 512, make_uint4(__float_as_uint(c[m][0]), __float_as_uint(c[m][1]), __float_as_uint(c[m][2]), __float_as_uint(c[m][3])));
            nbar_arrive<NB_AB, 320>();
            d[0] |= __float_as_uint(c[1][3]) & (side >> 1);
        }
        PROF(10);
#pragma unroll 1
        for (int it = 0; !have_x1(); it++) {
            load_x1();
            if (it > SPIN_LIMIT) __trap();
        }
        PROF(13);
        {
            float y[2][4], st[4] = {0.f, 0.f, 0.f, 0.f};
#pragma unroll
            for (int m = 0; m < 2; m++) y[m][0] = y[m][1] = y[m][2] = y[m][3] = 0.f;
#pragma unroll
            for (int i = 0; i < 5; i++) d[i] = bf2_add(d[i], piv);
            d[5] = 0u;
#pragma unroll
            for (int i = 0; i < 5; i++) {
                if (i < 3) {
                    const uint32_t a[4] = {d[2 * i], 0x3f803f80u, d[2 * i + 1], 0x3f803f80u};
                    mma16816(st, a, d[2 * i], d[2 * i + 1]);
                }
                const uint32_t y0 = bf2_mul(d[i], cs[2 * i]), y1 = bf2_mul(d[i], cs[2 * i + 1]);
                mma16816(y[0], f1[i][0], y0, y1);
                mma16816(y[1], f1[i][1], y0, y1);
            }
            const float q = odd ? st[1] : st[0];
            const float q2 = q + __shfl_xor_sync(0xffffffffu, q, 4);
            if (diag && !odd) sts_f32x2(s_st, q2, st[2] + st[3]);
#pragma unroll
            for (int m = 0; m < 2; m++) sts_f32x2(y_st + m * 256, y[m][0] + y[m][1], y[m][2] + y[m][3]);
        }
        nbar_arrive<NB_Y, 320>();
        PROF(14);
        mbar_wait(w2bar, 0);
        mbar_wait(w2bar + 8, 0);
#pragma unroll
        for (int i = 0; i < 5; i++) { ldsm4t(f2[i][0], w2a[i]); ldsm4t(f2[i][1], w2a[i] + 2048); }
        asm volatile("bar.sync %0, 96;" ::"r"(wbar) : "memory");
        PROF(15);
        {
            const uint4 hb = lds128(h_ld);
            float c[5][4];
#pragma unroll
            for (int i = 0; i < 7; i++) {
                if (i < 5) { c[i][0] = c[i][1] = c[i][2] = c[i][3] = 0.f; mma16816(c[i], f2[i][0], hb.x, hb.y); }
                if (i > 0 && i < 6) mma16816(c[i - 1], f2[i - 1][1], hb.z, hb.w);
                if (i > 1) {
                    stg_relaxed2_if(t4 < 2, dst2[2 * i - 4], flag(c[i - 2][0]), flag(c[i - 2][1]));
                    stg_relaxed2_if(t4 < 2, dst2[2 * i - 3], flag(c[i - 2][2]), flag(c[i - 2][3]));
                }
            }
        }
    }
    PROF(16);
    if (is_owner) {
        const uint32_t b2w = lds32(sb + OWN_B2 + (lane & 15) * 4), gb_ld = pin(sb + OWN_GB + (lane & 15) * 4);
        const bool two = tid < NF * 8 - 256;
        uint4 v, w = make_uint4(1, 1, 1, 1);
        for (int it = 0;; it++) {
            ldg_relaxed_if(two, w, in2b);
            v = ldg_relaxed(in2a);
            if (__all_sync(0xffffffffu, and3(and3(v.x, v.y, v.z), and3(v.w, w.x, w.y), and3(w.z, w.w, 1u)))) break;
            if (it > SPIN_LIMIT) __trap();
        }
        PROF(17);
        const float s0 = (__uint_as_float(v.x) + __uint_as_float(w.x)) + __shfl_xor_sync(0xffffffffu, __uint_as_float(v.z) + __uint_as_float(w.z), 8);
        const float s1 = (__uint_as_float(v.y) + __uint_as_float(w.y)) + __shfl_xor_sync(0xffffffffu, __uint_as_float(v.w) + __uint_as_float(w.w), 8);
        sts_f32(red_st + (SC_E6 - SC_E4), s0 + __shfl_xor_sync(0xffffffffu, s1, 16));
        if (warp != 0) {
            nbar_arrive<NB_E6, 288>();
        } else {
            nbar_sync<NB_E6, 288>();
            float2 a[8];
#pragma unroll
            for (int i = 0; i < 8; i++) a[i] = lds_f32x2(red_ld + (SC_E6 - SC_E4) + i * 128);
            const uint32_t gb_w = lds32(gb_ld);
            const uint32_t aw = pack_bf(((a[0].x + a[1].x) + (a[2].x + a[3].x)) + ((a[4].x + a[5].x) + (a[6].x + a[7].x)),
                                        ((a[0].y + a[1].y) + (a[2].y + a[3].y)) + ((a[4].y + a[5].y) + (a[6].y + a[7].y)));
            x1w = bf2_add(x1w, bf2_mul(gb_w, bf2_add(aw, b2w)));
            if (lane < 16) asm volatile("st.global.u32 [%0], %1;" ::"l"(out_dst), "r"(x1w) : "memory");
        }
    }
    PROF(18);
    PROF_DUMP;
}

typedef CUresult (*EncodeFn)(CUtensorMap*, CUtensorMapDataType, cuuint32_t, void*, const cuuint64_t*, const cuuint64_t*, const cuuint32_t*,
                             const cuuint32_t*, CUtensorMapInterleave, CUtensorMapSwizzle, CUtensorMapL2promotion, CUtensorMapFloatOOBfill);

static CUtensorMap make_map(EncodeFn enc, const void* ptr, int cols, int rows, int box_cols, int box_rows, CUtensorMapSwizzle sw,
                            CUtensorMapL2promotion promo = CU_TENSOR_MAP_L2_PROMOTION_NONE) {
    CUtensorMap m;
    cuuint64_t dims[2] = {(cuuint64_t)cols, (cuuint64_t)rows};
    cuuint64_t strides[1] = {(cuuint64_t)cols * 2};
    cuuint32_t box[2] = {(cuuint32_t)box_cols, (cuuint32_t)box_rows};
    cuuint32_t es[2] = {1, 1};
    enc(&m, CU_TENSOR_MAP_DATA_TYPE_BFLOAT16, 2, const_cast<void*>(ptr), dims, strides, box, es, CU_TENSOR_MAP_INTERLEAVE_NONE, sw,
        promo, CU_TENSOR_MAP_FLOAT_OOB_FILL_NONE);
    return m;
}

}

extern "C" void kernel_launch(void* const* d_in, const int* in_sizes, int n_in, void* d_out, int out_size) {
    (void)in_sizes; (void)n_in; (void)out_size;
    static EncodeFn enc = nullptr;
    if (!enc) {
        void* fn = nullptr;
        cudaDriverEntryPointQueryResult qr;
        cudaGetDriverEntryPoint("cuTensorMapEncodeTiled", &fn, cudaEnableDefault, &qr);
        enc = (EncodeFn)fn;
        cudaFuncSetAttribute(fused_kernel, cudaFuncAttributeMaxDynamicSharedMemorySize, SMEM_BYTES);
    }
    Params p;
    p.x = (const __nv_bfloat16*)d_in[0];
    p.kc = (const __nv_bfloat16*)d_in[1];
    p.vc = (const __nv_bfloat16*)d_in[2];
    p.b1 = (const __nv_bfloat16*)d_in[7];
    p.b2 = (const __nv_bfloat16*)d_in[9];
    p.c = (const __nv_bfloat16*)d_in[10];
    p.out = (__nv_bfloat16*)d_out;
    CUtensorMap tm_wmod = make_map(enc, d_in[11], NMOD, D, 32, 160, CU_TENSOR_MAP_SWIZZLE_64B);
    CUtensorMap tm_wq = make_map(enc, d_in[3], NH * DH, D, 32, 160, CU_TENSOR_MAP_SWIZZLE_64B);
    CUtensorMap tm_wo = make_map(enc, d_in[4], D, NH * DH, 32, 128, CU_TENSOR_MAP_SWIZZLE_64B);
    CUtensorMap tm_w1 = make_map(enc, d_in[6], FF, D, 32, 160, CU_TENSOR_MAP_SWIZZLE_64B);
    CUtensorMap tm_w2 = make_map(enc, d_in[8], D, FF, 64, 32, CU_TENSOR_MAP_SWIZZLE_128B);
    CUtensorMap tm_v = make_map(enc, d_in[2], DH, NB * NH * SK, 64, TILE_KEYS, CU_TENSOR_MAP_SWIZZLE_128B);
    CUtensorMap tm_gb = make_map(enc, d_in[11], NMOD, D, 8, 160, CU_TENSOR_MAP_SWIZZLE_NONE, CU_TENSOR_MAP_L2_PROMOTION_L2_128B);
    fused_kernel<<<NCTA, NTHREADS, SMEM_BYTES>>>(p, tm_wmod, tm_wq, tm_wo, tm_w1, tm_w2, tm_v, tm_gb);
}
```

```cpp
#include <cuda_runtime.h>
#include <cuda.h>
#include <cuda_bf16.h>
#include <stdint.h>

namespace {

constexpr int NB = 4, D = 640, NH = 32, DH = 128, SK = 8192, WIN = 2048, FF = 1728, NMOD = 6 * D;
constexpr int NCTA = 128;
constexpr int NOWN = 80;
constexpr int NF = 54;
constexpr int NTHREADS = 320;
constexpr int TILE_KEYS = 64;
constexpr int TILE_BYTES = TILE_KEYS * DH * 2;
constexpr int NITEM = 2 * WIN / TILE_KEYS;
constexpr int NS = 8;
constexpr int NMODC = 120;
constexpr int SPIN_LIMIT = 1 << 18;
#define INFLIGHT 3
#define WQ_DELAY 400
#define PACE_A 7800
#define PACE_TAU 635
#define PF_END 14
#define PH_FIRST 20
#define PH_LAG 5
#define LAT_T 2100
#define WO_T -1100
#define WO_S 200
#define W1_T 1000
#define W2_T 1700
#define GB_T 2500
#define GB_EV 300
#define CLR_CHECK 28000
constexpr int NPROBE = 8, PROBE_END = 10000;
constexpr int SEG_J = 8;

constexpr int OFF_RING = 0;
constexpr int OFF_X = OFF_RING + NS * TILE_BYTES;
constexpr int X_WM = OFF_X;
constexpr int X_WQ = OFF_X + D * 64;
constexpr int X_WO = OFF_X;
constexpr int X_W1 = X_WO + 5 * DH * 64;
constexpr int X_END = X_W1 + D * 64;
constexpr int X_W2 = OFF_RING;
constexpr int X_GB = OFF_RING + 3 * TILE_BYTES;
static_assert(X_WQ + D * 64 <= X_END, "prologue weights must fit");
constexpr int VEC_STRIDE = 1296;
constexpr int OFF_VA = X_END;
constexpr int OFF_VB = OFF_VA + 4 * VEC_STRIDE;
constexpr int OFF_RED = OFF_VB + 4 * VEC_STRIDE;
constexpr int OFF_ML = OFF_RED + 4 * VEC_STRIDE;
constexpr int O_STRIDE = 288;
constexpr int OFF_O = OFF_ML + 64;
constexpr int OFF_Q = OFF_O + 4 * O_STRIDE;
constexpr int OFF_OWN = OFF_Q + 256;
constexpr int OWN_X = OFF_OWN, OWN_B2 = OWN_X + 64, OWN_GA = OWN_B2 + 64, OWN_GB = OWN_GA + 64, OWN_B1 = OWN_GB + 64;
constexpr int OFF_STAT = OWN_B1 + 128;
constexpr int OFF_TAB1 = OFF_STAT + 32;
constexpr int OFF_TAB2 = OFF_TAB1 + NOWN * 4;
constexpr int OFF_SIDE = OFF_TAB2 + NOWN * 4;
constexpr int OFF_BAR = OFF_SIDE + 8;
constexpr int NBAR = 2 * NS + 32;
constexpr int SMEM_BYTES = OFF_BAR + NBAR * 8;
constexpr int SC_OP = OFF_RING + 4 * TILE_BYTES;
constexpr int SC_AB = SC_OP + 4096;
constexpr int SC_Y = SC_AB + 8192;
constexpr int SC_ST = SC_Y + 4096;
constexpr int SC_E4 = SC_ST + 256;
constexpr int SC_E6 = SC_E4 + 1024;
constexpr int SC_P = SC_E6 + 1024;
constexpr int SC_H1 = SC_P + 256;
static_assert(SMEM_BYTES <= 232448, "smem");
static_assert(OFF_BAR % 8 == 0 && OFF_X % 1024 == 0 && X_WQ % 512 == 0 && X_W1 % 512 == 0 && OFF_VA % 16 == 0 && OFF_RED % 16 == 0 && OFF_ML % 16 == 0 && OFF_O % 16 == 0 && OFF_Q % 16 == 0, "align");
constexpr int NB_O = 2  , NB_E4 = 10, NB_E6 = 11, NB_AB = 12, NB_Y = 13;

__device__ uint32_t g_mod[NMODC * 64];
__device__ uint32_t g_q[NCTA * 64];
__device__ uint32_t g_clr[NCTA];
__device__ uint32_t g_phase[16 * 32];
constexpr int SL_P1 = 0;
constexpr int SL_P2 = SL_P1 + NOWN;
constexpr int SL_O = SL_P2 + 2 * NOWN;
constexpr int SL_X1 = SL_O + 8;
constexpr int SL_SIDE = SL_X1 + 3;
static_assert(SL_SIDE < 256, "one 2 MB page");
__device__ uint32_t g_slots[2 * 256 * 2048];
__device__ __forceinline__ uint32_t* slot(int i, int side) {
    const size_t base = ((size_t)g_slots + 0x1fffff) & ~(size_t)0x1fffff;
    return (uint32_t*)base + i * 2048 + (((__popc(i & 0x59) ^ side) & 1) << 10);
}
#define PROF_DECL
#define HPROF(i) do { } while (0)
#define PROF(i) do { } while (0)
#define PROF_DUMP do { } while (0)

__device__ __forceinline__ uint32_t smem_u32(const void* p) { return (uint32_t)__cvta_generic_to_shared(p); }
__device__ __forceinline__ void mbar_init(uint32_t bar, uint32_t cnt) { asm volatile("mbarrier.init.shared::cta.b64 [%0], %1;" ::"r"(bar), "r"(cnt) : "memory"); }
__device__ __forceinline__ void mbar_expect_tx(uint32_t bar, uint32_t bytes) { asm volatile("mbarrier.arrive.expect_tx.shared::cta.b64 _, [%0], %1;" ::"r"(bar), "r"(bytes) : "memory"); }
__device__ __forceinline__ void mbar_arrive(uint32_t bar) { asm volatile("mbarrier.arrive.shared::cta.b64 _, [%0];" ::"r"(bar) : "memory"); }
__device__ __forceinline__ void mbar_wait(uint32_t bar, uint32_t parity) {
    uint32_t ok;
    int it = 0;
    while (true) {
        asm volatile("{\n.reg .pred p;\nmbarrier.try_wait.parity.shared::cta.b64 p, [%1], %2;\nselp.u32 %0, 1, 0, p;\n}" : "=r"(ok) : "r"(bar), "r"(parity) : "memory");
        if (ok) break;
        if (++it > SPIN_LIMIT) __trap();
    }
}
__device__ __forceinline__ void bulk_load(uint32_t dst, const void* src, uint32_t bytes, uint32_t bar, uint64_t pol) {
    asm volatile("cp.async.bulk.shared::cluster.global.mbarrier::complete_tx::bytes.L2::cache_hint [%0], [%1], %2, [%3], %4;"
                 ::"r"(dst), "l"(src), "r"(bytes), "r"(bar), "l"(pol) : "memory");
}
__device__ __forceinline__ void bar_cons() { asm volatile("bar.sync 1, 256;" ::: "memory"); }
template <int ID, int N> __device__ __forceinline__ void nbar_sync() { asm volatile("bar.sync %0, %1;" ::"n"(ID), "n"(N) : "memory"); }
template <int ID, int N> __device__ __forceinline__ void nbar_arrive() { asm volatile("bar.arrive %0, %1;" ::"n"(ID), "n"(N) : "memory"); }
__device__ __forceinline__ bool mbar_test(uint32_t bar, uint32_t parity) {
    uint32_t ok;
    asm volatile("{\n.reg .pred p;\nmbarrier.test_wait.parity.shared::cta.b64 p, [%1], %2;\nselp.u32 %0, 1, 0, p;\n}" : "=r"(ok) : "r"(bar), "r"(parity) : "memory");
    return ok;
}
__device__ __forceinline__ uint32_t pin(uint32_t v) { asm volatile("" : "+r"(v)); return v; }
template <class T> __device__ __forceinline__ T pin_hard(T v) { return __shfl_sync(0xffffffffu, v, threadIdx.x & 31); }
template <class T> __device__ __forceinline__ T* pin(T* v) { asm volatile("" : "+l"(v)); return v; }
__device__ __forceinline__ void ldsm4(uint32_t (&a)[4], uint32_t addr) {
    asm volatile("ldmatrix.sync.aligned.m8n8.x4.shared.b16 {%0,%1,%2,%3}, [%4];" : "=r"(a[0]), "=r"(a[1]), "=r"(a[2]), "=r"(a[3]) : "r"(addr) : "memory");
}
__device__ __forceinline__ void ldsm4t(uint32_t (&a)[4], uint32_t addr) {
    asm volatile("ldmatrix.sync.aligned.m8n8.x4.trans.shared.b16 {%0,%1,%2,%3}, [%4];" : "=r"(a[0]), "=r"(a[1]), "=r"(a[2]), "=r"(a[3]) : "r"(addr) : "memory");
}
__device__ __forceinline__ void mma16816(float (&c)[4], const uint32_t (&a)[4], uint32_t b0, uint32_t b1) {
    asm volatile("mma.sync.aligned.m16n8k16.row.col.f32.bf16.bf16.f32 {%0,%1,%2,%3}, {%4,%5,%6,%7}, {%8,%9}, {%0,%1,%2,%3};"
                 : "+f"(c[0]), "+f"(c[1]), "+f"(c[2]), "+f"(c[3]) : "r"(a[0]), "r"(a[1]), "r"(a[2]), "r"(a[3]), "r"(b0), "r"(b1));
}
__device__ __forceinline__ uint32_t lds32(uint32_t addr) { uint32_t v; asm volatile("ld.shared.u32 %0, [%1];" : "=r"(v) : "r"(addr) : "memory"); return v; }
__device__ __forceinline__ float lds_f32(uint32_t addr) { float v; asm volatile("ld.shared.f32 %0, [%1];" : "=f"(v) : "r"(addr) : "memory"); return v; }
__device__ __forceinline__ float2 lds_f32x2(uint32_t addr) { float2 v; asm volatile("ld.shared.v2.f32 {%0,%1}, [%2];" : "=f"(v.x), "=f"(v.y) : "r"(addr) : "memory"); return v; }
__device__ __forceinline__ float4 lds_f32x4(uint32_t addr) { float4 v; asm volatile("ld.shared.v4.f32 {%0,%1,%2,%3}, [%4];" : "=f"(v.x), "=f"(v.y), "=f"(v.z), "=f"(v.w) : "r"(addr) : "memory"); return v; }
__device__ __forceinline__ uint2 lds64(uint32_t addr) { uint2 v; asm volatile("ld.shared.v2.u32 {%0,%1}, [%2];" : "=r"(v.x), "=r"(v.y) : "r"(addr) : "memory"); return v; }
__device__ __forceinline__ uint4 lds128(uint32_t addr) { uint4 v; asm volatile("ld.shared.v4.u32 {%0,%1,%2,%3}, [%4];" : "=r"(v.x), "=r"(v.y), "=r"(v.z), "=r"(v.w) : "r"(addr) : "memory"); return v; }
__device__ __forceinline__ void sts16(uint32_t addr, uint32_t v) { asm volatile("st.shared.b16 [%0], %1;" ::"r"(addr), "h"((unsigned short)v) : "memory"); }
__device__ __forceinline__ void sts32(uint32_t addr, uint32_t v) { asm volatile("st.shared.u32 [%0], %1;" ::"r"(addr), "r"(v) : "memory"); }
__device__ __forceinline__ void sts_f32(uint32_t addr, float v) { asm volatile("st.shared.f32 [%0], %1;" ::"r"(addr), "f"(v) : "memory"); }
__device__ __forceinline__ void sts_f32x2(uint32_t addr, float a, float b) { asm volatile("st.shared.v2.f32 [%0], {%1,%2};" ::"r"(addr), "f"(a), "f"(b) : "memory"); }
__device__ __forceinline__ void sts128(uint32_t addr, uint4 v) { asm volatile("st.shared.v4.u32 [%0], {%1,%2,%3,%4};" ::"r"(addr), "r"(v.x), "r"(v.y), "r"(v.z), "r"(v.w) : "memory"); }
__device__ __forceinline__ uint4 ldg_relaxed(const uint32_t* p) {
    uint4 v;
    asm volatile("ld.relaxed.gpu.global.v4.u32 {%0,%1,%2,%3}, [%4];" : "=r"(v.x), "=r"(v.y), "=r"(v.z), "=r"(v.w) : "l"(p) : "memory");
    return v;
}
__device__ __forceinline__ void ldg_relaxed_if(bool on, uint4& v, const uint32_t* p) {
    asm volatile("{\n.reg .pred q;\nsetp.ne.u32 q, %5, 0;\n@q ld.relaxed.gpu.global.v4.u32 {%0,%1,%2,%3}, [%4];\n}"
                 : "+r"(v.x), "+r"(v.y), "+r"(v.z), "+r"(v.w) : "l"(p), "r"((uint32_t)on) : "memory");
}
__device__ __forceinline__ void stg_relaxed2_if(bool on, uint32_t* p, uint32_t a, uint32_t b) {
    asm volatile("{\n.reg .pred q;\nsetp.ne.u32 q, %3, 0;\n@q st.relaxed.gpu.global.v2.u32 [%0], {%1,%2};\n}" ::"l"(p), "r"(a), "r"(b), "r"((uint32_t)on) : "memory");
}
__device__ __forceinline__ uint32_t ldg_relaxed32(const uint32_t* p) { uint32_t v; asm volatile("ld.relaxed.gpu.global.u32 %0, [%1];" : "=r"(v) : "l"(p) : "memory"); return v; }
__device__ __forceinline__ void stg_relaxed(uint32_t* p, uint32_t v) { asm volatile("st.relaxed.gpu.global.u32 [%0], %1;" ::"l"(p), "r"(v) : "memory"); }
__device__ __forceinline__ void stg_zero4(uint32_t* p) { asm volatile("st.relaxed.gpu.global.v4.u32 [%0], {%1,%1,%1,%1};" ::"l"(p), "r"(0u) : "memory"); }
__device__ __forceinline__ bool ready(const uint4& v) { return (v.x != 0u) & (v.y != 0u) & (v.z != 0u) & (v.w != 0u); }
__device__ __forceinline__ uint4 inv4(const uint4& v) { return make_uint4(~v.x, ~v.y, ~v.z, ~v.w); }
__device__ __forceinline__ uint32_t pack_bf(float lo, float hi) {
    uint32_t r;
    asm("cvt.rn.bf16x2.f32 %0, %1, %2;" : "=r"(r) : "f"(hi), "f"(lo));
    return r;
}
__device__ __forceinline__ float bfr(float x) { return __uint_as_float(pack_bf(0.f, x) & 0xffff0000u); }
__device__ __forceinline__ float bf_lo(uint32_t w) { return __uint_as_float(w << 16); }
__device__ __forceinline__ float bf_hi(uint32_t w) { return __uint_as_float(w & 0xffff0000u); }
__device__ __forceinline__ float bf2f(__nv_bfloat16 v) { return __bfloat162float(v); }
__device__ __forceinline__ float ex2(float x) { float y; asm("ex2.approx.ftz.f32 %0, %1;" : "=f"(y) : "f"(x)); return y; }
__device__ __forceinline__ float rcp_fast(float x) { float y; asm("rcp.approx.ftz.f32 %0, %1;" : "=f"(y) : "f"(x)); return y; }
__device__ __forceinline__ float rsqrt_fast(float x) { float y; asm("rsqrt.approx.ftz.f32 %0, %1;" : "=f"(y) : "f"(x)); return y; }
__device__ __forceinline__ float sqrt_fast(float x) { float y; asm("sqrt.approx.f32 %0, %1;" : "=f"(y) : "f"(x)); return y; }
__device__ __forceinline__ uint32_t bf2_add(uint32_t a, uint32_t b) { uint32_t r; asm("add.rn.bf16x2 %0, %1, %2;" : "=r"(r) : "r"(a), "r"(b)); return r; }
__device__ __forceinline__ uint32_t bf2_sub(uint32_t a, uint32_t b) { uint32_t r; asm("sub.rn.bf16x2 %0, %1, %2;" : "=r"(r) : "r"(a), "r"(b)); return r; }
__device__ __forceinline__ uint32_t bf2_mul(uint32_t a, uint32_t b) { uint32_t r; asm("mul.rn.bf16x2 %0, %1, %2;" : "=r"(r) : "r"(a), "r"(b)); return r; }
__device__ __forceinline__ uint32_t gtime32() { uint32_t c; asm volatile("mov.u32 %0, %%globaltimer_lo;" : "=r"(c)); return c; }
__device__ __forceinline__ uint32_t clock32() { uint32_t c; asm volatile("mov.u32 %0, %%clock;" : "=r"(c)); return c; }

__device__ __forceinline__ float warp_sum(float v) {
#pragma unroll
    for (int o = 16; o > 0; o >>= 1) v += __shfl_xor_sync(0xffffffffu, v, o);
    return v;
}

struct Params {
    const __nv_bfloat16 *x, *kc, *vc, *b1, *b2, *c;
    __nv_bfloat16* out;
};

__device__ __forceinline__ void tma2d(uint32_t dst, const CUtensorMap* tm, int x, int y, uint32_t bar) {
    asm volatile("cp.async.bulk.tensor.2d.shared::cluster.global.mbarrier::complete_tx::bytes [%0], [%1, {%2, %3}], [%4];"
                 ::"r"(dst), "l"(tm), "r"(x), "r"(y), "r"(bar) : "memory");
}

__device__ __forceinline__ void tma2d_hint(uint32_t dst, const CUtensorMap* tm, int x, int y, uint32_t bar, uint64_t pol) {
    asm volatile("cp.async.bulk.tensor.2d.shared::cluster.global.mbarrier::complete_tx::bytes.L2::cache_hint [%0], [%1, {%2, %3}], [%4], %5;"
                 ::"r"(dst), "l"(tm), "r"(x), "r"(y), "r"(bar), "l"(pol) : "memory");
}
__device__ __forceinline__ uint32_t flag(float v) { return __float_as_uint(v) | 1u; }
__device__ __forceinline__ uint32_t and3(uint32_t a, uint32_t b, uint32_t c) { uint32_t r; asm("lop3.b32 %0, %1, %2, %3, 0x80;" : "=r"(r) : "r"(a), "r"(b), "r"(c)); return r; }
__device__ __forceinline__ uint32_t* slot_ptr(uint32_t lo) {
    uint32_t* r;
    asm volatile("mov.b64 %0, {%1, %2};" : "=l"(r) : "r"(lo), "r"((uint32_t)((size_t)slot(0, 0) >> 32)));
    return r;
}

__device__ __forceinline__ void load_bfrag(uint32_t vec, int stride, int k0, int g, int t, uint32_t& b0, uint32_t& b1) {
    uint32_t a = vec + (g & 3) * stride + (k0 + 2 * t) * 2;
    b0 = lds32(a);
    b1 = lds32(a + 16);
}

__device__ __forceinline__ void ln_finish(float pivot, float sum, float sumsq, uint32_t& m2, float& rden) {
    float dm = sum * (1.f / D);
    float var = fmaxf(sumsq * (1.f / D) - dm * dm, 0.f);
    float mean = pivot + dm;
    m2 = pack_bf(mean, mean);
    rden = rcp_fast(bfr(sqrt_fast(bfr(bfr(var) + 1e-5f))));
}
__device__ __forceinline__ uint32_t ln_mod_pair(uint32_t xw, uint32_t cw, uint32_t sw, uint32_t m2, float rden) {
    uint32_t d = bf2_sub(xw, m2);
    uint32_t ln = pack_bf(bf_lo(d) * rden, bf_hi(d) * rden);
    return bf2_add(bf2_mul(ln, bf2_add(cw, 0x3f803f80u)), sw);
}
__device__ __forceinline__ uint4 ln_mod4(const uint4& x, const uint4& c, const uint4& s, uint32_t m2, float rden) {
    return make_uint4(ln_mod_pair(x.x, c.x, s.x, m2, rden), ln_mod_pair(x.y, c.y, s.y, m2, rden),
                      ln_mod_pair(x.z, c.z, s.z, m2, rden), ln_mod_pair(x.w, c.w, s.w, m2, rden));
}
__device__ __forceinline__ void acc_stats(const uint4& v, float pv, float& s, float& q) {
    const float a0 = bf_lo(v.x) - pv, a1 = bf_hi(v.x) - pv, a2 = bf_lo(v.y) - pv, a3 = bf_hi(v.y) - pv;
    const float a4 = bf_lo(v.z) - pv, a5 = bf_hi(v.z) - pv, a6 = bf_lo(v.w) - pv, a7 = bf_hi(v.w) - pv;
    s += ((a0 + a1) + (a2 + a3)) + ((a4 + a5) + (a6 + a7));
    q += (fmaf(a0, a0, a1 * a1) + fmaf(a2, a2, a3 * a3)) + (fmaf(a4, a4, a5 * a5) + fmaf(a6, a6, a7 * a7));
}
__device__ __forceinline__ uint32_t* mod_slot(int kind, int j, int b) { return g_mod + (kind * 20 + (j >> 2)) * 64 + b * 16 + (j & 3) * 4; }

template <int N>
__device__ __forceinline__ void poll_n(uint4 (&v)[N], const uint32_t* const* ptr, const bool* on) {
    bool pend[N];
#pragma unroll
    for (int i = 0; i < N; i++) pend[i] = on[i];
    int it = 0;
    while (true) {
#pragma unroll
        for (int i = 0; i < N; i++) if (pend[i]) v[i] = ldg_relaxed(ptr[i]);
        bool any = false;
#pragma unroll
        for (int i = 0; i < N; i++) { pend[i] = pend[i] && !ready(v[i]); any |= pend[i]; }
        if (!__any_sync(0xffffffffu, any)) break;
        if (++it > SPIN_LIMIT) __trap();
    }
#pragma unroll
    for (int i = 0; i < N; i++) v[i] = inv4(v[i]);
}
__device__ __forceinline__ uint4 poll1(const uint32_t* p, bool on) {
    uint4 v[1] = {make_uint4(0, 0, 0, 0)};
    const uint32_t* const ptr[1] = {p};
    const bool o[1] = {on};
    poll_n<1>(v, ptr, o);
    return v[0];
}

__device__ __forceinline__ void gelu_stage(uint32_t sb, int m, int lane) {
    const int g = lane >> 2, b = lane & 3;
    const uint32_t y_ld = pin_hard(sb + SC_Y + m * 256 + lane * 8), s_ld = pin_hard(sb + SC_ST + b * 64);
    const uint32_t h_st = pin_hard(sb + SC_H1 + b * 64 + (g >> 1) * 16 + m * 8 + (g & 1) * 2);
    float a0 = 0.f, b0 = lds_f32(sb + OWN_B1 + (16 * m + g) * 4), a1 = 0.f, b1 = lds_f32(sb + OWN_B1 + (16 * m + g + 8) * 4);
    const float piv = bf_hi(lds32(sb + OFF_STAT + b * 8));
    nbar_sync<NB_AB, 320>();
#pragma unroll
    for (int w = 0; w < 8; w++) {
        const float4 t = lds_f32x4(sb + SC_AB + w * 1024 + m * 512 + lane * 16);
        a0 += t.x; b0 += t.y; a1 += t.z; b1 += t.w;
    }
    sts128(sb + SC_AB + m * 512 + lane * 16, make_uint4(__float_as_uint(a0), __float_as_uint(b0), __float_as_uint(a1), __float_as_uint(b1)));
    nbar_sync<NB_Y, 320>();
    float4 q[4];
    float2 y[8];
#pragma unroll
    for (int i = 0; i < 4; i++) q[i] = lds_f32x4(s_ld + i * 16);
#pragma unroll
    for (int w = 0; w < 8; w++) y[w] = lds_f32x2(y_ld + w * 512);
    const float dm = (((q[0].y + q[0].w) + (q[1].y + q[1].w)) + ((q[2].y + q[2].w) + (q[3].y + q[3].w))) * (1.f / D);
    const float sq = ((q[0].x + q[0].z) + (q[1].x + q[1].z)) + ((q[2].x + q[2].z) + (q[3].x + q[3].z));
    const float r = rsqrt_fast(fmaxf(fmaf(-dm, dm, fmaf(sq, 1.f / D, 1e-5f)), 1e-5f));
    const float y0 = ((y[0].x + y[1].x) + (y[2].x + y[3].x)) + ((y[4].x + y[5].x) + (y[6].x + y[7].x));
    const float y1 = ((y[0].y + y[1].y) + (y[2].y + y[3].y)) + ((y[4].y + y[5].y) + (y[6].y + y[7].y));
    const float dmr = piv - bfr(piv - dm);
    const float u0 = fmaf(r, fmaf(dmr, a0, -y0), b0), u1 = fmaf(r, fmaf(dmr, a1, -y1), b1);
    const float e0 = ex2(u0 * fmaf(u0 * u0, -0.044715f * 2.302208198144325f, -2.302208198144325f));
    const float e1 = ex2(u1 * fmaf(u1 * u1, -0.044715f * 2.302208198144325f, -2.302208198144325f));
    sts16(h_st, pack_bf(u0 * rcp_fast(1.f + e0), 0.f));
    sts16(h_st + 4, pack_bf(u1 * rcp_fast(1.f + e1), 0.f));
#pragma unroll
    for (int w = 0; w < 8; w++) asm volatile("bar.arrive %0, 96;" ::"r"(NB_O + w) : "memory");
}

struct Roles { bool is_f, is_owner; int f, own; };
__device__ __forceinline__ Roles roles(int cta) {
    Roles r;
    r.f = (cta * 27) >> 6;
    r.is_f = (((cta + 1) * 27) >> 6) != r.f;
    r.is_owner = !r.is_f || r.f % 9 == 4;
    r.own = r.is_f ? 74 + r.f / 9 : cta - r.f;
    return r;
}

__global__ void __launch_bounds__(NTHREADS, 1)
fused_kernel(const Params p, const __grid_constant__ CUtensorMap tm_wmod, const __grid_constant__ CUtensorMap tm_wq,
             const __grid_constant__ CUtensorMap tm_wo, const __grid_constant__ CUtensorMap tm_w1, const __grid_constant__ CUtensorMap tm_w2,
             const __grid_constant__ CUtensorMap tm_v, const __grid_constant__ CUtensorMap tm_gb) {
    extern __shared__ __align__(1024) unsigned char smem[];
    const uint32_t t_start = gtime32();
    const uint32_t sb = smem_u32(smem);
    const int cta = blockIdx.x;
    const int head = cta >> 2, bown = cta & 3;
    const int rot = (8 * head) & (NITEM / 2 - 1);
    const char* const kb = (const char*)(p.kc + ((size_t)(bown * NH + head) * SK + (SK - WIN)) * DH);
    uint64_t pol = 0;
    if (threadIdx.x == 256) {
        mbar_init(sb + OFF_BAR, 1);
        asm volatile("fence.mbarrier_init.release.cluster;" ::: "memory");
        asm volatile("createpolicy.fractional.L2::evict_first.b64 %0, 1.0;" : "=l"(pol));
        mbar_expect_tx(sb + OFF_BAR, TILE_BYTES);
        bulk_load(sb + OFF_RING, kb + (size_t)rot * TILE_BYTES, TILE_BYTES, sb + OFF_BAR, pol);
        if ((((cta + 1) * 5) >> 4) != ((cta * 5) >> 4)) {
            const uint32_t bar = sb + OFF_BAR + 2 * NS * 8;
            mbar_init(bar, 1);
            asm volatile("fence.mbarrier_init.release.cluster;" ::: "memory");
            mbar_expect_tx(bar, D * 64);
#pragma unroll 1
            for (int r = 0; r < D; r += 160) tma2d(sb + X_WM + r * 64, &tm_wmod, 32 * ((cta * 5) >> 4), r, bar);
        }
    }
    const uint32_t bar_full = sb + OFF_BAR, bar_empty = bar_full + NS * 8;
    const uint32_t bar_wm = bar_empty + NS * 8, bar_wq = bar_wm + 8, bar_xfree = bar_wq + 8, bar_wo = bar_xfree + 8  ;
    const uint32_t bar_w1 = bar_wo + 40  , bar_w2 = bar_w1 + 32  , bar_help = bar_w2 + 80, bar_v = bar_help + 8  ;
    const uint32_t bar_gb = bar_v + 32  , bar_x1 = bar_gb + 32;
    const int tid = threadIdx.x, warp = tid >> 5, lane = tid & 31;
    const Roles role = roles(cta);
    const bool is_f = role.is_f, is_owner = role.is_owner;
    const int f = role.f, own = role.own;
    const bool crit = (((cta + 1) * 5) >> 4) != ((cta * 5) >> 4);
    const int mr = cta - ((cta * 5) >> 4);
    const int ml = mr * 31 / 44;
    const bool late = !crit && (mr + 1) * 31 / 44 != ml;
    const int mc = crit ? (cta * 5) >> 4 : ml < 60 ? 40 + ml : 58 + ml;
    const bool gb_own = is_owner && own < 72;

    PROF_DECL
    PROF(0);
    uint4 xa = make_uint4(0, 0, 0, 0), xb = xa, ca0 = xa, ca1 = xa, xs[3] = {xa, xa, xa};
    uint32_t own0 = 0;
    __nv_bfloat16 own2 = __float2bfloat16(0.f);
    if (warp < 8) {
        xa = *(const uint4*)(p.x + (tid & 3) * D + (tid >> 2) * 8);
        ca0 = ((const uint4*)p.c)[tid];
        if (tid < 64) { xb = *(const uint4*)(p.x + (tid & 3) * D + (64 + (tid >> 2)) * 8); ca1 = ((const uint4*)p.c)[256 + tid]; }
        if (warp < 4) {
#pragma unroll
            for (int i = 0; i < 3; i++) if (lane + 32 * i < 80) xs[i] = ((const uint4*)p.x)[warp * 80 + lane + 32 * i];
        } else if (warp == 4) {
            if (is_owner) own0 = *(const uint32_t*)((lane < 16 ? p.x + (lane >> 2) * D : p.b2) + 8 * own + 2 * (lane & 3));
            if (is_f) own2 = p.b1[32 * f + lane];
        }
    }
    const char* const vb = (const char*)(p.vc + ((size_t)(bown * NH + head) * SK + (SK - WIN)) * DH);
    const uint32_t bar_first = crit ? bar_wm : bar_wq;
    if (threadIdx.x == 256) {
        if (!crit) {
            mbar_init(bar_wq, 1);
            asm volatile("fence.mbarrier_init.release.cluster;" ::: "memory");
            mbar_expect_tx(bar_wq, D * 64);
            const uint32_t c0 = clock32();
            while (clock32() - c0 < WQ_DELAY) { }
#pragma unroll
            for (int r = 0; r < D; r += 160) tma2d(sb + X_WQ + r * 64, &tm_wq, 32 * cta, r, bar_wq);
        }
    } else if (threadIdx.x == 0) {
#pragma unroll
        for (int s = 0; s < NS; s++) { if (s) mbar_init(bar_full + s * 8, 1); mbar_init(bar_empty + s * 8, 4); }
        mbar_init(crit ? bar_wq : bar_wm, 1);
        mbar_init(bar_xfree, 1);
#pragma unroll
        for (int i = 0; i < 5; i++) { mbar_init(bar_wo + i * 8, 1); mbar_init(bar_w2 + i * 16, 1); mbar_init(bar_w2 + i * 16 + 8, 1); }
        mbar_init(bar_help, 1); mbar_init(bar_x1, 1);
#pragma unroll
        for (int i = 0; i < 4; i++) { mbar_init(bar_v + i * 8, 1); mbar_init(bar_w1 + i * 8, 1); mbar_init(bar_gb + i * 8, 1); }
        asm volatile("fence.mbarrier_init.release.cluster;" ::: "memory");
    }
    __syncthreads();

    if (warp == 8) {
        if (lane == 0) {
            int tp = NS;
            int sched = PACE_A - NS * PACE_TAU;
#pragma unroll 1
            for (int t = 1; t <= NITEM; t++) {
                if (t == 1) mbar_wait(bar_full, 0);
                if (t == 2) {
                    mbar_wait(bar_first, 0);
                    if (crit) {
                        mbar_expect_tx(bar_wq, D * 64);
#pragma unroll 1
                        for (int r = 0; r < D; r += 160) tma2d(sb + X_WQ + r * 64, &tm_wq, 32 * cta, r, bar_wq);
                    }
                }
                if (t == 3) {
                    asm volatile("prefetch.tensormap [%0];" ::"l"(&tm_v) : "memory");
                    asm volatile("prefetch.tensormap [%0];" ::"l"(&tm_wo) : "memory");
                    asm volatile("prefetch.tensormap [%0];" ::"l"(&tm_w1) : "memory");
                    asm volatile("prefetch.tensormap [%0];" ::"l"(&tm_w2) : "memory");
                    asm volatile("prefetch.tensormap [%0];" ::"l"(&tm_gb) : "memory");
                }
                if (t == NS && late) {
                    mbar_wait(bar_full + (NS - INFLIGHT) * 8, 0);
                    mbar_expect_tx(bar_wm, D * 64);
#pragma unroll 1
                    for (int r = 0; r < D; r += 160) tma2d(sb + X_WM + r * 64, &tm_wmod, 32 * mc, r, bar_wm);
                }
                if (t >= NS && t < PF_END) {
                    int it = 0;
                    while (!mbar_test(bar_empty + (t & (NS - 1)) * 8, ((t >> 3) - 1) & 1)) {
                        if (tp < PF_END && (int)(gtime32() - t_start) >= PACE_A + (tp - NS) * PACE_TAU) {
                            asm volatile("cp.async.bulk.prefetch.L2.global.L2::cache_hint [%0], %1, %2;"
                                         ::"l"(((tp & 1) ? vb : kb) + (size_t)(((tp >> 1) + rot) & (NITEM / 2 - 1)) * TILE_BYTES), "r"(TILE_BYTES), "l"(pol) : "memory");
                            tp++;
                        }
                        if (++it > 16 * SPIN_LIMIT) __trap();
                    }
                    if (tp <= t) tp = t + 1;
                }
                if (t == NITEM) {
                    mbar_wait(bar_xfree, 0);
                    const uint32_t t_ref = t_start + sched + LAT_T + (NITEM - 1) * PACE_TAU;
#pragma unroll 1
                    for (int i = 0; i < 5; i++) {
                        while ((int)(gtime32() - t_ref) < WO_T + i * WO_S) { }
                        mbar_expect_tx(bar_wo + i * 8, DH * 64);
                        tma2d(sb + X_WO + i * (DH * 64), &tm_wo, bown * 160 + i * 32, head * DH, bar_wo + i * 8);
                    }
                    if (gb_own) {
                        mbar_wait(bar_empty + 3 * 8, ((NITEM >> 3) - 1) & 1);
                        mbar_wait(bar_x1, 0);
                        { const uint32_t c0 = clock32(); while (clock32() - c0 < GB_EV) { } }
                        while ((int)(gtime32() - t_ref) < GB_T) { }
#pragma unroll 1
                        for (int i = 0; i < 4; i++) {
                            mbar_expect_tx(bar_gb + i * 8, 160 * 16);
                            tma2d(sb + X_GB + i * (160 * 16), &tm_gb, 5 * D + 8 * own, 160 * i, bar_gb + i * 8);
                        }
                    }
                    if (is_f) {
#pragma unroll 1
                        for (int i = 0; i < 3; i++) mbar_wait(bar_empty + i * 8, ((NITEM >> 3) - 1) & 1);
                        while ((int)(gtime32() - t_ref) < W1_T) { }
#pragma unroll 1
                        for (int i = 0; i < 4; i++) {
                            mbar_expect_tx(bar_w1 + i * 8, 160 * 64);
                            tma2d(sb + X_W1 + i * (160 * 64), &tm_w1, 32 * f, 160 * i, bar_w1 + i * 8);
                        }
                        while ((int)(gtime32() - t_ref) < W2_T) { }
#pragma unroll 1
                        for (int i = 0; i < 10; i++) {
                            mbar_expect_tx(bar_w2 + i * 8, 4096);
                            tma2d(sb + X_W2 + i * 4096, &tm_w2, 64 * i, 32 * f, bar_w2 + i * 8);
                        }
                    }
                    break;
                }
                const int s = t & (NS - 1);
                if (t >= NS) {
                    mbar_wait(bar_empty + s * 8, ((t >> 3) - 1) & 1);
                    while ((int)(gtime32() - t_start) < sched + t * PACE_TAU) { }
                } else if (t >= INFLIGHT) {
                    mbar_wait(bar_full + (t - INFLIGHT) * 8, 0);
                }
                if (t < NITEM - 2) {
                    const int pair = t == NITEM - 3 ? NITEM / 2 - 1 : t >> 1;
                    mbar_expect_tx(bar_full + s * 8, TILE_BYTES);
                    bulk_load(sb + OFF_RING + s * TILE_BYTES, ((t & 1) && t != NITEM - 3 ? vb : kb) + (size_t)((pair + rot) & (NITEM / 2 - 1)) * TILE_BYTES, TILE_BYTES, bar_full + s * 8, pol);
                } else {
                    const int row = (bown * NH + head) * SK + (SK - WIN) + ((t - NITEM / 2 + rot) & (NITEM / 2 - 1)) * TILE_KEYS;
#pragma unroll 1
                    for (int i = 0; i < 2; i++) {
                        const uint32_t bar = bar_v + (2 * (t - (NITEM - 2)) + i) * 8;
                        mbar_expect_tx(bar, TILE_BYTES / 2);
                        tma2d_hint(sb + OFF_RING + s * TILE_BYTES + i * (TILE_BYTES / 2), &tm_v, 64 * i, row, bar, pol);
                    }
                }
                if (t >= PH_FIRST + PH_LAG && (t & 3) == (PH_LAG & 3)) {
                    const int now = (int)(gtime32() - t_start) - (t - PH_LAG) * PACE_TAU;
                    uint32_t ph;
                    asm volatile("atom.relaxed.gpu.global.add.u32 %0, [%1], 0;" : "=r"(ph) : "l"(g_phase + ((t - PH_LAG) >> 2) * 32) : "memory");
                    sched = (int)min(((ph & 0xffffffu) * 4 + (NCTA - (ph >> 24)) * now) >> 7, 65535u) - LAT_T;
                }
            }
        }
        __syncwarp();
    }

    if (warp == 9) {
        int side = 0;
        if (lane == 0) {
            uint32_t best[2] = {~0u, ~0u};
#pragma unroll 1
            for (int i = 0; i < 2 * NPROBE && ((i & 1) || (int)(gtime32() - t_start) < PROBE_END); i++) {
                uint32_t t0 = clock32(), v, t1;
                asm volatile("atom.relaxed.gpu.global.exch.b32 %0, [%1], %2;" : "=r"(v) : "l"(slot(SL_SIDE, i & 1) + cta * 8), "r"(0u) : "memory");
                asm volatile("{\n.reg .pred p;\nsetp.ne.u32 p, %1, 0xffffffff;\nmov.u32 %0, 0;\n@p mov.u32 %0, %%clock;\n}" : "=r"(t1) : "r"(v) : "memory");
                if (i & 1) best[1] = min(best[1], t1 - t0); else best[0] = min(best[0], t1 - t0);
            }
            side = best[1] < best[0];
        }
        side = __shfl_sync(0xffffffffu, side, 0);
        HPROF(1);
        mbar_wait(bar_full + (NS - 1) * 8, 0);
        stg_zero4(slot(SL_O + (cta >> 4), lane >> 4) + (cta & 15) * 64 + (lane & 15) * 4);
        if (is_owner) {
#pragma unroll 1
            for (int i = lane; i < NH * 8; i += 32) stg_zero4(slot(SL_P1 + own, side) + i * 4);
#pragma unroll 1
            for (int i = lane; i < NF * 8; i += 32) stg_zero4(slot(SL_P2 + 2 * own + (i >> 8), side) + (i & 255) * 4);
            if (lane < 8) stg_zero4(slot(SL_X1 + own / 30, lane >> 2) + (own % 30) * 32 + (lane & 3) * 4);
        }
        __threadfence();
        __syncwarp();
        if (lane == 0) stg_relaxed(g_clr + cta, 1u + side);
        HPROF(0);
        HPROF(2);
        while ((int)(gtime32() - t_start) < CLR_CHECK) __nanosleep(1000);
        mbar_wait(bar_xfree, 0);
        {
            uint4 v = make_uint4(1, 1, 1, 1), gv = v, mv[20];
#pragma unroll
            for (int i = 0; i < 20; i++) mv[i] = v;
#pragma unroll 1
            for (int it = 0;; it++) {
                v = ldg_relaxed(g_clr + lane * 4);

                ldg_relaxed_if(is_owner && lane < (gb_own ? 4 : 8), gv, mod_slot(lane < 4 ? 2 : 5, own, lane & 3));
#pragma unroll
                for (int i = 0; i < 20; i++) ldg_relaxed_if(is_f, mv[i], mod_slot(3, 8 * i + (lane >> 2), lane & 3));
                bool ok = ready(v) && ready(gv);
#pragma unroll
                for (int i = 0; i < 20; i++) ok = ok && ready(mv[i]);
                if (__all_sync(0xffffffffu, ok)) break;
                if (it > SPIN_LIMIT) __trap();
                __nanosleep(2000);
            }
            const uint32_t w[4] = {v.x, v.y, v.z, v.w};
#pragma unroll
            for (int i = 0; i < 4; i++) {
                const Roles r = roles(4 * lane + i);
                if (r.is_owner) {
                    sts32(sb + OFF_TAB1 + r.own * 4, (uint32_t)(size_t)(slot(SL_P1 + r.own, w[i] - 1) + head * 32));
                    sts32(sb + OFF_TAB2 + r.own * 4, (uint32_t)(size_t)(slot(SL_P2 + 2 * r.own + (f >> 5), w[i] - 1) + (f & 31) * 32));
                }
            }
            if (lane == 0) sts32(sb + OFF_SIDE, side);
            if (lane < 8) sts128(sb + OWN_GA + lane * 16, inv4(gv));
            const uint32_t dst = sb + OFF_VB + (lane & 3) * VEC_STRIDE + (lane >> 2) * 16;
#pragma unroll
            for (int i = 0; i < 10; i++) {
                const uint4 c = inv4(mv[10 + i]);
                sts128(dst + i * 128, make_uint4(bf2_add(c.x, 0x3f803f80u), bf2_add(c.y, 0x3f803f80u), bf2_add(c.z, 0x3f803f80u), bf2_add(c.w, 0x3f803f80u)));
                sts128(dst + (OFF_RED - OFF_VB) + i * 128, inv4(mv[i]));
            }
        }
        asm volatile("fence.acq_rel.gpu;" ::: "memory");
        __syncwarp();
        HPROF(3);
        if (lane == 0) mbar_arrive(bar_help);
        {
            const uint32_t* const src = pin(slot(SL_O + (cta >> 4), side) + (cta & 12) * 64 + lane * 4);
            const uint32_t dst = pin(sb + OFF_O + (lane >> 4) * O_STRIDE + (lane & 15) * 16);
            mbar_wait(bar_v + 16, 0);
            mbar_wait(bar_v + 24, 0);
            uint4 v[2];
            const uint32_t* const ptr[2] = {src, src + 128};
            const bool on[2] = {true, true};
            poll_n<2>(v, ptr, on);
            sts128(dst, v[0]);
            sts128(dst + 2 * O_STRIDE, v[1]);
#pragma unroll
            for (int w = 0; w < 8; w++) asm volatile("bar.arrive %0, 64;" ::"r"(NB_O + w) : "memory");
        }
        HPROF(4);
    }
    if (warp >= 8) {
        if (gb_own && warp == 9) {
            uint32_t a[20][4];
#pragma unroll
            for (int i = 0; i < 20; i++) ldsm4(a[i], sb + OFF_VA + (lane & 3) * VEC_STRIDE + (4 * i + (lane >> 3)) * 16);
            float c[4][4];
#pragma unroll
            for (int i = 0; i < 4; i++) c[i][0] = c[i][1] = c[i][2] = c[i][3] = 0.f;
#pragma unroll
            for (int bx = 0; bx < 4; bx++) {
                mbar_wait(bar_gb + bx * 8, 0);
#pragma unroll
                for (int i = 5 * bx; i < 5 * bx + 5; i++) {
                    uint32_t w[4];
                    ldsm4t(w, sb + X_GB + (32 * i + lane) * 16);
                    const uint32_t a0[4] = {a[i][0], 0u, a[i][1], 0u}, a1[4] = {a[i][2], 0u, a[i][3], 0u};
                    mma16816(c[(2 * i) & 3], a0, w[0], w[1]);
                    mma16816(c[(2 * i + 1) & 3], a1, w[2], w[3]);
                }
            }
            if (lane < 16) sts32(sb + OWN_GB + lane * 4, pack_bf((c[0][0] + c[1][0]) + (c[2][0] + c[3][0]), (c[0][1] + c[1][1]) + (c[2][1] + c[3][1])));
            HPROF(6);
        }
        if (is_owner && warp == 9) nbar_arrive<NB_E6, 288>();
        if (is_f) gelu_stage(sb, warp - 8, lane);
        return;
    }

    const int g = lane >> 2, t4 = lane & 3;
    const int mi = lane >> 3, r8 = lane & 7;

    {
        auto silu4 = [&](const uint4& cv) {
            uint32_t w4[4] = {cv.x, cv.y, cv.z, cv.w};
#pragma unroll
            for (int e = 0; e < 4; e++) {
                float c0 = bf_lo(w4[e]), c1 = bf_hi(w4[e]);
                w4[e] = pack_bf(c0 * rcp_fast(1.f + ex2(-1.4426950408889634f * c0)), c1 * rcp_fast(1.f + ex2(-1.4426950408889634f * c1)));
            }
            return make_uint4(w4[0], w4[1], w4[2], w4[3]);
        };
        {
            uint4 v = silu4(ca0);
            sts128(sb + OFF_VA + (tid / 80) * VEC_STRIDE + (tid % 80) * 16, v);
            if (tid < 64) { v = silu4(ca1); sts128(sb + OFF_VA + 3 * VEC_STRIDE + (16 + tid) * 16, v); }
        }
        if (warp < 4) {
            float s = 0.f, q = 0.f;
            const float pv = __shfl_sync(0xffffffffu, bf_lo(xs[0].x), 0);
#pragma unroll
            for (int i = 0; i < 3; i++) if (i < 2 || lane < 16) acc_stats(xs[i], pv, s, q);
#pragma unroll
            for (int of = 16; of > 0; of >>= 1) { s += __shfl_xor_sync(0xffffffffu, s, of); q += __shfl_xor_sync(0xffffffffu, q, of); }
            uint32_t m2; float rden;
            ln_finish(pv, s, q, m2, rden);
            if (lane == 0) { sts32(sb + OFF_STAT + warp * 8, m2); sts_f32(sb + OFF_STAT + warp * 8 + 4, rden); }
        } else if (warp == 4) {
            sts32(sb + OWN_X + lane * 4, bf2_add(own0, 0u));
            sts_f32(sb + OWN_B1 + lane * 4, bf2f(own2));
        }
    }
    bar_cons();
    PROF(24);
    uint32_t qf[8][2];
    float o[8][4];
#pragma unroll
    for (int c = 0; c < 8; c++) { o[c][0] = o[c][1] = o[c][2] = o[c][3] = 0.f; }
    float m_run = -INFINITY, l_run = 0.f;
    const bool diag = (t4 == (g >> 1));
    const bool odd = g & 1;
    const uint32_t koff = (warp & 3) * 4096 + (r8 + 8 * (mi & 1)) * 256 + (mi >> 1) * 128 + (r8 << 4);
    const uint32_t voff = TILE_BYTES + (warp & 3) * 4096 + (r8 + 8 * (mi >> 1)) * 256 + (mi & 1) * 128 + (r8 << 4);
    const int src0 = (2 * t4) * 4 + t4, src1 = (2 * t4 + 1) * 4 + t4;
#pragma unroll 1
    for (int step = crit ? 0 : 1; step < 3; step++) {
        if (step < 2 || late) {
            if (step == 1) {
                if (!crit) mbar_wait(bar_wq, 0);
                const uint32_t m2 = lds32(sb + OFF_STAT + (tid & 3) * 8);
                const float rden = lds_f32(sb + OFF_STAT + (tid & 3) * 8 + 4);
                uint4 v[4] = {xa, xa, xa, xa};
                const uint32_t* const ptr[4] = {mod_slot(0, tid >> 2, tid & 3), mod_slot(1, tid >> 2, tid & 3),
                                                mod_slot(0, 64 + ((tid & 63) >> 2), tid & 3), mod_slot(1, 64 + ((tid & 63) >> 2), tid & 3)};
                const bool on[4] = {true, true, tid < 64, tid < 64};
                poll_n<4>(v, ptr, on);
                uint4 h0 = ln_mod4(xa, v[1], v[0], m2, rden);
                sts128(sb + OFF_VB + (tid & 3) * VEC_STRIDE + (tid >> 2) * 16, h0);
                if (tid < 64) {
                    h0 = ln_mod4(xb, v[3], v[2], m2, rden);
                    sts128(sb + OFF_VB + (tid & 3) * VEC_STRIDE + (64 + (tid >> 2)) * 16, h0);
                }
            }
            mbar_wait(step == 1 ? bar_wq : bar_wm, 0);
            bar_cons();
            const uint32_t strip = sb + (step == 1 ? X_WQ : X_WM), vec = sb + (step == 1 ? OFF_VB : OFF_VA);
            float acc[2][4];
#pragma unroll
            for (int m = 0; m < 2; m++) { acc[m][0] = acc[m][1] = acc[m][2] = acc[m][3] = 0.f; }
#pragma unroll
            for (int i = 0; i < 5; i++) {
                int k0 = (warp * 5 + i) * 16;
                uint32_t b0, b1;
                load_bfrag(vec, VEC_STRIDE, k0, g, t4, b0, b1);
                int krow = k0 + r8 + 8 * (mi >> 1);
#pragma unroll
                for (int m = 0; m < 2; m++) {
                    uint32_t a[4];
                    int ch = 2 * m + (mi & 1);
                    ldsm4t(a, strip + krow * 64 + ((ch ^ ((krow >> 1) & 3)) << 4));
                    mma16816(acc[m], a, b0, b1);
                }
            }
            if (t4 < 2) {
#pragma unroll
                for (int m = 0; m < 2; m++) {
                    sts_f32x2(sb + OFF_RED + ((warp * 32 + m * 16 + g) * 4 + 2 * t4) * 4, acc[m][0], acc[m][1]);
                    sts_f32x2(sb + OFF_RED + ((warp * 32 + m * 16 + g + 8) * 4 + 2 * t4) * 4, acc[m][2], acc[m][3]);
                }
            }
            bar_cons();
            if (tid < 128) {
                float v = 0.f;
#pragma unroll
                for (int w = 0; w < 8; w++) v += lds_f32(sb + OFF_RED + (w * 128 + tid) * 4);
                float vn = __shfl_down_sync(0xffffffffu, v, 4);
                uint32_t* dst = step == 1 ? g_q + ((cta & ~3) + (tid & 3)) * 64 + bown * 16 + (tid >> 3) : g_mod + mc * 64 + (tid & 3) * 16 + (tid >> 3);
                if (!((tid >> 2) & 1)) stg_relaxed(dst, ~pack_bf(v, vn));
            }
        }
        if (step == 0) continue;
        if (step == 1) {
            if (warp == 0) {
                uint4 v = poll1(g_q + cta * 64 + (lane & 15) * 4, lane < 16);
                if (lane < 16) {
                    sts128(sb + OFF_Q + lane * 16, v);
                    stg_zero4(g_q + cta * 64 + lane * 4);
                }
            }
            bar_cons();
            PROF(4);

#pragma unroll
            for (int c = 0; c < 8; c++) {
                qf[c][0] = lds32(sb + OFF_Q + (((c ^ g) * 4 + t4) << 2));
                qf[c][1] = lds32(sb + OFF_Q + 128 + (((c ^ g) * 4 + t4) << 2));
            }
        } else {
            bar_cons();
            if (tid == 0) mbar_arrive(bar_xfree);
        }
#pragma unroll 1
        for (int j = (step == 1 ? 0 : SEG_J) + (warp >> 2); j < (step == 1 ? SEG_J : NITEM / 2 - 2); j += 2) {
            const int s = (2 * j) & (NS - 1);
            const uint32_t par = (j >> 2) & 1;
            mbar_wait(bar_full + s * 8, par);
            if (tid == 0 && 2 * j >= PH_FIRST) {
                const int x = min(max((int)(gtime32() - t_start) - 2 * j * PACE_TAU, 0), 65535);
                asm volatile("red.relaxed.gpu.global.add.u32 [%0], %1;" ::"l"(g_phase + (j >> 1) * 32), "r"((1u << 24) + (x >> 2)) : "memory");
            }
            const uint32_t base = sb + OFF_RING + s * TILE_BYTES;
            float sa[4] = {0.f, 0.f, 0.f, 0.f}, sb2[4] = {0.f, 0.f, 0.f, 0.f};
#pragma unroll
            for (int c = 0; c < 8; c += 2) {
                uint32_t a[4], a2[4];
                ldsm4(a, (base + koff) ^ (c << 4));
                ldsm4(a2, (base + koff) ^ ((c + 1) << 4));
                mma16816(sa, a, qf[c][0], qf[c][1]);
                mma16816(sb2, a2, qf[c + 1][0], qf[c + 1][1]);
            }
            const uint32_t sw = pack_bf(odd ? sa[1] + sb2[1] : sa[0] + sb2[0], odd ? sa[3] + sb2[3] : sa[2] + sb2[2]);
            const uint32_t sv = pack_bf(bf_lo(sw) * 0.08838834764831845f, bf_hi(sw) * 0.08838834764831845f);
            const float s0 = bf_lo(sv) * 1.4426950408889634f, s1 = bf_hi(sv) * 1.4426950408889634f;
            float m_new = fmaxf(m_run, fmaxf(s0, s1));
            const bool grow = __any_sync(0xffffffffu, (diag && (m_new > m_run)));
            if (lane == 0) mbar_arrive(bar_empty + s * 8);
            if (grow) {
                float al = ex2(m_run - m_new);
                float a0 = __shfl_sync(0xffffffffu, al, src0), a1 = __shfl_sync(0xffffffffu, al, src1);
#pragma unroll
                for (int c = 0; c < 8; c++) { o[c][0] *= a0; o[c][1] *= a1; o[c][2] *= a0; o[c][3] *= a1; }
                l_run *= al;
                m_run = m_new;
            }
            uint32_t pw = pack_bf(ex2(s0 - m_run), ex2(s1 - m_run));
            l_run += bf_lo(pw) + bf_hi(pw);
            uint32_t b0 = odd ? (pw << 16) : (pw & 0xffffu);
            uint32_t b1 = odd ? (pw & 0xffff0000u) : (pw >> 16);
            if (!diag) { b0 = 0u; b1 = 0u; }
            mbar_wait(bar_full + (s + 1) * 8, par);
#pragma unroll
            for (int c = 0; c < 8; c++) {
                uint32_t a[4];
                ldsm4t(a, (base + voff) ^ (c << 4));
                mma16816(o[c], a, b0, b1);
            }
            __syncwarp();
            if (lane == 0) mbar_arrive(bar_empty + (s + 1) * 8);
        }
    }
    PROF(5);
    float acc[4][4];
    uint32_t pa[8][2];
    float rinv;
    {
        const int s = 4 + (warp >> 2);
        mbar_wait(bar_full + s * 8, 1);
        const uint32_t base = sb + OFF_RING + s * TILE_BYTES;
        float sa[4] = {0.f, 0.f, 0.f, 0.f}, sb2[4] = {0.f, 0.f, 0.f, 0.f};
#pragma unroll
        for (int c = 0; c < 8; c += 2) {
            uint32_t a[4], a2[4];
            ldsm4(a, (base + koff) ^ (c << 4));
            ldsm4(a2, (base + koff) ^ ((c + 1) << 4));
            mma16816(sa, a, qf[c][0], qf[c][1]);
            mma16816(sb2, a2, qf[c + 1][0], qf[c + 1][1]);
        }
        const uint32_t sw = pack_bf(odd ? sa[1] + sb2[1] : sa[0] + sb2[0], odd ? sa[3] + sb2[3] : sa[2] + sb2[2]);
        const uint32_t sv = pack_bf(bf_lo(sw) * 0.08838834764831845f, bf_hi(sw) * 0.08838834764831845f);
        const float s0 = bf_lo(sv) * 1.4426950408889634f, s1 = bf_hi(sv) * 1.4426950408889634f;
        int mi_ = __float_as_int(diag ? fmaxf(m_run, fmaxf(s0, s1)) : -INFINITY);
        mi_ ^= (mi_ >> 31) & 0x7fffffff;
        mi_ = __reduce_max_sync(0xffffffffu, mi_);
        mi_ ^= (mi_ >> 31) & 0x7fffffff;
        if (lane == 0) sts32(sb + OFF_ML + warp * 4, mi_);
        bar_cons();
        const float4 m0 = lds_f32x4(sb + OFF_ML), m1 = lds_f32x4(sb + OFF_ML + 16);
        const float mx = fmaxf(fmaxf(fmaxf(m0.x, m0.y), fmaxf(m0.z, m0.w)), fmaxf(fmaxf(m1.x, m1.y), fmaxf(m1.z, m1.w)));
        const float scl = ex2(m_run - mx);
        const uint32_t pw = pack_bf(ex2(s0 - mx), ex2(s1 - mx));
        if (diag) { sts16(sb + SC_P + (warp * 16 + g) * 2, pw); sts16(sb + SC_P + (warp * 16 + g + 8) * 2, pw >> 16); }
        const float lw = warp_sum(diag ? fmaf(l_run, scl, bf_lo(pw) + bf_hi(pw)) : 0.f);
        const float a0 = __shfl_sync(0xffffffffu, scl, src0), a1 = __shfl_sync(0xffffffffu, scl, src1);
        float v[8], u[8];
#pragma unroll
        for (int c = 0; c < 8; c++) {
            v[c] = a0 * o[c][0] + a1 * o[c ^ 1][1];
            u[c] = a0 * o[c][2] + a1 * o[c ^ 1][3];
        }
#pragma unroll
        for (int c = 0; c < 8; c++) {
            if (!(c & 2)) {
                v[c] += __shfl_xor_sync(0xffffffffu, v[c ^ 2], 1);
                u[c] += __shfl_xor_sync(0xffffffffu, u[c ^ 2], 1);
            }
        }
#pragma unroll
        for (int c = 0; c < 2; c++) {
            v[c] += __shfl_xor_sync(0xffffffffu, v[c ^ 4], 2);
            u[c] += __shfl_xor_sync(0xffffffffu, u[c ^ 4], 2);
        }
        const uint32_t dst = sb + SC_OP + (warp * 128 + 16 * t4 + g) * 4;
        sts_f32(dst, v[0]); sts_f32(dst + 32, v[1]); sts_f32(dst + 256, u[0]); sts_f32(dst + 288, u[1]);
        if (lane == 0) sts_f32(sb + OFF_ML + 32 + warp * 4, lw);
        mbar_wait(bar_help, 0);
        bar_cons();
        const float4 l0 = lds_f32x4(sb + OFF_ML + 32), l1 = lds_f32x4(sb + OFF_ML + 48);
        rinv = rcp_fast(((l0.x + l0.y) + (l0.z + l0.w)) + ((l1.x + l1.y) + (l1.z + l1.w)));
#pragma unroll
        for (int i = 0; i < 4; i++) acc[i][0] = acc[i][1] = acc[i][2] = acc[i][3] = 0.f;
#pragma unroll
        for (int w = 0; w < 8; w++) {
            const float2 x0 = lds_f32x2(sb + SC_OP + (w * 128 + 16 * warp + 2 * t4) * 4), x1 = lds_f32x2(sb + SC_OP + (w * 128 + 16 * warp + 8 + 2 * t4) * 4);
            acc[2 * (w & 1)][0] += x0.x; acc[2 * (w & 1)][1] += x0.y;
            acc[2 * (w & 1) + 1][0] += x1.x; acc[2 * (w & 1) + 1][1] += x1.y;
        }
#pragma unroll
        for (int ks = 0; ks < 8; ks++) { pa[ks][0] = lds32(sb + SC_P + (8 * ks + t4) * 4); pa[ks][1] = lds32(sb + SC_P + (8 * ks + 4 + t4) * 4); }
    }
    PROF(20);
    const int mt = warp < 2 ? warp : warp + 2;
    {
        const uint32_t va = pin(sb + OFF_RING + 6 * TILE_BYTES + (warp >> 2) * (TILE_BYTES / 2) + (8 * (mi & 1) + r8) * 128 + (((2 * (warp & 3) + (mi >> 1)) ^ r8) << 4));
        const uint32_t vbar = pin(bar_v + (warp >> 2) * 8);
        uint32_t* const o_dst = pin(slot(SL_O + (cta >> 4), g) + (cta & 15) * 64 + warp * 8 + 2 * t4);
#pragma unroll
        for (int tl = 0; tl < 2; tl++) {
            mbar_wait(vbar + tl * 16, 0);
            uint32_t r[4][4];
#pragma unroll
            for (int ks = 0; ks < 4; ks++) ldsm4t(r[ks], va + tl * TILE_BYTES + ks * 2048);
#pragma unroll
            for (int ks = 0; ks < 4; ks++) {
                const uint32_t a[4] = {pa[4 * tl + ks][0], 0u, pa[4 * tl + ks][1], 0u};
                mma16816(acc[2 * (ks & 1)], a, r[ks][0], r[ks][1]);
                mma16816(acc[2 * (ks & 1) + 1], a, r[ks][2], r[ks][3]);
            }
        }
        stg_relaxed2_if(g < 2, o_dst, ~pack_bf((acc[0][0] + acc[2][0]) * rinv, (acc[0][1] + acc[2][1]) * rinv),
                        ~pack_bf((acc[1][0] + acc[3][0]) * rinv, (acc[1][1] + acc[3][1]) * rinv));
    }
    PROF(7);
    const int side = lds32(sb + OFF_SIDE);
    const uint32_t red_st = pin(sb + SC_E4 + ((warp * 4 + 2 * ((lane >> 3) & 1) + (lane >> 4)) * 8 + (lane & 7)) * 4);
    const uint32_t red_ld = pin(sb + SC_E4 + (lane & 15) * 8);
    const uint32_t* const in1 = pin(slot(SL_P1 + own, side) + tid * 4);
    const uint32_t* const in2a = pin(slot(SL_P2 + 2 * own, side) + tid * 4);
    const uint32_t* const in2b = pin(slot(SL_P2 + 2 * own + 1, side) + tid * 4);
    uint32_t* const out_dst = pin((uint32_t*)(p.out + ((lane >> 2) & 3) * D + 8 * own) + t4);
    uint32_t* const x1_dst = pin(slot(SL_X1 + own / 30, lane >> 4) + (own % 30) * 32 + (lane & 15));
    uint32_t* const rst = pin(tid >= 32 && tid < 56 ? mod_slot(lane >> 2, own, lane & 3) : own < 32 && tid == 64 ? g_clr + own * 4 : own < 16 && tid == 96 ? g_phase + own * 32 : nullptr);
    const uint32_t xw = lds32(sb + OWN_X + (lane & 15) * 4), ga_w = lds32(sb + OWN_GA + (lane & 15) * 4);
    uint32_t cs[15];
    uint32_t* dst2[10];
    uint32_t w2a[5];
#pragma unroll
    for (int j = 0; j < 10; j++) cs[j] = lds32(sb + OFF_VB + ((g & 1) * 4 + (g >> 1)) * VEC_STRIDE + warp * 160 + t4 * 4 + j * 16);
#pragma unroll
    for (int i = 0; i < 5; i++) {
        cs[10 + i] = lds32(sb + OFF_VB + (g >> 1) * VEC_STRIDE + warp * 160 + (g & 1) * 16 + t4 * 4 + i * 32);
        const uint2 t = lds64(sb + OFF_TAB2 + warp * 40 + i * 8);
        dst2[2 * i] = slot_ptr(t.x + g * 16 + t4 * 8);
        dst2[2 * i + 1] = slot_ptr(t.y + g * 16 + t4 * 8);
        const int cc = 2 * (warp * 5 + i) + (mi & 1);
        w2a[i] = pin(sb + X_W2 + (cc >> 3) * 4096 + (r8 + 8 * (mi >> 1)) * 128 + (((cc & 7) ^ r8) << 4));
    }
    const uint32_t piv = lds32(sb + OFF_STAT + (g >> 1) * 8);
    const uint32_t* const xin = pin(slot(SL_X1 + warp / 3, side) + ((warp % 3) * 10 + (g & 1)) * 32 + (g >> 1) * 4 + t4);
    const uint32_t w1a = pin(sb + X_W1 + (warp * 80 + r8 + 8 * (mi >> 1)) * 64 + (((mi & 1) ^ ((r8 >> 1) & 3)) << 4));
    const uint32_t w1bar = pin(bar_w1 + (warp >> 1) * 8), w2bar = pin(bar_w2 + (warp + (warp >> 2)) * 8);
    const uint32_t wbar = pin(NB_O + warp);
    const uint32_t ab_st = pin(sb + SC_AB + warp * 1024 + lane * 16), y_st = pin(sb + SC_Y + warp * 512 + lane * 8), s_st = pin(sb + SC_ST + (t4 * 8 + warp) * 8);
    const uint32_t h_ld = pin(sb + SC_H1 + ((g & 3) ^ (2 * (f & 1) + ((f >> 1) & 1))) * 64 + t4 * 16);
    {
        const int kap = 2 * (head & 1) + ((head >> 1) & 1);
        const uint32_t wa = pin(sb + X_WO + (mt >> 1) * (DH * 64) + (r8 + 8 * (mi >> 1)) * 64 + ((((mt & 1) * 2 + (mi & 1)) ^ ((r8 >> 1) & 3)) << 4));
        const uint32_t oa = pin(sb + OFF_O + ((g & 3) ^ kap) * O_STRIDE + t4 * 8);
        uint32_t* dst[4];
#pragma unroll
        for (int i = 0; i < 2; i++) {
            const uint2 t = lds64(sb + OFF_TAB1 + (bown * 20 + 2 * mt + (warp < 2 ? 4 * i : 0)) * 4);
            dst[2 * i] = slot_ptr(t.x + g * 16 + t4 * 8);
            dst[2 * i + 1] = slot_ptr(t.y + g * 16 + t4 * 8);
        }
        PROF(6);
        uint32_t wf[8][4], wg[8][4];
        mbar_wait(bar_wo + (mt >> 1) * 8, 0);
#pragma unroll
        for (int ks = 0; ks < 8; ks++) ldsm4t(wf[ks], wa + ks * 1024);
        if (warp < 2) {
            mbar_wait(bar_wo + 8, 0);
#pragma unroll
            for (int ks = 0; ks < 8; ks++) ldsm4t(wg[ks], wa + DH * 64 + ks * 1024);
        }
        asm volatile("bar.sync %0, 64;" ::"r"(wbar) : "memory");
        PROF(8);
        uint2 ob[8];
#pragma unroll
        for (int ks = 0; ks < 8; ks++) ob[ks] = lds64(oa + ks * 32);
        float c0[4] = {0.f, 0.f, 0.f, 0.f}, c1[4] = {0.f, 0.f, 0.f, 0.f};
        if (warp < 2) {
            float c2[4] = {0.f, 0.f, 0.f, 0.f}, c3[4] = {0.f, 0.f, 0.f, 0.f};
#pragma unroll
            for (int ks = 0; ks < 8; ks += 2) {
                mma16816(c0, wf[ks], ob[ks].x, ob[ks].y);
                mma16816(c2, wg[ks], ob[ks].x, ob[ks].y);
                mma16816(c1, wf[ks + 1], ob[ks + 1].x, ob[ks + 1].y);
                mma16816(c3, wg[ks + 1], ob[ks + 1].x, ob[ks + 1].y);
            }
            stg_relaxed2_if(t4 < 2, dst[2], flag(c2[0] + c3[0]), flag(c2[1] + c3[1]));
            stg_relaxed2_if(t4 < 2, dst[3], flag(c2[2] + c3[2]), flag(c2[3] + c3[3]));
        } else {
#pragma unroll
            for (int ks = 0; ks < 8; ks += 2) {
                mma16816(c0, wf[ks], ob[ks].x, ob[ks].y);
                mma16816(c1, wf[ks + 1], ob[ks + 1].x, ob[ks + 1].y);
            }
        }
        stg_relaxed2_if(t4 < 2, dst[0], flag(c0[0] + c1[0]), flag(c0[1] + c1[1]));
        stg_relaxed2_if(t4 < 2, dst[1], flag(c0[2] + c1[2]), flag(c0[3] + c1[3]));
    }
    PROF(9);
    uint32_t x1w = 0;
    if (is_owner) {
        uint4 v;
        for (int it = 0;; it++) {
            v = ldg_relaxed(in1);
            if (__all_sync(0xffffffffu, and3(and3(v.x, v.y, v.z), v.w, 1u))) break;
            if (it > SPIN_LIMIT) __trap();
        }
        PROF(11);
        const float s0 = __uint_as_float(v.x) + __shfl_xor_sync(0xffffffffu, __uint_as_float(v.z), 8);
        const float s1 = __uint_as_float(v.y) + __shfl_xor_sync(0xffffffffu, __uint_as_float(v.w), 8);
        sts_f32(red_st, s0 + __shfl_xor_sync(0xffffffffu, s1, 16));
        nbar_sync<NB_E4, 256>();
        if (warp == 0) {
            float2 a[8];
#pragma unroll
            for (int w = 0; w < 8; w++) a[w] = lds_f32x2(red_ld + w * 128);
            const uint32_t aw = pack_bf(((a[0].x + a[1].x) + (a[2].x + a[3].x)) + ((a[4].x + a[5].x) + (a[6].x + a[7].x)),
                                        ((a[0].y + a[1].y) + (a[2].y + a[3].y)) + ((a[4].y + a[5].y) + (a[6].y + a[7].y)));
            x1w = bf2_add(xw, bf2_mul(ga_w, aw));
            stg_relaxed(x1_dst, x1w ^ 0x80008000u);
            if (lane == 0) mbar_arrive(bar_x1);
        }
        if (rst) stg_zero4(rst);
    }
    PROF(12);
    if (is_f) {
        uint32_t f1[5][2][4], f2[5][2][4];
        uint32_t d[6];
        auto load_x1 = [&] {
#pragma unroll
            for (int i = 0; i < 5; i++) d[i] = ldg_relaxed32(xin + i * 64);
        };
        auto have_x1 = [&] { return __all_sync(0xffffffffu, __vimin3_u32(__vimin3_u32(d[0], d[1], d[2]), d[3], d[4]) != 0u); };
        mbar_wait(w1bar, 0);
        load_x1();
        {
#pragma unroll
            for (int i = 0; i < 5; i++) { ldsm4t(f1[i][0], w1a + i * 1024); ldsm4t(f1[i][1], (w1a ^ 32) + i * 1024); }
            float c[2][4];
#pragma unroll
            for (int m = 0; m < 2; m++) c[m][0] = c[m][1] = c[m][2] = c[m][3] = 0.f;
#pragma unroll
            for (int i = 0; i < 5; i++) { mma16816(c[0], f1[i][0], cs[2 * i], cs[2 * i + 1]); mma16816(c[1], f1[i][1], cs[2 * i], cs[2 * i + 1]); }
#pragma unroll
            for (int i = 0; i < 5; i++) { cs[2 * i] = pin(odd ? 0u : cs[10 + i]); cs[2 * i + 1] = pin(odd ? cs[10 + i] : 0u); }
#pragma unroll
            for (int m = 0; m < 2; m++) sts128(ab_st + m * 512, make_uint4(__float_as_uint(c[m][0]), __float_as_uint(c[m][1]), __float_as_uint(c[m][2]), __float_as_uint(c[m][3])));
            nbar_arrive<NB_AB, 320>();
            d[0] |= __float_as_uint(c[1][3]) & (side >> 1);
        }
        PROF(10);
#pragma unroll 1
        for (int it = 0; !have_x1(); it++) {
            load_x1();
            if (it > SPIN_LIMIT) __trap();
        }
        PROF(13);
        {
            float y[2][4], st[4] = {0.f, 0.f, 0.f, 0.f};
#pragma unroll
            for (int m = 0; m < 2; m++) y[m][0] = y[m][1] = y[m][2] = y[m][3] = 0.f;
#pragma unroll
            for (int i = 0; i < 5; i++) d[i] = bf2_add(d[i], piv);
            d[5] = 0u;
#pragma unroll
            for (int i = 0; i < 5; i++) {
                if (i < 3) {
                    const uint32_t a[4] = {d[2 * i], 0x3f803f80u, d[2 * i + 1], 0x3f803f80u};
                    mma16816(st, a, d[2 * i], d[2 * i + 1]);
                }
                const uint32_t y0 = bf2_mul(d[i], cs[2 * i]), y1 = bf2_mul(d[i], cs[2 * i + 1]);
                mma16816(y[0], f1[i][0], y0, y1);
                mma16816(y[1], f1[i][1], y0, y1);
            }
            const float q = odd ? st[1] : st[0];
            const float q2 = q + __shfl_xor_sync(0xffffffffu, q, 4);
            if (diag && !odd) sts_f32x2(s_st, q2, st[2] + st[3]);
#pragma unroll
            for (int m = 0; m < 2; m++) sts_f32x2(y_st + m * 256, y[m][0] + y[m][1], y[m][2] + y[m][3]);
        }
        nbar_arrive<NB_Y, 320>();
        PROF(14);
        mbar_wait(w2bar, 0);
        mbar_wait(w2bar + 8, 0);
#pragma unroll
        for (int i = 0; i < 5; i++) { ldsm4t(f2[i][0], w2a[i]); ldsm4t(f2[i][1], w2a[i] + 2048); }
        asm volatile("bar.sync %0, 96;" ::"r"(wbar) : "memory");
        PROF(15);
        {
            const uint4 hb = lds128(h_ld);
            float c[5][4];
#pragma unroll
            for (int i = 0; i < 7; i++) {
                if (i < 5) { c[i][0] = c[i][1] = c[i][2] = c[i][3] = 0.f; mma16816(c[i], f2[i][0], hb.x, hb.y); }
                if (i > 0 && i < 6) mma16816(c[i - 1], f2[i - 1][1], hb.z, hb.w);
                if (i > 1) {
                    stg_relaxed2_if(t4 < 2, dst2[2 * i - 4], flag(c[i - 2][0]), flag(c[i - 2][1]));
                    stg_relaxed2_if(t4 < 2, dst2[2 * i - 3], flag(c[i - 2][2]), flag(c[i - 2][3]));
                }
            }
        }
    }
    PROF(16);
    if (is_owner) {
        const uint32_t b2w = lds32(sb + OWN_B2 + (lane & 15) * 4), gb_ld = pin(sb + OWN_GB + (lane & 15) * 4);
        const bool two = tid < NF * 8 - 256;
        uint4 v, w = make_uint4(1, 1, 1, 1);
        for (int it = 0;; it++) {
            ldg_relaxed_if(two, w, in2b);
            v = ldg_relaxed(in2a);
            if (__all_sync(0xffffffffu, and3(and3(v.x, v.y, v.z), and3(v.w, w.x, w.y), and3(w.z, w.w, 1u)))) break;
            if (it > SPIN_LIMIT) __trap();
        }
        PROF(17);
        const float s0 = (__uint_as_float(v.x) + __uint_as_float(w.x)) + __shfl_xor_sync(0xffffffffu, __uint_as_float(v.z) + __uint_as_float(w.z), 8);
        const float s1 = (__uint_as_float(v.y) + __uint_as_float(w.y)) + __shfl_xor_sync(0xffffffffu, __uint_as_float(v.w) + __uint_as_float(w.w), 8);
        sts_f32(red_st + (SC_E6 - SC_E4), s0 + __shfl_xor_sync(0xffffffffu, s1, 16));
        if (warp != 0) {
            nbar_arrive<NB_E6, 288>();
        } else {
            nbar_sync<NB_E6, 288>();
            float2 a[8];
#pragma unroll
            for (int i = 0; i < 8; i++) a[i] = lds_f32x2(red_ld + (SC_E6 - SC_E4) + i * 128);
            const uint32_t gb_w = lds32(gb_ld);
            const uint32_t aw = pack_bf(((a[0].x + a[1].x) + (a[2].x + a[3].x)) + ((a[4].x + a[5].x) + (a[6].x + a[7].x)),
                                        ((a[0].y + a[1].y) + (a[2].y + a[3].y)) + ((a[4].y + a[5].y) + (a[6].y + a[7].y)));
            x1w = bf2_add(x1w, bf2_mul(gb_w, bf2_add(aw, b2w)));
            if (lane < 16) asm volatile("st.global.u32 [%0], %1;" ::"l"(out_dst), "r"(x1w) : "memory");
        }
    }
    PROF(18);
    PROF_DUMP;
}

typedef CUresult (*EncodeFn)(CUtensorMap*, CUtensorMapDataType, cuuint32_t, void*, const cuuint64_t*, const cuuint64_t*, const cuuint32_t*,
                             const cuuint32_t*, CUtensorMapInterleave, CUtensorMapSwizzle, CUtensorMapL2promotion, CUtensorMapFloatOOBfill);

static CUtensorMap make_map(EncodeFn enc, const void* ptr, int cols, int rows, int box_cols, int box_rows, CUtensorMapSwizzle sw,
                            CUtensorMapL2promotion promo = CU_TENSOR_MAP_L2_PROMOTION_NONE) {
    CUtensorMap m;
    cuuint64_t dims[2] = {(cuuint64_t)cols, (cuuint64_t)rows};
    cuuint64_t strides[1] = {(cuuint64_t)cols * 2};
    cuuint32_t box[2] = {(cuuint32_t)box_cols, (cuuint32_t)box_rows};
    cuuint32_t es[2] = {1, 1};
    enc(&m, CU_TENSOR_MAP_DATA_TYPE_BFLOAT16, 2, const_cast<void*>(ptr), dims, strides, box, es, CU_TENSOR_MAP_INTERLEAVE_NONE, sw,
        promo, CU_TENSOR_MAP_FLOAT_OOB_FILL_NONE);
    return m;
}

}

extern "C" void kernel_launch(void* const* d_in, const int* in_sizes, int n_in, void* d_out, int out_size) {
    (void)in_sizes; (void)n_in; (void)out_size;
    static EncodeFn enc = nullptr;
    if (!enc) {
        void* fn = nullptr;
        cudaDriverEntryPointQueryResult qr;
        cudaGetDriverEntryPoint("cuTensorMapEncodeTiled", &fn, cudaEnableDefault, &qr);
        enc = (EncodeFn)fn;
        cudaFuncSetAttribute(fused_kernel, cudaFuncAttributeMaxDynamicSharedMemorySize, SMEM_BYTES);
    }
    Params p;
    p.x = (const __nv_bfloat16*)d_in[0];
    p.kc = (const __nv_bfloat16*)d_in[1];
    p.vc = (const __nv_bfloat16*)d_in[2];
    p.b1 = (const __nv_bfloat16*)d_in[7];
    p.b2 = (const __nv_bfloat16*)d_in[9];
    p.c = (const __nv_bfloat16*)d_in[10];
    p.out = (__nv_bfloat16*)d_out;
    CUtensorMap tm_wmod = make_map(enc, d_in[11], NMOD, D, 32, 160, CU_TENSOR_MAP_SWIZZLE_64B);
    CUtensorMap tm_wq = make_map(enc, d_in[3], NH * DH, D, 32, 160, CU_TENSOR_MAP_SWIZZLE_64B);
    CUtensorMap tm_wo = make_map(enc, d_in[4], D, NH * DH, 32, 128, CU_TENSOR_MAP_SWIZZLE_64B);
    CUtensorMap tm_w1 = make_map(enc, d_in[6], FF, D, 32, 160, CU_TENSOR_MAP_SWIZZLE_64B);
    CUtensorMap tm_w2 = make_map(enc, d_in[8], D, FF, 64, 32, CU_TENSOR_MAP_SWIZZLE_128B);
    CUtensorMap tm_v = make_map(enc, d_in[2], DH, NB * NH * SK, 64, TILE_KEYS, CU_TENSOR_MAP_SWIZZLE_128B);
    CUtensorMap tm_gb = make_map(enc, d_in[11], NMOD, D, 8, 160, CU_TENSOR_MAP_SWIZZLE_NONE, CU_TENSOR_MAP_L2_PROMOTION_L2_128B);
    fused_kernel<<<NCTA, NTHREADS, SMEM_BYTES>>>(p, tm_wmod, tm_wq, tm_wo, tm_w1, tm_w2, tm_v, tm_gb);
}
```

```cpp
#include <cuda_runtime.h>
#include <cuda.h>
#include <cuda_bf16.h>
#include <stdint.h>

namespace {

constexpr int NB = 4, D = 640, NH = 32, DH = 128, SK = 8192, WIN = 2048, FF = 1728, NMOD = 6 * D;
constexpr int NCTA = 128;
constexpr int NOWN = 80;
constexpr int NF = 54;
constexpr int NTHREADS = 320;
constexpr int TILE_KEYS = 64;
constexpr int TILE_BYTES = TILE_KEYS * DH * 2;
constexpr int NITEM = 2 * WIN / TILE_KEYS;
constexpr int NS = 8;
constexpr int NMODC = 120;
constexpr int SPIN_LIMIT = 1 << 18;
#define INFLIGHT 3
#define WQ_DELAY 400
#define PACE_A 7800
#define PACE_TAU 635
#define PF_END 14
#define PH_FIRST 20
#define PH_LAG 5
#define LAT_T 2100
#define WO_T -1100
#define WO_S 200
#define W1_T 950
#define W2_T 1650
#define GB_T 2500
#define GB_EV 300
#define CLR_CHECK 28000
constexpr int NPROBE = 8, PROBE_END = 10000;
constexpr int SEG_J = 8;

constexpr int OFF_RING = 0;
constexpr int OFF_X = OFF_RING + NS * TILE_BYTES;
constexpr int X_WM = OFF_X;
constexpr int X_WQ = OFF_X + D * 64;
constexpr int X_WO = OFF_X;
constexpr int X_W1 = X_WO + 5 * DH * 64;
constexpr int X_END = X_W1 + D * 64;
constexpr int X_W2 = OFF_RING;
constexpr int X_GB = OFF_RING + 3 * TILE_BYTES;
static_assert(X_WQ + D * 64 <= X_END, "prologue weights must fit");
constexpr int VEC_STRIDE = 1296;
constexpr int OFF_VA = X_END;
constexpr int OFF_VB = OFF_VA + 4 * VEC_STRIDE;
constexpr int OFF_RED = OFF_VB + 4 * VEC_STRIDE;
constexpr int OFF_ML = OFF_RED + 4 * VEC_STRIDE;
constexpr int O_STRIDE = 288;
constexpr int OFF_O = OFF_ML + 64;
constexpr int OFF_Q = OFF_O + 4 * O_STRIDE;
constexpr int OFF_OWN = OFF_Q + 256;
constexpr int OWN_X = OFF_OWN, OWN_B2 = OWN_X + 64, OWN_GA = OWN_B2 + 64, OWN_GB = OWN_GA + 64, OWN_B1 = OWN_GB + 64;
constexpr int OFF_STAT = OWN_B1 + 128;
constexpr int OFF_TAB1 = OFF_STAT + 32;
constexpr int OFF_TAB2 = OFF_TAB1 + NOWN * 4;
constexpr int OFF_SIDE = OFF_TAB2 + NOWN * 4;
constexpr int OFF_BAR = OFF_SIDE + 8;
constexpr int NBAR = 2 * NS + 32;
constexpr int SMEM_BYTES = OFF_BAR + NBAR * 8;
constexpr int SC_OP = OFF_RING + 4 * TILE_BYTES;
constexpr int SC_AB = SC_OP + 4096;
constexpr int SC_Y = SC_AB + 8192;
constexpr int SC_ST = SC_Y + 4096;
constexpr int SC_E4 = SC_ST + 256;
constexpr int SC_E6 = SC_E4 + 1024;
constexpr int SC_P = SC_E6 + 1024;
constexpr int SC_H1 = SC_P + 256;
static_assert(SMEM_BYTES <= 232448, "smem");
static_assert(OFF_BAR % 8 == 0 && OFF_X % 1024 == 0 && X_WQ % 512 == 0 && X_W1 % 512 == 0 && OFF_VA % 16 == 0 && OFF_RED % 16 == 0 && OFF_ML % 16 == 0 && OFF_O % 16 == 0 && OFF_Q % 16 == 0, "align");
constexpr int NB_O = 2  , NB_E4 = 10, NB_E6 = 11, NB_AB = 12, NB_Y = 13;

__device__ uint32_t g_mod[NMODC * 64];
__device__ uint32_t g_q[NCTA * 64];
__device__ uint32_t g_clr[NCTA];
__device__ uint32_t g_phase[16 * 32];
constexpr int SL_P1 = 0;
constexpr int SL_P2 = SL_P1 + NOWN;
constexpr int SL_O = SL_P2 + 2 * NOWN;
constexpr int SL_X1 = SL_O + 8;
constexpr int SL_SIDE = SL_X1 + 3;
static_assert(SL_SIDE < 256, "one 2 MB page");
__device__ uint32_t g_slots[2 * 256 * 2048];
__device__ __forceinline__ uint32_t* slot(int i, int side) {
    const size_t base = ((size_t)g_slots + 0x1fffff) & ~(size_t)0x1fffff;
    return (uint32_t*)base + i * 2048 + (((__popc(i & 0x59) ^ side) & 1) << 10);
}
#define PROF_DECL
#define HPROF(i) do { } while (0)
#define PROF(i) do { } while (0)
#define PROF_DUMP do { } while (0)

__device__ __forceinline__ uint32_t smem_u32(const void* p) { return (uint32_t)__cvta_generic_to_shared(p); }
__device__ __forceinline__ void mbar_init(uint32_t bar, uint32_t cnt) { asm volatile("mbarrier.init.shared::cta.b64 [%0], %1;" ::"r"(bar), "r"(cnt) : "memory"); }
__device__ __forceinline__ void mbar_expect_tx(uint32_t bar, uint32_t bytes) { asm volatile("mbarrier.arrive.expect_tx.shared::cta.b64 _, [%0], %1;" ::"r"(bar), "r"(bytes) : "memory"); }
__device__ __forceinline__ void mbar_arrive(uint32_t bar) { asm volatile("mbarrier.arrive.shared::cta.b64 _, [%0];" ::"r"(bar) : "memory"); }
__device__ __forceinline__ void mbar_wait(uint32_t bar, uint32_t parity) {
    uint32_t ok;
    int it = 0;
    while (true) {
        asm volatile("{\n.reg .pred p;\nmbarrier.try_wait.parity.shared::cta.b64 p, [%1], %2;\nselp.u32 %0, 1, 0, p;\n}" : "=r"(ok) : "r"(bar), "r"(parity) : "memory");
        if (ok) break;
        if (++it > SPIN_LIMIT) __trap();
    }
}
__device__ __forceinline__ void bulk_load(uint32_t dst, const void* src, uint32_t bytes, uint32_t bar, uint64_t pol) {
    asm volatile("cp.async.bulk.shared::cluster.global.mbarrier::complete_tx::bytes.L2::cache_hint [%0], [%1], %2, [%3], %4;"
                 ::"r"(dst), "l"(src), "r"(bytes), "r"(bar), "l"(pol) : "memory");
}
__device__ __forceinline__ void bar_cons() { asm volatile("bar.sync 1, 256;" ::: "memory"); }
template <int ID, int N> __device__ __forceinline__ void nbar_sync() { asm volatile("bar.sync %0, %1;" ::"n"(ID), "n"(N) : "memory"); }
template <int ID, int N> __device__ __forceinline__ void nbar_arrive() { asm volatile("bar.arrive %0, %1;" ::"n"(ID), "n"(N) : "memory"); }
__device__ __forceinline__ bool mbar_test(uint32_t bar, uint32_t parity) {
    uint32_t ok;
    asm volatile("{\n.reg .pred p;\nmbarrier.test_wait.parity.shared::cta.b64 p, [%1], %2;\nselp.u32 %0, 1, 0, p;\n}" : "=r"(ok) : "r"(bar), "r"(parity) : "memory");
    return ok;
}
__device__ __forceinline__ uint32_t pin(uint32_t v) { asm volatile("" : "+r"(v)); return v; }
template <class T> __device__ __forceinline__ T pin_hard(T v) { return __shfl_sync(0xffffffffu, v, threadIdx.x & 31); }
template <class T> __device__ __forceinline__ T* pin(T* v) { asm volatile("" : "+l"(v)); return v; }
__device__ __forceinline__ void ldsm4(uint32_t (&a)[4], uint32_t addr) {
    asm volatile("ldmatrix.sync.aligned.m8n8.x4.shared.b16 {%0,%1,%2,%3}, [%4];" : "=r"(a[0]), "=r"(a[1]), "=r"(a[2]), "=r"(a[3]) : "r"(addr) : "memory");
}
__device__ __forceinline__ void ldsm4t(uint32_t (&a)[4], uint32_t addr) {
    asm volatile("ldmatrix.sync.aligned.m8n8.x4.trans.shared.b16 {%0,%1,%2,%3}, [%4];" : "=r"(a[0]), "=r"(a[1]), "=r"(a[2]), "=r"(a[3]) : "r"(addr) : "memory");
}
__device__ __forceinline__ void mma16816(float (&c)[4], const uint32_t (&a)[4], uint32_t b0, uint32_t b1) {
    asm volatile("mma.sync.aligned.m16n8k16.row.col.f32.bf16.bf16.f32 {%0,%1,%2,%3}, {%4,%5,%6,%7}, {%8,%9}, {%0,%1,%2,%3};"
                 : "+f"(c[0]), "+f"(c[1]), "+f"(c[2]), "+f"(c[3]) : "r"(a[0]), "r"(a[1]), "r"(a[2]), "r"(a[3]), "r"(b0), "r"(b1));
}
__device__ __forceinline__ uint32_t lds32(uint32_t addr) { uint32_t v; asm volatile("ld.shared.u32 %0, [%1];" : "=r"(v) : "r"(addr) : "memory"); return v; }
__device__ __forceinline__ float lds_f32(uint32_t addr) { float v; asm volatile("ld.shared.f32 %0, [%1];" : "=f"(v) : "r"(addr) : "memory"); return v; }
__device__ __forceinline__ float2 lds_f32x2(uint32_t addr) { float2 v; asm volatile("ld.shared.v2.f32 {%0,%1}, [%2];" : "=f"(v.x), "=f"(v.y) : "r"(addr) : "memory"); return v; }
__device__ __forceinline__ float4 lds_f32x4(uint32_t addr) { float4 v; asm volatile("ld.shared.v4.f32 {%0,%1,%2,%3}, [%4];" : "=f"(v.x), "=f"(v.y), "=f"(v.z), "=f"(v.w) : "r"(addr) : "memory"); return v; }
__device__ __forceinline__ uint2 lds64(uint32_t addr) { uint2 v; asm volatile("ld.shared.v2.u32 {%0,%1}, [%2];" : "=r"(v.x), "=r"(v.y) : "r"(addr) : "memory"); return v; }
__device__ __forceinline__ uint4 lds128(uint32_t addr) { uint4 v; asm volatile("ld.shared.v4.u32 {%0,%1,%2,%3}, [%4];" : "=r"(v.x), "=r"(v.y), "=r"(v.z), "=r"(v.w) : "r"(addr) : "memory"); return v; }
__device__ __forceinline__ void sts16(uint32_t addr, uint32_t v) { asm volatile("st.shared.b16 [%0], %1;" ::"r"(addr), "h"((unsigned short)v) : "memory"); }
__device__ __forceinline__ void sts32(uint32_t addr, uint32_t v) { asm volatile("st.shared.u32 [%0], %1;" ::"r"(addr), "r"(v) : "memory"); }
__device__ __forceinline__ void sts_f32(uint32_t addr, float v) { asm volatile("st.shared.f32 [%0], %1;" ::"r"(addr), "f"(v) : "memory"); }
__device__ __forceinline__ void sts_f32x2(uint32_t addr, float a, float b) { asm volatile("st.shared.v2.f32 [%0], {%1,%2};" ::"r"(addr), "f"(a), "f"(b) : "memory"); }
__device__ __forceinline__ void sts128(uint32_t addr, uint4 v) { asm volatile("st.shared.v4.u32 [%0], {%1,%2,%3,%4};" ::"r"(addr), "r"(v.x), "r"(v.y), "r"(v.z), "r"(v.w) : "memory"); }
__device__ __forceinline__ uint4 ldg_relaxed(const uint32_t* p) {
    uint4 v;
    asm volatile("ld.relaxed.gpu.global.v4.u32 {%0,%1,%2,%3}, [%4];" : "=r"(v.x), "=r"(v.y), "=r"(v.z), "=r"(v.w) : "l"(p) : "memory");
    return v;
}
__device__ __forceinline__ void ldg_relaxed_if(bool on, uint4& v, const uint32_t* p) {
    asm volatile("{\n.reg .pred q;\nsetp.ne.u32 q, %5, 0;\n@q ld.relaxed.gpu.global.v4.u32 {%0,%1,%2,%3}, [%4];\n}"
                 : "+r"(v.x), "+r"(v.y), "+r"(v.z), "+r"(v.w) : "l"(p), "r"((uint32_t)on) : "memory");
}
__device__ __forceinline__ void stg_relaxed2_if(bool on, uint32_t* p, uint32_t a, uint32_t b) {
    asm volatile("{\n.reg .pred q;\nsetp.ne.u32 q, %3, 0;\n@q st.relaxed.gpu.global.v2.u32 [%0], {%1,%2};\n}" ::"l"(p), "r"(a), "r"(b), "r"((uint32_t)on) : "memory");
}
__device__ __forceinline__ uint32_t ldg_relaxed32(const uint32_t* p) { uint32_t v; asm volatile("ld.relaxed.gpu.global.u32 %0, [%1];" : "=r"(v) : "l"(p) : "memory"); return v; }
__device__ __forceinline__ void stg_relaxed(uint32_t* p, uint32_t v) { asm volatile("st.relaxed.gpu.global.u32 [%0], %1;" ::"l"(p), "r"(v) : "memory"); }
__device__ __forceinline__ void stg_zero4(uint32_t* p) { asm volatile("st.relaxed.gpu.global.v4.u32 [%0], {%1,%1,%1,%1};" ::"l"(p), "r"(0u) : "memory"); }
__device__ __forceinline__ bool ready(const uint4& v) { return (v.x != 0u) & (v.y != 0u) & (v.z != 0u) & (v.w != 0u); }
__device__ __forceinline__ uint4 inv4(const uint4& v) { return make_uint4(~v.x, ~v.y, ~v.z, ~v.w); }
__device__ __forceinline__ uint32_t pack_bf(float lo, float hi) {
    uint32_t r;
    asm("cvt.rn.bf16x2.f32 %0, %1, %2;" : "=r"(r) : "f"(hi), "f"(lo));
    return r;
}
__device__ __forceinline__ float bfr(float x) { return __uint_as_float(pack_bf(0.f, x) & 0xffff0000u); }
__device__ __forceinline__ float bf_lo(uint32_t w) { return __uint_as_float(w << 16); }
__device__ __forceinline__ float bf_hi(uint32_t w) { return __uint_as_float(w & 0xffff0000u); }
__device__ __forceinline__ float bf2f(__nv_bfloat16 v) { return __bfloat162float(v); }
__device__ __forceinline__ float ex2(float x) { float y; asm("ex2.approx.ftz.f32 %0, %1;" : "=f"(y) : "f"(x)); return y; }
__device__ __forceinline__ float rcp_fast(float x) { float y; asm("rcp.approx.ftz.f32 %0, %1;" : "=f"(y) : "f"(x)); return y; }
__device__ __forceinline__ float rsqrt_fast(float x) { float y; asm("rsqrt.approx.ftz.f32 %0, %1;" : "=f"(y) : "f"(x)); return y; }
__device__ __forceinline__ float sqrt_fast(float x) { float y; asm("sqrt.approx.f32 %0, %1;" : "=f"(y) : "f"(x)); return y; }
__device__ __forceinline__ uint32_t bf2_add(uint32_t a, uint32_t b) { uint32_t r; asm("add.rn.bf16x2 %0, %1, %2;" : "=r"(r) : "r"(a), "r"(b)); return r; }
__device__ __forceinline__ uint32_t bf2_sub(uint32_t a, uint32_t b) { uint32_t r; asm("sub.rn.bf16x2 %0, %1, %2;" : "=r"(r) : "r"(a), "r"(b)); return r; }
__device__ __forceinline__ uint32_t bf2_mul(uint32_t a, uint32_t b) { uint32_t r; asm("mul.rn.bf16x2 %0, %1, %2;" : "=r"(r) : "r"(a), "r"(b)); return r; }
__device__ __forceinline__ uint32_t gtime32() { uint32_t c; asm volatile("mov.u32 %0, %%globaltimer_lo;" : "=r"(c)); return c; }
__device__ __forceinline__ uint32_t clock32() { uint32_t c; asm volatile("mov.u32 %0, %%clock;" : "=r"(c)); return c; }

__device__ __forceinline__ float warp_sum(float v) {
#pragma unroll
    for (int o = 16; o > 0; o >>= 1) v += __shfl_xor_sync(0xffffffffu, v, o);
    return v;
}

struct Params {
    const __nv_bfloat16 *x, *kc, *vc, *b1, *b2, *c;
    __nv_bfloat16* out;
};

__device__ __forceinline__ void tma2d(uint32_t dst, const CUtensorMap* tm, int x, int y, uint32_t bar) {
    asm volatile("cp.async.bulk.tensor.2d.shared::cluster.global.mbarrier::complete_tx::bytes [%0], [%1, {%2, %3}], [%4];"
                 ::"r"(dst), "l"(tm), "r"(x), "r"(y), "r"(bar) : "memory");
}

__device__ __forceinline__ void tma2d_hint(uint32_t dst, const CUtensorMap* tm, int x, int y, uint32_t bar, uint64_t pol) {
    asm volatile("cp.async.bulk.tensor.2d.shared::cluster.global.mbarrier::complete_tx::bytes.L2::cache_hint [%0], [%1, {%2, %3}], [%4], %5;"
                 ::"r"(dst), "l"(tm), "r"(x), "r"(y), "r"(bar), "l"(pol) : "memory");
}
__device__ __forceinline__ uint32_t flag(float v) { return __float_as_uint(v) | 1u; }
__device__ __forceinline__ uint32_t and3(uint32_t a, uint32_t b, uint32_t c) { uint32_t r; asm("lop3.b32 %0, %1, %2, %3, 0x80;" : "=r"(r) : "r"(a), "r"(b), "r"(c)); return r; }
__device__ __forceinline__ uint32_t* slot_ptr(uint32_t lo) {
    uint32_t* r;
    asm volatile("mov.b64 %0, {%1, %2};" : "=l"(r) : "r"(lo), "r"((uint32_t)((size_t)slot(0, 0) >> 32)));
    return r;
}

__device__ __forceinline__ void load_bfrag(uint32_t vec, int stride, int k0, int g, int t, uint32_t& b0, uint32_t& b1) {
    uint32_t a = vec + (g & 3) * stride + (k0 + 2 * t) * 2;
    b0 = lds32(a);
    b1 = lds32(a + 16);
}

__device__ __forceinline__ void ln_finish(float pivot, float sum, float sumsq, uint32_t& m2, float& rden) {
    float dm = sum * (1.f / D);
    float var = fmaxf(sumsq * (1.f / D) - dm * dm, 0.f);
    float mean = pivot + dm;
    m2 = pack_bf(mean, mean);
    rden = rcp_fast(bfr(sqrt_fast(bfr(bfr(var) + 1e-5f))));
}
__device__ __forceinline__ uint32_t ln_mod_pair(uint32_t xw, uint32_t cw, uint32_t sw, uint32_t m2, float rden) {
    uint32_t d = bf2_sub(xw, m2);
    uint32_t ln = pack_bf(bf_lo(d) * rden, bf_hi(d) * rden);
    return bf2_add(bf2_mul(ln, bf2_add(cw, 0x3f803f80u)), sw);
}
__device__ __forceinline__ uint4 ln_mod4(const uint4& x, const uint4& c, const uint4& s, uint32_t m2, float rden) {
    return make_uint4(ln_mod_pair(x.x, c.x, s.x, m2, rden), ln_mod_pair(x.y, c.y, s.y, m2, rden),
                      ln_mod_pair(x.z, c.z, s.z, m2, rden), ln_mod_pair(x.w, c.w, s.w, m2, rden));
}
__device__ __forceinline__ void acc_stats(const uint4& v, float pv, float& s, float& q) {
    const float a0 = bf_lo(v.x) - pv, a1 = bf_hi(v.x) - pv, a2 = bf_lo(v.y) - pv, a3 = bf_hi(v.y) - pv;
    const float a4 = bf_lo(v.z) - pv, a5 = bf_hi(v.z) - pv, a6 = bf_lo(v.w) - pv, a7 = bf_hi(v.w) - pv;
    s += ((a0 + a1) + (a2 + a3)) + ((a4 + a5) + (a6 + a7));
    q += (fmaf(a0, a0, a1 * a1) + fmaf(a2, a2, a3 * a3)) + (fmaf(a4, a4, a5 * a5) + fmaf(a6, a6, a7 * a7));
}
__device__ __forceinline__ uint32_t* mod_slot(int kind, int j, int b) { return g_mod + (kind * 20 + (j >> 2)) * 64 + b * 16 + (j & 3) * 4; }

template <int N>
__device__ __forceinline__ void poll_n(uint4 (&v)[N], const uint32_t* const* ptr, const bool* on) {
    bool pend[N];
#pragma unroll
    for (int i = 0; i < N; i++) pend[i] = on[i];
    int it = 0;
    while (true) {
#pragma unroll
        for (int i = 0; i < N; i++) if (pend[i]) v[i] = ldg_relaxed(ptr[i]);
        bool any = false;
#pragma unroll
        for (int i = 0; i < N; i++) { pend[i] = pend[i] && !ready(v[i]); any |= pend[i]; }
        if (!__any_sync(0xffffffffu, any)) break;
        if (++it > SPIN_LIMIT) __trap();
    }
#pragma unroll
    for (int i = 0; i < N; i++) v[i] = inv4(v[i]);
}
__device__ __forceinline__ uint4 poll1(const uint32_t* p, bool on) {
    uint4 v[1] = {make_uint4(0, 0, 0, 0)};
    const uint32_t* const ptr[1] = {p};
    const bool o[1] = {on};
    poll_n<1>(v, ptr, o);
    return v[0];
}

__device__ __forceinline__ void gelu_stage(uint32_t sb, int m, int lane) {
    const int g = lane >> 2, b = lane & 3;
    const uint32_t y_ld = pin_hard(sb + SC_Y + m * 256 + lane * 8), s_ld = pin_hard(sb + SC_ST + b * 64);
    const uint32_t h_st = pin_hard(sb + SC_H1 + b * 64 + (g >> 1) * 16 + m * 8 + (g & 1) * 2);
    float a0 = 0.f, b0 = lds_f32(sb + OWN_B1 + (16 * m + g) * 4), a1 = 0.f, b1 = lds_f32(sb + OWN_B1 + (16 * m + g + 8) * 4);
    const float piv = bf_hi(lds32(sb + OFF_STAT + b * 8));
    nbar_sync<NB_AB, 320>();
#pragma unroll
    for (int w = 0; w < 8; w++) {
        const float4 t = lds_f32x4(sb + SC_AB + w * 1024 + m * 512 + lane * 16);
        a0 += t.x; b0 += t.y; a1 += t.z; b1 += t.w;
    }
    sts128(sb + SC_AB + m * 512 + lane * 16, make_uint4(__float_as_uint(a0), __float_as_uint(b0), __float_as_uint(a1), __float_as_uint(b1)));
    nbar_sync<NB_Y, 320>();
    float4 q[4];
    float2 y[8];
#pragma unroll
    for (int i = 0; i < 4; i++) q[i] = lds_f32x4(s_ld + i * 16);
#pragma unroll
    for (int w = 0; w < 8; w++) y[w] = lds_f32x2(y_ld + w * 512);
    const float dm = (((q[0].y + q[0].w) + (q[1].y + q[1].w)) + ((q[2].y + q[2].w) + (q[3].y + q[3].w))) * (1.f / D);
    const float sq = ((q[0].x + q[0].z) + (q[1].x + q[1].z)) + ((q[2].x + q[2].z) + (q[3].x + q[3].z));
    const float r = rsqrt_fast(fmaxf(fmaf(-dm, dm, fmaf(sq, 1.f / D, 1e-5f)), 1e-5f));
    const float y0 = ((y[0].x + y[1].x) + (y[2].x + y[3].x)) + ((y[4].x + y[5].x) + (y[6].x + y[7].x));
    const float y1 = ((y[0].y + y[1].y) + (y[2].y + y[3].y)) + ((y[4].y + y[5].y) + (y[6].y + y[7].y));
    const float dmr = piv - bfr(piv - dm);
    const float u0 = fmaf(r, fmaf(dmr, a0, -y0), b0), u1 = fmaf(r, fmaf(dmr, a1, -y1), b1);
    const float e0 = ex2(u0 * fmaf(u0 * u0, -0.044715f * 2.302208198144325f, -2.302208198144325f));
    const float e1 = ex2(u1 * fmaf(u1 * u1, -0.044715f * 2.302208198144325f, -2.302208198144325f));
    sts16(h_st, pack_bf(u0 * rcp_fast(1.f + e0), 0.f));
    sts16(h_st + 4, pack_bf(u1 * rcp_fast(1.f + e1), 0.f));
#pragma unroll
    for (int w = 0; w < 8; w++) asm volatile("bar.arrive %0, 96;" ::"r"(NB_O + w) : "memory");
}

struct Roles { bool is_f, is_owner; int f, own; };
__device__ __forceinline__ Roles roles(int cta) {
    Roles r;
    r.f = (cta * 27) >> 6;
    r.is_f = (((cta + 1) * 27) >> 6) != r.f;
    r.is_owner = !r.is_f || r.f % 9 == 4;
    r.own = r.is_f ? 74 + r.f / 9 : cta - r.f;
    return r;
}

__global__ void __launch_bounds__(NTHREADS, 1)
fused_kernel(const Params p, const __grid_constant__ CUtensorMap tm_wmod, const __grid_constant__ CUtensorMap tm_wq,
             const __grid_constant__ CUtensorMap tm_wo, const __grid_constant__ CUtensorMap tm_w1, const __grid_constant__ CUtensorMap tm_w2,
             const __grid_constant__ CUtensorMap tm_v, const __grid_constant__ CUtensorMap tm_gb) {
    extern __shared__ __align__(1024) unsigned char smem[];
    const uint32_t t_start = gtime32();
    const uint32_t sb = smem_u32(smem);
    const int cta = blockIdx.x;
    const int head = cta >> 2, bown = cta & 3;
    const int rot = (8 * head) & (NITEM / 2 - 1);
    const char* const kb = (const char*)(p.kc + ((size_t)(bown * NH + head) * SK + (SK - WIN)) * DH);
    uint64_t pol = 0;
    if (threadIdx.x == 256) {
        mbar_init(sb + OFF_BAR, 1);
        asm volatile("fence.mbarrier_init.release.cluster;" ::: "memory");
        asm volatile("createpolicy.fractional.L2::evict_first.b64 %0, 1.0;" : "=l"(pol));
        mbar_expect_tx(sb + OFF_BAR, TILE_BYTES);
        bulk_load(sb + OFF_RING, kb + (size_t)rot * TILE_BYTES, TILE_BYTES, sb + OFF_BAR, pol);
        if ((((cta + 1) * 5) >> 4) != ((cta * 5) >> 4)) {
            const uint32_t bar = sb + OFF_BAR + 2 * NS * 8;
            mbar_init(bar, 1);
            asm volatile("fence.mbarrier_init.release.cluster;" ::: "memory");
            mbar_expect_tx(bar, D * 64);
#pragma unroll 1
            for (int r = 0; r < D; r += 160) tma2d(sb + X_WM + r * 64, &tm_wmod, 32 * ((cta * 5) >> 4), r, bar);
        }
    }
    const uint32_t bar_full = sb + OFF_BAR, bar_empty = bar_full + NS * 8;
    const uint32_t bar_wm = bar_empty + NS * 8, bar_wq = bar_wm + 8, bar_xfree = bar_wq + 8, bar_wo = bar_xfree + 8  ;
    const uint32_t bar_w1 = bar_wo + 40  , bar_w2 = bar_w1 + 32  , bar_help = bar_w2 + 80, bar_v = bar_help + 8  ;
    const uint32_t bar_gb = bar_v + 32  , bar_x1 = bar_gb + 32;
    const int tid = threadIdx.x, warp = tid >> 5, lane = tid & 31;
    const Roles role = roles(cta);
    const bool is_f = role.is_f, is_owner = role.is_owner;
    const int f = role.f, own = role.own;
    const bool crit = (((cta + 1) * 5) >> 4) != ((cta * 5) >> 4);
    const int mr = cta - ((cta * 5) >> 4);
    const int ml = mr * 31 / 44;
    const bool late = !crit && (mr + 1) * 31 / 44 != ml;
    const int mc = crit ? (cta * 5) >> 4 : ml < 60 ? 40 + ml : 58 + ml;
    const bool gb_own = is_owner && own < 72;

    PROF_DECL
    PROF(0);
    uint4 xa = make_uint4(0, 0, 0, 0), xb = xa, ca0 = xa, ca1 = xa, xs[3] = {xa, xa, xa};
    uint32_t own0 = 0;
    __nv_bfloat16 own2 = __float2bfloat16(0.f);
    if (warp < 8) {
        xa = *(const uint4*)(p.x + (tid & 3) * D + (tid >> 2) * 8);
        ca0 = ((const uint4*)p.c)[tid];
        if (tid < 64) { xb = *(const uint4*)(p.x + (tid & 3) * D + (64 + (tid >> 2)) * 8); ca1 = ((const uint4*)p.c)[256 + tid]; }
        if (warp < 4) {
#pragma unroll
            for (int i = 0; i < 3; i++) if (lane + 32 * i < 80) xs[i] = ((const uint4*)p.x)[warp * 80 + lane + 32 * i];
        } else if (warp == 4) {
            if (is_owner) own0 = *(const uint32_t*)((lane < 16 ? p.x + (lane >> 2) * D : p.b2) + 8 * own + 2 * (lane & 3));
            if (is_f) own2 = p.b1[32 * f + lane];
        }
    }
    const char* const vb = (const char*)(p.vc + ((size_t)(bown * NH + head) * SK + (SK - WIN)) * DH);
    const uint32_t bar_first = crit ? bar_wm : bar_wq;
    if (threadIdx.x == 256) {
        if (!crit) {
            mbar_init(bar_wq, 1);
            asm volatile("fence.mbarrier_init.release.cluster;" ::: "memory");
            mbar_expect_tx(bar_wq, D * 64);
            const uint32_t c0 = clock32();
            while (clock32() - c0 < WQ_DELAY) { }
#pragma unroll
            for (int r = 0; r < D; r += 160) tma2d(sb + X_WQ + r * 64, &tm_wq, 32 * cta, r, bar_wq);
        }
    } else if (threadIdx.x == 0) {
#pragma unroll
        for (int s = 0; s < NS; s++) { if (s) mbar_init(bar_full + s * 8, 1); mbar_init(bar_empty + s * 8, 4); }
        mbar_init(crit ? bar_wq : bar_wm, 1);
        mbar_init(bar_xfree, 1);
#pragma unroll
        for (int i = 0; i < 5; i++) { mbar_init(bar_wo + i * 8, 1); mbar_init(bar_w2 + i * 16, 1); mbar_init(bar_w2 + i * 16 + 8, 1); }
        mbar_init(bar_help, 1); mbar_init(bar_x1, 1);
#pragma unroll
        for (int i = 0; i < 4; i++) { mbar_init(bar_v + i * 8, 1); mbar_init(bar_w1 + i * 8, 1); mbar_init(bar_gb + i * 8, 1); }
        asm volatile("fence.mbarrier_init.release.cluster;" ::: "memory");
    }
    __syncthreads();

    if (warp == 8) {
        if (lane == 0) {
            int tp = NS;
            int sched = PACE_A - NS * PACE_TAU;
#pragma unroll 1
            for (int t = 1; t <= NITEM; t++) {
                if (t == 1) mbar_wait(bar_full, 0);
                if (t == 2) {
                    mbar_wait(bar_first, 0);
                    if (crit) {
                        mbar_expect_tx(bar_wq, D * 64);
#pragma unroll 1
                        for (int r = 0; r < D; r += 160) tma2d(sb + X_WQ + r * 64, &tm_wq, 32 * cta, r, bar_wq);
                    }
                }
                if (t == 3) {
                    asm volatile("prefetch.tensormap [%0];" ::"l"(&tm_v) : "memory");
                    asm volatile("prefetch.tensormap [%0];" ::"l"(&tm_wo) : "memory");
                    asm volatile("prefetch.tensormap [%0];" ::"l"(&tm_w1) : "memory");
                    asm volatile("prefetch.tensormap [%0];" ::"l"(&tm_w2) : "memory");
                    asm volatile("prefetch.tensormap [%0];" ::"l"(&tm_gb) : "memory");
                }
                if (t == NS && late) {
                    mbar_wait(bar_full + (NS - INFLIGHT) * 8, 0);
                    mbar_expect_tx(bar_wm, D * 64);
#pragma unroll 1
                    for (int r = 0; r < D; r += 160) tma2d(sb + X_WM + r * 64, &tm_wmod, 32 * mc, r, bar_wm);
                }
                if (t >= NS && t < PF_END) {
                    int it = 0;
                    while (!mbar_test(bar_empty + (t & (NS - 1)) * 8, ((t >> 3) - 1) & 1)) {
                        if (tp < PF_END && (int)(gtime32() - t_start) >= PACE_A + (tp - NS) * PACE_TAU) {
                            asm volatile("cp.async.bulk.prefetch.L2.global.L2::cache_hint [%0], %1, %2;"
                                         ::"l"(((tp & 1) ? vb : kb) + (size_t)(((tp >> 1) + rot) & (NITEM / 2 - 1)) * TILE_BYTES), "r"(TILE_BYTES), "l"(pol) : "memory");
                            tp++;
                        }
                        if (++it > 16 * SPIN_LIMIT) __trap();
                    }
                    if (tp <= t) tp = t + 1;
                }
                if (t == NITEM) {
                    mbar_wait(bar_xfree, 0);
                    const uint32_t t_ref = t_start + sched + LAT_T + (NITEM - 1) * PACE_TAU;
#pragma unroll 1
                    for (int i = 0; i < 5; i++) {
                        while ((int)(gtime32() - t_ref) < WO_T + i * WO_S) { }
                        mbar_expect_tx(bar_wo + i * 8, DH * 64);
                        tma2d(sb + X_WO + i * (DH * 64), &tm_wo, bown * 160 + i * 32, head * DH, bar_wo + i * 8);
                    }
                    if (gb_own) {
                        mbar_wait(bar_empty + 3 * 8, ((NITEM >> 3) - 1) & 1);
                        mbar_wait(bar_x1, 0);
                        { const uint32_t c0 = clock32(); while (clock32() - c0 < GB_EV) { } }
                        while ((int)(gtime32() - t_ref) < GB_T) { }
#pragma unroll 1
                        for (int i = 0; i < 4; i++) {
                            mbar_expect_tx(bar_gb + i * 8, 160 * 16);
                            tma2d(sb + X_GB + i * (160 * 16), &tm_gb, 5 * D + 8 * own, 160 * i, bar_gb + i * 8);
                        }
                    }
                    if (is_f) {
#pragma unroll 1
                        for (int i = 0; i < 3; i++) mbar_wait(bar_empty + i * 8, ((NITEM >> 3) - 1) & 1);
                        while ((int)(gtime32() - t_ref) < W1_T) { }
#pragma unroll 1
                        for (int i = 0; i < 4; i++) {
                            mbar_expect_tx(bar_w1 + i * 8, 160 * 64);
                            tma2d(sb + X_W1 + i * (160 * 64), &tm_w1, 32 * f, 160 * i, bar_w1 + i * 8);
                        }
                        while ((int)(gtime32() - t_ref) < W2_T) { }
#pragma unroll 1
                        for (int i = 0; i < 10; i++) {
                            mbar_expect_tx(bar_w2 + i * 8, 4096);
                            tma2d(sb + X_W2 + i * 4096, &tm_w2, 64 * i, 32 * f, bar_w2 + i * 8);
                        }
                    }
                    break;
                }
                const int s = t & (NS - 1);
                if (t >= NS) {
                    mbar_wait(bar_empty + s * 8, ((t >> 3) - 1) & 1);
                    while ((int)(gtime32() - t_start) < sched + t * PACE_TAU) { }
                } else if (t >= INFLIGHT) {
                    mbar_wait(bar_full + (t - INFLIGHT) * 8, 0);
                }
                if (t < NITEM - 2) {
                    const int pair = t == NITEM - 3 ? NITEM / 2 - 1 : t >> 1;
                    mbar_expect_tx(bar_full + s * 8, TILE_BYTES);
                    bulk_load(sb + OFF_RING + s * TILE_BYTES, ((t & 1) && t != NITEM - 3 ? vb : kb) + (size_t)((pair + rot) & (NITEM / 2 - 1)) * TILE_BYTES, TILE_BYTES, bar_full + s * 8, pol);
                } else {
                    const int row = (bown * NH + head) * SK + (SK - WIN) + ((t - NITEM / 2 + rot) & (NITEM / 2 - 1)) * TILE_KEYS;
#pragma unroll 1
                    for (int i = 0; i < 2; i++) {
                        const uint32_t bar = bar_v + (2 * (t - (NITEM - 2)) + i) * 8;
                        mbar_expect_tx(bar, TILE_BYTES / 2);
                        tma2d_hint(sb + OFF_RING + s * TILE_BYTES + i * (TILE_BYTES / 2), &tm_v, 64 * i, row, bar, pol);
                    }
                }
                if (t >= PH_FIRST + PH_LAG && (t & 3) == (PH_LAG & 3)) {
                    const int now = (int)(gtime32() - t_start) - (t - PH_LAG) * PACE_TAU;
                    uint32_t ph;
                    asm volatile("atom.relaxed.gpu.global.add.u32 %0, [%1], 0;" : "=r"(ph) : "l"(g_phase + ((t - PH_LAG) >> 2) * 32) : "memory");
                    sched = (int)min(((ph & 0xffffffu) * 4 + (NCTA - (ph >> 24)) * now) >> 7, 65535u) - LAT_T;
                }
            }
        }
        __syncwarp();
    }

    if (warp == 9) {
        int side = 0;
        if (lane == 0) {
            uint32_t best[2] = {~0u, ~0u};
#pragma unroll 1
            for (int i = 0; i < 2 * NPROBE && ((i & 1) || (int)(gtime32() - t_start) < PROBE_END); i++) {
                uint32_t t0 = clock32(), v, t1;
                asm volatile("atom.relaxed.gpu.global.exch.b32 %0, [%1], %2;" : "=r"(v) : "l"(slot(SL_SIDE, i & 1) + cta * 8), "r"(0u) : "memory");
                asm volatile("{\n.reg .pred p;\nsetp.ne.u32 p, %1, 0xffffffff;\nmov.u32 %0, 0;\n@p mov.u32 %0, %%clock;\n}" : "=r"(t1) : "r"(v) : "memory");
                if (i & 1) best[1] = min(best[1], t1 - t0); else best[0] = min(best[0], t1 - t0);
            }
            side = best[1] < best[0];
        }
        side = __shfl_sync(0xffffffffu, side, 0);
        HPROF(1);
        mbar_wait(bar_full + (NS - 1) * 8, 0);
        stg_zero4(slot(SL_O + (cta >> 4), lane >> 4) + (cta & 15) * 64 + (lane & 15) * 4);
        if (is_owner) {
#pragma unroll 1
            for (int i = lane; i < NH * 8; i += 32) stg_zero4(slot(SL_P1 + own, side) + i * 4);
#pragma unroll 1
            for (int i = lane; i < NF * 8; i += 32) stg_zero4(slot(SL_P2 + 2 * own + (i >> 8), side) + (i & 255) * 4);
            if (lane < 8) stg_zero4(slot(SL_X1 + own / 30, lane >> 2) + (own % 30) * 32 + (lane & 3) * 4);
        }
        __threadfence();
        __syncwarp();
        if (lane == 0) stg_relaxed(g_clr + cta, 1u + side);
        HPROF(0);
        HPROF(2);
        while ((int)(gtime32() - t_start) < CLR_CHECK) __nanosleep(1000);
        mbar_wait(bar_xfree, 0);
        {
            uint4 v = make_uint4(1, 1, 1, 1), gv = v, mv[20];
#pragma unroll
            for (int i = 0; i < 20; i++) mv[i] = v;
#pragma unroll 1
            for (int it = 0;; it++) {
                v = ldg_relaxed(g_clr + lane * 4);

                ldg_relaxed_if(is_owner && lane < (gb_own ? 4 : 8), gv, mod_slot(lane < 4 ? 2 : 5, own, lane & 3));
#pragma unroll
                for (int i = 0; i < 20; i++) ldg_relaxed_if(is_f, mv[i], mod_slot(3, 8 * i + (lane >> 2), lane & 3));
                bool ok = ready(v) && ready(gv);
#pragma unroll
                for (int i = 0; i < 20; i++) ok = ok && ready(mv[i]);
                if (__all_sync(0xffffffffu, ok)) break;
                if (it > SPIN_LIMIT) __trap();
                __nanosleep(2000);
            }
            const uint32_t w[4] = {v.x, v.y, v.z, v.w};
#pragma unroll
            for (int i = 0; i < 4; i++) {
                const Roles r = roles(4 * lane + i);
                if (r.is_owner) {
                    sts32(sb + OFF_TAB1 + r.own * 4, (uint32_t)(size_t)(slot(SL_P1 + r.own, w[i] - 1) + head * 32));
                    sts32(sb + OFF_TAB2 + r.own * 4, (uint32_t)(size_t)(slot(SL_P2 + 2 * r.own + (f >> 5), w[i] - 1) + (f & 31) * 32));
                }
            }
            if (lane == 0) sts32(sb + OFF_SIDE, side);
            if (lane < 8) sts128(sb + OWN_GA + lane * 16, inv4(gv));
            const uint32_t dst = sb + OFF_VB + (lane & 3) * VEC_STRIDE + (lane >> 2) * 16;
#pragma unroll
            for (int i = 0; i < 10; i++) {
                const uint4 c = inv4(mv[10 + i]);
                sts128(dst + i * 128, make_uint4(bf2_add(c.x, 0x3f803f80u), bf2_add(c.y, 0x3f803f80u), bf2_add(c.z, 0x3f803f80u), bf2_add(c.w, 0x3f803f80u)));
                sts128(dst + (OFF_RED - OFF_VB) + i * 128, inv4(mv[i]));
            }
        }
        asm volatile("fence.acq_rel.gpu;" ::: "memory");
        __syncwarp();
        HPROF(3);
        if (lane == 0) mbar_arrive(bar_help);
        {
            const uint32_t* const src = pin(slot(SL_O + (cta >> 4), side) + (cta & 12) * 64 + lane * 4);
            const uint32_t dst = pin(sb + OFF_O + (lane >> 4) * O_STRIDE + (lane & 15) * 16);
            mbar_wait(bar_v + 16, 0);
            mbar_wait(bar_v + 24, 0);
            uint4 v[2];
            const uint32_t* const ptr[2] = {src, src + 128};
            const bool on[2] = {true, true};
            poll_n<2>(v, ptr, on);
            sts128(dst, v[0]);
            sts128(dst + 2 * O_STRIDE, v[1]);
#pragma unroll
            for (int w = 0; w < 8; w++) asm volatile("bar.arrive %0, 64;" ::"r"(NB_O + w) : "memory");
        }
        HPROF(4);
    }
    if (warp >= 8) {
        if (gb_own && warp == 9) {
            uint32_t a[20][4];
#pragma unroll
            for (int i = 0; i < 20; i++) ldsm4(a[i], sb + OFF_VA + (lane & 3) * VEC_STRIDE + (4 * i + (lane >> 3)) * 16);
            float c[4][4];
#pragma unroll
            for (int i = 0; i < 4; i++) c[i][0] = c[i][1] = c[i][2] = c[i][3] = 0.f;
#pragma unroll
            for (int bx = 0; bx < 4; bx++) {
                mbar_wait(bar_gb + bx * 8, 0);
#pragma unroll
                for (int i = 5 * bx; i < 5 * bx + 5; i++) {
                    uint32_t w[4];
                    ldsm4t(w, sb + X_GB + (32 * i + lane) * 16);
                    const uint32_t a0[4] = {a[i][0], 0u, a[i][1], 0u}, a1[4] = {a[i][2], 0u, a[i][3], 0u};
                    mma16816(c[(2 * i) & 3], a0, w[0], w[1]);
                    mma16816(c[(2 * i + 1) & 3], a1, w[2], w[3]);
                }
            }
            if (lane < 16) sts32(sb + OWN_GB + lane * 4, pack_bf((c[0][0] + c[1][0]) + (c[2][0] + c[3][0]), (c[0][1] + c[1][1]) + (c[2][1] + c[3][1])));
            HPROF(6);
        }
        if (is_owner && warp == 9) nbar_arrive<NB_E6, 288>();
        if (is_f) gelu_stage(sb, warp - 8, lane);
        return;
    }

    const int g = lane >> 2, t4 = lane & 3;
    const int mi = lane >> 3, r8 = lane & 7;

    {
        auto silu4 = [&](const uint4& cv) {
            uint32_t w4[4] = {cv.x, cv.y, cv.z, cv.w};
#pragma unroll
            for (int e = 0; e < 4; e++) {
                float c0 = bf_lo(w4[e]), c1 = bf_hi(w4[e]);
                w4[e] = pack_bf(c0 * rcp_fast(1.f + ex2(-1.4426950408889634f * c0)), c1 * rcp_fast(1.f + ex2(-1.4426950408889634f * c1)));
            }
            return make_uint4(w4[0], w4[1], w4[2], w4[3]);
        };
        {
            uint4 v = silu4(ca0);
            sts128(sb + OFF_VA + (tid / 80) * VEC_STRIDE + (tid % 80) * 16, v);
            if (tid < 64) { v = silu4(ca1); sts128(sb + OFF_VA + 3 * VEC_STRIDE + (16 + tid) * 16, v); }
        }
        if (warp < 4) {
            float s = 0.f, q = 0.f;
            const float pv = __shfl_sync(0xffffffffu, bf_lo(xs[0].x), 0);
#pragma unroll
            for (int i = 0; i < 3; i++) if (i < 2 || lane < 16) acc_stats(xs[i], pv, s, q);
#pragma unroll
            for (int of = 16; of > 0; of >>= 1) { s += __shfl_xor_sync(0xffffffffu, s, of); q += __shfl_xor_sync(0xffffffffu, q, of); }
            uint32_t m2; float rden;
            ln_finish(pv, s, q, m2, rden);
            if (lane == 0) { sts32(sb + OFF_STAT + warp * 8, m2); sts_f32(sb + OFF_STAT + warp * 8 + 4, rden); }
        } else if (warp == 4) {
            sts32(sb + OWN_X + lane * 4, bf2_add(own0, 0u));
            sts_f32(sb + OWN_B1 + lane * 4, bf2f(own2));
        }
    }
    bar_cons();
    PROF(24);
    uint32_t qf[8][2];
    float o[8][4];
#pragma unroll
    for (int c = 0; c < 8; c++) { o[c][0] = o[c][1] = o[c][2] = o[c][3] = 0.f; }
    float m_run = -INFINITY, l_run = 0.f;
    const bool diag = (t4 == (g >> 1));
    const bool odd = g & 1;
    const uint32_t koff = (warp & 3) * 4096 + (r8 + 8 * (mi & 1)) * 256 + (mi >> 1) * 128 + (r8 << 4);
    const uint32_t voff = TILE_BYTES + (warp & 3) * 4096 + (r8 + 8 * (mi >> 1)) * 256 + (mi & 1) * 128 + (r8 << 4);
    const int src0 = (2 * t4) * 4 + t4, src1 = (2 * t4 + 1) * 4 + t4;
#pragma unroll 1
    for (int step = crit ? 0 : 1; step < 3; step++) {
        if (step < 2 || late) {
            if (step == 1) {
                if (!crit) mbar_wait(bar_wq, 0);
                const uint32_t m2 = lds32(sb + OFF_STAT + (tid & 3) * 8);
                const float rden = lds_f32(sb + OFF_STAT + (tid & 3) * 8 + 4);
                uint4 v[4] = {xa, xa, xa, xa};
                const uint32_t* const ptr[4] = {mod_slot(0, tid >> 2, tid & 3), mod_slot(1, tid >> 2, tid & 3),
                                                mod_slot(0, 64 + ((tid & 63) >> 2), tid & 3), mod_slot(1, 64 + ((tid & 63) >> 2), tid & 3)};
                const bool on[4] = {true, true, tid < 64, tid < 64};
                poll_n<4>(v, ptr, on);
                uint4 h0 = ln_mod4(xa, v[1], v[0], m2, rden);
                sts128(sb + OFF_VB + (tid & 3) * VEC_STRIDE + (tid >> 2) * 16, h0);
                if (tid < 64) {
                    h0 = ln_mod4(xb, v[3], v[2], m2, rden);
                    sts128(sb + OFF_VB + (tid & 3) * VEC_STRIDE + (64 + (tid >> 2)) * 16, h0);
                }
            }
            mbar_wait(step == 1 ? bar_wq : bar_wm, 0);
            bar_cons();
            const uint32_t strip = sb + (step == 1 ? X_WQ : X_WM), vec = sb + (step == 1 ? OFF_VB : OFF_VA);
            float acc[2][4];
#pragma unroll
            for (int m = 0; m < 2; m++) { acc[m][0] = acc[m][1] = acc[m][2] = acc[m][3] = 0.f; }
#pragma unroll
            for (int i = 0; i < 5; i++) {
                int k0 = (warp * 5 + i) * 16;
                uint32_t b0, b1;
                load_bfrag(vec, VEC_STRIDE, k0, g, t4, b0, b1);
                int krow = k0 + r8 + 8 * (mi >> 1);
#pragma unroll
                for (int m = 0; m < 2; m++) {
                    uint32_t a[4];
                    int ch = 2 * m + (mi & 1);
                    ldsm4t(a, strip + krow * 64 + ((ch ^ ((krow >> 1) & 3)) << 4));
                    mma16816(acc[m], a, b0, b1);
                }
            }
            if (t4 < 2) {
#pragma unroll
                for (int m = 0; m < 2; m++) {
                    sts_f32x2(sb + OFF_RED + ((warp * 32 + m * 16 + g) * 4 + 2 * t4) * 4, acc[m][0], acc[m][1]);
                    sts_f32x2(sb + OFF_RED + ((warp * 32 + m * 16 + g + 8) * 4 + 2 * t4) * 4, acc[m][2], acc[m][3]);
                }
            }
            bar_cons();
            if (tid < 128) {
                float v = 0.f;
#pragma unroll
                for (int w = 0; w < 8; w++) v += lds_f32(sb + OFF_RED + (w * 128 + tid) * 4);
                float vn = __shfl_down_sync(0xffffffffu, v, 4);
                uint32_t* dst = step == 1 ? g_q + ((cta & ~3) + (tid & 3)) * 64 + bown * 16 + (tid >> 3) : g_mod + mc * 64 + (tid & 3) * 16 + (tid >> 3);
                if (!((tid >> 2) & 1)) stg_relaxed(dst, ~pack_bf(v, vn));
            }
        }
        if (step == 0) continue;
        if (step == 1) {
            if (warp == 0) {
                uint4 v = poll1(g_q + cta * 64 + (lane & 15) * 4, lane < 16);
                if (lane < 16) {
                    sts128(sb + OFF_Q + lane * 16, v);
                    stg_zero4(g_q + cta * 64 + lane * 4);
                }
            }
            bar_cons();
            PROF(4);

#pragma unroll
            for (int c = 0; c < 8; c++) {
                qf[c][0] = lds32(sb + OFF_Q + (((c ^ g) * 4 + t4) << 2));
                qf[c][1] = lds32(sb + OFF_Q + 128 + (((c ^ g) * 4 + t4) << 2));
            }
        } else {
            bar_cons();
            if (tid == 0) mbar_arrive(bar_xfree);
        }
#pragma unroll 1
        for (int j = (step == 1 ? 0 : SEG_J) + (warp >> 2); j < (step == 1 ? SEG_J : NITEM / 2 - 2); j += 2) {
            const int s = (2 * j) & (NS - 1);
            const uint32_t par = (j >> 2) & 1;
            mbar_wait(bar_full + s * 8, par);
            if (tid == 0 && 2 * j >= PH_FIRST) {
                const int x = min(max((int)(gtime32() - t_start) - 2 * j * PACE_TAU, 0), 65535);
                asm volatile("red.relaxed.gpu.global.add.u32 [%0], %1;" ::"l"(g_phase + (j >> 1) * 32), "r"((1u << 24) + (x >> 2)) : "memory");
            }
            const uint32_t base = sb + OFF_RING + s * TILE_BYTES;
            float sa[4] = {0.f, 0.f, 0.f, 0.f}, sb2[4] = {0.f, 0.f, 0.f, 0.f};
#pragma unroll
            for (int c = 0; c < 8; c += 2) {
                uint32_t a[4], a2[4];
                ldsm4(a, (base + koff) ^ (c << 4));
                ldsm4(a2, (base + koff) ^ ((c + 1) << 4));
                mma16816(sa, a, qf[c][0], qf[c][1]);
                mma16816(sb2, a2, qf[c + 1][0], qf[c + 1][1]);
            }
            const uint32_t sw = pack_bf(odd ? sa[1] + sb2[1] : sa[0] + sb2[0], odd ? sa[3] + sb2[3] : sa[2] + sb2[2]);
            const uint32_t sv = pack_bf(bf_lo(sw) * 0.08838834764831845f, bf_hi(sw) * 0.08838834764831845f);
            const float s0 = bf_lo(sv) * 1.4426950408889634f, s1 = bf_hi(sv) * 1.4426950408889634f;
            float m_new = fmaxf(m_run, fmaxf(s0, s1));
            const bool grow = __any_sync(0xffffffffu, (diag && (m_new > m_run)));
            if (lane == 0) mbar_arrive(bar_empty + s * 8);
            if (grow) {
                float al = ex2(m_run - m_new);
                float a0 = __shfl_sync(0xffffffffu, al, src0), a1 = __shfl_sync(0xffffffffu, al, src1);
#pragma unroll
                for (int c = 0; c < 8; c++) { o[c][0] *= a0; o[c][1] *= a1; o[c][2] *= a0; o[c][3] *= a1; }
                l_run *= al;
                m_run = m_new;
            }
            uint32_t pw = pack_bf(ex2(s0 - m_run), ex2(s1 - m_run));
            l_run += bf_lo(pw) + bf_hi(pw);
            uint32_t b0 = odd ? (pw << 16) : (pw & 0xffffu);
            uint32_t b1 = odd ? (pw & 0xffff0000u) : (pw >> 16);
            if (!diag) { b0 = 0u; b1 = 0u; }
            mbar_wait(bar_full + (s + 1) * 8, par);
#pragma unroll
            for (int c = 0; c < 8; c++) {
                uint32_t a[4];
                ldsm4t(a, (base + voff) ^ (c << 4));
                mma16816(o[c], a, b0, b1);
            }
            __syncwarp();
            if (lane == 0) mbar_arrive(bar_empty + (s + 1) * 8);
        }
    }
    PROF(5);
    float acc[4][4];
    uint32_t pa[8][2];
    float rinv;
    {
        const int s = 4 + (warp >> 2);
        mbar_wait(bar_full + s * 8, 1);
        const uint32_t base = sb + OFF_RING + s * TILE_BYTES;
        float sa[4] = {0.f, 0.f, 0.f, 0.f}, sb2[4] = {0.f, 0.f, 0.f, 0.f};
#pragma unroll
        for (int c = 0; c < 8; c += 2) {
            uint32_t a[4], a2[4];
            ldsm4(a, (base + koff) ^ (c << 4));
            ldsm4(a2, (base + koff) ^ ((c + 1) << 4));
            mma16816(sa, a, qf[c][0], qf[c][1]);
            mma16816(sb2, a2, qf[c + 1][0], qf[c + 1][1]);
        }
        const uint32_t sw = pack_bf(odd ? sa[1] + sb2[1] : sa[0] + sb2[0], odd ? sa[3] + sb2[3] : sa[2] + sb2[2]);
        const uint32_t sv = pack_bf(bf_lo(sw) * 0.08838834764831845f, bf_hi(sw) * 0.08838834764831845f);
        const float s0 = bf_lo(sv) * 1.4426950408889634f, s1 = bf_hi(sv) * 1.4426950408889634f;
        int mi_ = __float_as_int(diag ? fmaxf(m_run, fmaxf(s0, s1)) : -INFINITY);
        mi_ ^= (mi_ >> 31) & 0x7fffffff;
        mi_ = __reduce_max_sync(0xffffffffu, mi_);
        mi_ ^= (mi_ >> 31) & 0x7fffffff;
        if (lane == 0) sts32(sb + OFF_ML + warp * 4, mi_);
        bar_cons();
        const float4 m0 = lds_f32x4(sb + OFF_ML), m1 = lds_f32x4(sb + OFF_ML + 16);
        const float mx = fmaxf(fmaxf(fmaxf(m0.x, m0.y), fmaxf(m0.z, m0.w)), fmaxf(fmaxf(m1.x, m1.y), fmaxf(m1.z, m1.w)));
        const float scl = ex2(m_run - mx);
        const uint32_t pw = pack_bf(ex2(s0 - mx), ex2(s1 - mx));
        if (diag) { sts16(sb + SC_P + (warp * 16 + g) * 2, pw); sts16(sb + SC_P + (warp * 16 + g + 8) * 2, pw >> 16); }
        const float lw = warp_sum(diag ? fmaf(l_run, scl, bf_lo(pw) + bf_hi(pw)) : 0.f);
        const float a0 = __shfl_sync(0xffffffffu, scl, src0), a1 = __shfl_sync(0xffffffffu, scl, src1);
        float v[8], u[8];
#pragma unroll
        for (int c = 0; c < 8; c++) {
            v[c] = a0 * o[c][0] + a1 * o[c ^ 1][1];
            u[c] = a0 * o[c][2] + a1 * o[c ^ 1][3];
        }
#pragma unroll
        for (int c = 0; c < 8; c++) {
            if (!(c & 2)) {
                v[c] += __shfl_xor_sync(0xffffffffu, v[c ^ 2], 1);
                u[c] += __shfl_xor_sync(0xffffffffu, u[c ^ 2], 1);
            }
        }
#pragma unroll
        for (int c = 0; c < 2; c++) {
            v[c] += __shfl_xor_sync(0xffffffffu, v[c ^ 4], 2);
            u[c] += __shfl_xor_sync(0xffffffffu, u[c ^ 4], 2);
        }
        const uint32_t dst = sb + SC_OP + (warp * 128 + 16 * t4 + g) * 4;
        sts_f32(dst, v[0]); sts_f32(dst + 32, v[1]); sts_f32(dst + 256, u[0]); sts_f32(dst + 288, u[1]);
        if (lane == 0) sts_f32(sb + OFF_ML + 32 + warp * 4, lw);
        mbar_wait(bar_help, 0);
        bar_cons();
        const float4 l0 = lds_f32x4(sb + OFF_ML + 32), l1 = lds_f32x4(sb + OFF_ML + 48);
        rinv = rcp_fast(((l0.x + l0.y) + (l0.z + l0.w)) + ((l1.x + l1.y) + (l1.z + l1.w)));
#pragma unroll
        for (int i = 0; i < 4; i++) acc[i][0] = acc[i][1] = acc[i][2] = acc[i][3] = 0.f;
#pragma unroll
        for (int w = 0; w < 8; w++) {
            const float2 x0 = lds_f32x2(sb + SC_OP + (w * 128 + 16 * warp + 2 * t4) * 4), x1 = lds_f32x2(sb + SC_OP + (w * 128 + 16 * warp + 8 + 2 * t4) * 4);
            acc[2 * (w & 1)][0] += x0.x; acc[2 * (w & 1)][1] += x0.y;
            acc[2 * (w & 1) + 1][0] += x1.x; acc[2 * (w & 1) + 1][1] += x1.y;
        }
#pragma unroll
        for (int ks = 0; ks < 8; ks++) { pa[ks][0] = lds32(sb + SC_P + (8 * ks + t4) * 4); pa[ks][1] = lds32(sb + SC_P + (8 * ks + 4 + t4) * 4); }
    }
    PROF(20);
    const int mt = warp < 2 ? warp : warp + 2;
    {
        const uint32_t va = pin(sb + OFF_RING + 6 * TILE_BYTES + (warp >> 2) * (TILE_BYTES / 2) + (8 * (mi & 1) + r8) * 128 + (((2 * (warp & 3) + (mi >> 1)) ^ r8) << 4));
        const uint32_t vbar = pin(bar_v + (warp >> 2) * 8);
        uint32_t* const o_dst = pin(slot(SL_O + (cta >> 4), g) + (cta & 15) * 64 + warp * 8 + 2 * t4);
#pragma unroll
        for (int tl = 0; tl < 2; tl++) {
            mbar_wait(vbar + tl * 16, 0);
            uint32_t r[4][4];
#pragma unroll
            for (int ks = 0; ks < 4; ks++) ldsm4t(r[ks], va + tl * TILE_BYTES + ks * 2048);
#pragma unroll
            for (int ks = 0; ks < 4; ks++) {
                const uint32_t a[4] = {pa[4 * tl + ks][0], 0u, pa[4 * tl + ks][1], 0u};
                mma16816(acc[2 * (ks & 1)], a, r[ks][0], r[ks][1]);
                mma16816(acc[2 * (ks & 1) + 1], a, r[ks][2], r[ks][3]);
            }
        }
        stg_relaxed2_if(g < 2, o_dst, ~pack_bf((acc[0][0] + acc[2][0]) * rinv, (acc[0][1] + acc[2][1]) * rinv),
                        ~pack_bf((acc[1][0] + acc[3][0]) * rinv, (acc[1][1] + acc[3][1]) * rinv));
    }
    PROF(7);
    const int side = lds32(sb + OFF_SIDE);
    const uint32_t red_st = pin(sb + SC_E4 + ((warp * 4 + 2 * ((lane >> 3) & 1) + (lane >> 4)) * 8 + (lane & 7)) * 4);
    const uint32_t red_ld = pin(sb + SC_E4 + (lane & 15) * 8);
    const uint32_t* const in1 = pin(slot(SL_P1 + own, side) + tid * 4);
    const uint32_t* const in2a = pin(slot(SL_P2 + 2 * own, side) + tid * 4);
    const uint32_t* const in2b = pin(slot(SL_P2 + 2 * own + 1, side) + tid * 4);
    uint32_t* const out_dst = pin((uint32_t*)(p.out + ((lane >> 2) & 3) * D + 8 * own) + t4);
    uint32_t* const x1_dst = pin(slot(SL_X1 + own / 30, lane >> 4) + (own % 30) * 32 + (lane & 15));
    uint32_t* const rst = pin(tid >= 32 && tid < 56 ? mod_slot(lane >> 2, own, lane & 3) : own < 32 && tid == 64 ? g_clr + own * 4 : own < 16 && tid == 96 ? g_phase + own * 32 : nullptr);
    const uint32_t xw = lds32(sb + OWN_X + (lane & 15) * 4), ga_w = lds32(sb + OWN_GA + (lane & 15) * 4);
    uint32_t cs[15];
    uint32_t* dst2[5];
    uint32_t w2a[5];
#pragma unroll
    for (int j = 0; j < 10; j++) cs[j] = lds32(sb + OFF_VB + ((g & 1) * 4 + (g >> 1)) * VEC_STRIDE + warp * 160 + t4 * 4 + j * 16);
#pragma unroll
    for (int i = 0; i < 5; i++) {
        cs[10 + i] = lds32(sb + OFF_VB + (g >> 1) * VEC_STRIDE + warp * 160 + (g & 1) * 16 + t4 * 4 + i * 32);
        const uint2 t = lds64(sb + OFF_TAB2 + warp * 40 + i * 8);
        dst2[i] = slot_ptr((t4 < 2 ? t.x : t.y) + g * 16 + (t4 & 1) * 8);
        const int cc = 2 * (warp * 5 + i) + (mi & 1);
        w2a[i] = pin(sb + X_W2 + (cc >> 3) * 4096 + (r8 + 8 * (mi >> 1)) * 128 + (((cc & 7) ^ r8) << 4));
    }
    const uint32_t piv = lds32(sb + OFF_STAT + (g >> 1) * 8);
    const uint32_t* const xin = pin(slot(SL_X1 + warp / 3, side) + ((warp % 3) * 10 + (g & 1)) * 32 + (g >> 1) * 4 + t4);
    const uint32_t w1a = pin(sb + X_W1 + (warp * 80 + r8 + 8 * (mi >> 1)) * 64 + (((mi & 1) ^ ((r8 >> 1) & 3)) << 4));
    const uint32_t w1bar = pin(bar_w1 + (warp >> 1) * 8), w2bar = pin(bar_w2 + (warp + (warp >> 2)) * 8);
    const uint32_t wbar = pin(NB_O + warp);
    const uint32_t ab_st = pin(sb + SC_AB + warp * 1024 + lane * 16), y_st = pin(sb + SC_Y + warp * 512 + lane * 8), s_st = pin(sb + SC_ST + (t4 * 8 + warp) * 8);
    const uint32_t h_ld = pin(sb + SC_H1 + ((g & 3) ^ (2 * (f & 1) + ((f >> 1) & 1))) * 64 + t4 * 16);
    {
        const int kap = 2 * (head & 1) + ((head >> 1) & 1);
        const uint32_t wa = pin(sb + X_WO + (mt >> 1) * (DH * 64) + (r8 + 8 * (mi >> 1)) * 64 + ((((mt & 1) * 2 + (mi & 1)) ^ ((r8 >> 1) & 3)) << 4));
        const uint32_t oa = pin(sb + OFF_O + ((g & 3) ^ kap) * O_STRIDE + t4 * 8);
        uint32_t* dst[4];
#pragma unroll
        for (int i = 0; i < 2; i++) {
            const uint2 t = lds64(sb + OFF_TAB1 + (bown * 20 + 2 * mt + (warp < 2 ? 4 * i : 0)) * 4);
            dst[2 * i] = slot_ptr(t.x + g * 16 + t4 * 8);
            dst[2 * i + 1] = slot_ptr(t.y + g * 16 + t4 * 8);
        }
        PROF(6);
        const uint32_t wobar = pin(bar_wo + (mt >> 1) * 8);
        asm volatile("bar.sync %0, 64;" ::"r"(wbar) : "memory");
        uint2 ob[8];
#pragma unroll
        for (int ks = 0; ks < 8; ks++) ob[ks] = lds64(oa + ks * 32);
#pragma unroll
        for (int m = 0; m < 2; m++) {
            if (m == 0 || warp < 2) {
                mbar_wait(wobar + m * 8, 0);
                PROF(8);
                uint32_t wf[8][4];
#pragma unroll
                for (int ks = 0; ks < 8; ks++) ldsm4t(wf[ks], wa + m * (DH * 64) + ks * 1024);
                float c[4][4];
#pragma unroll
                for (int ks = 0; ks < 8; ks++) {
                    if (ks < 4) c[ks][0] = c[ks][1] = c[ks][2] = c[ks][3] = 0.f;
                    mma16816(c[ks & 3], wf[ks], ob[ks].x, ob[ks].y);
                }
                stg_relaxed2_if(t4 < 2, dst[2 * m], flag((c[0][0] + c[1][0]) + (c[2][0] + c[3][0])), flag((c[0][1] + c[1][1]) + (c[2][1] + c[3][1])));
                stg_relaxed2_if(t4 < 2, dst[2 * m + 1], flag((c[0][2] + c[1][2]) + (c[2][2] + c[3][2])), flag((c[0][3] + c[1][3]) + (c[2][3] + c[3][3])));
            }
        }
    }
    PROF(9);
    uint32_t x1w = 0;
    if (is_owner) {
        uint4 v;
        for (int it = 0;; it++) {
            v = ldg_relaxed(in1);
            if (__all_sync(0xffffffffu, and3(and3(v.x, v.y, v.z), v.w, 1u))) break;
            if (it > SPIN_LIMIT) __trap();
        }
        PROF(11);
        const float s0 = __uint_as_float(v.x) + __shfl_xor_sync(0xffffffffu, __uint_as_float(v.z), 8);
        const float s1 = __uint_as_float(v.y) + __shfl_xor_sync(0xffffffffu, __uint_as_float(v.w), 8);
        sts_f32(red_st, s0 + __shfl_xor_sync(0xffffffffu, s1, 16));
        nbar_sync<NB_E4, 256>();
        if (warp == 0) {
            float2 a[8];
#pragma unroll
            for (int w = 0; w < 8; w++) a[w] = lds_f32x2(red_ld + w * 128);
            const uint32_t aw = pack_bf(((a[0].x + a[1].x) + (a[2].x + a[3].x)) + ((a[4].x + a[5].x) + (a[6].x + a[7].x)),
                                        ((a[0].y + a[1].y) + (a[2].y + a[3].y)) + ((a[4].y + a[5].y) + (a[6].y + a[7].y)));
            x1w = bf2_add(xw, bf2_mul(ga_w, aw));
            stg_relaxed(x1_dst, x1w ^ 0x80008000u);
            if (lane == 0) mbar_arrive(bar_x1);
        }
        if (rst) stg_zero4(rst);
    }
    PROF(12);
    if (is_f) {
        uint32_t f1[5][2][4], f2[5][2][4];
        uint32_t d[6];
        auto load_x1 = [&] {
#pragma unroll
            for (int i = 0; i < 5; i++) d[i] = ldg_relaxed32(xin + i * 64);
        };
        auto have_x1 = [&] { return __all_sync(0xffffffffu, __vimin3_u32(__vimin3_u32(d[0], d[1], d[2]), d[3], d[4]) != 0u); };
        mbar_wait(w1bar, 0);
        load_x1();
        {
#pragma unroll
            for (int i = 0; i < 5; i++) { ldsm4t(f1[i][0], w1a + i * 1024); ldsm4t(f1[i][1], (w1a ^ 32) + i * 1024); }
            float c[2][4];
#pragma unroll
            for (int m = 0; m < 2; m++) c[m][0] = c[m][1] = c[m][2] = c[m][3] = 0.f;
#pragma unroll
            for (int i = 0; i < 5; i++) { mma16816(c[0], f1[i][0], cs[2 * i], cs[2 * i + 1]); mma16816(c[1], f1[i][1], cs[2 * i], cs[2 * i + 1]); }
#pragma unroll
            for (int i = 0; i < 5; i++) { cs[2 * i] = pin(odd ? 0u : cs[10 + i]); cs[2 * i + 1] = pin(odd ? cs[10 + i] : 0u); }
#pragma unroll
            for (int m = 0; m < 2; m++) sts128(ab_st + m * 512, make_uint4(__float_as_uint(c[m][0]), __float_as_uint(c[m][1]), __float_as_uint(c[m][2]), __float_as_uint(c[m][3])));
            nbar_arrive<NB_AB, 320>();
            d[0] |= __float_as_uint(c[1][3]) & (side >> 1);
        }
        PROF(10);
#pragma unroll 1
        for (int it = 0; !have_x1(); it++) {
            load_x1();
            if (it > SPIN_LIMIT) __trap();
        }
        PROF(13);
        {
            float y[2][4], st[4] = {0.f, 0.f, 0.f, 0.f};
#pragma unroll
            for (int m = 0; m < 2; m++) y[m][0] = y[m][1] = y[m][2] = y[m][3] = 0.f;
#pragma unroll
            for (int i = 0; i < 5; i++) d[i] = bf2_add(d[i], piv);
            d[5] = 0u;
#pragma unroll
            for (int i = 0; i < 5; i++) {
                if (i < 3) {
                    const uint32_t a[4] = {d[2 * i], 0x3f803f80u, d[2 * i + 1], 0x3f803f80u};
                    mma16816(st, a, d[2 * i], d[2 * i + 1]);
                }
                const uint32_t y0 = bf2_mul(d[i], cs[2 * i]), y1 = bf2_mul(d[i], cs[2 * i + 1]);
                mma16816(y[0], f1[i][0], y0, y1);
                mma16816(y[1], f1[i][1], y0, y1);
            }
            const float q = odd ? st[1] : st[0];
            const float q2 = q + __shfl_xor_sync(0xffffffffu, q, 4);
            if (diag && !odd) sts_f32x2(s_st, q2, st[2] + st[3]);
#pragma unroll
            for (int m = 0; m < 2; m++) sts_f32x2(y_st + m * 256, y[m][0] + y[m][1], y[m][2] + y[m][3]);
        }
        nbar_arrive<NB_Y, 320>();
        PROF(14);
        mbar_wait(w2bar, 0);
        mbar_wait(w2bar + 8, 0);
#pragma unroll
        for (int i = 0; i < 5; i++) { ldsm4t(f2[i][0], w2a[i]); ldsm4t(f2[i][1], w2a[i] + 2048); }
        asm volatile("bar.sync %0, 96;" ::"r"(wbar) : "memory");
        PROF(15);
        {
            const uint4 hb = lds128(h_ld);
            float c[5][4];
#pragma unroll
            for (int i = 0; i < 5; i++) { c[i][0] = c[i][1] = c[i][2] = c[i][3] = 0.f; mma16816(c[i], f2[i][0], hb.x, hb.y); }
#pragma unroll
            for (int i = 0; i < 5; i++) {
                mma16816(c[i], f2[i][1], hb.z, hb.w);
                stg_relaxed2_if(true, dst2[i], flag(t4 < 2 ? c[i][0] : c[i][2]), flag(t4 < 2 ? c[i][1] : c[i][3]));
            }
        }
    }
    PROF(16);
    if (is_owner) {
        const uint32_t b2w = lds32(sb + OWN_B2 + (lane & 15) * 4), gb_ld = pin(sb + OWN_GB + (lane & 15) * 4);
        const bool two = tid < NF * 8 - 256;
        uint4 v, w = make_uint4(1, 1, 1, 1);
        for (int it = 0;; it++) {
            ldg_relaxed_if(two, w, in2b);
            v = ldg_relaxed(in2a);
            if (__all_sync(0xffffffffu, and3(and3(v.x, v.y, v.z), and3(v.w, w.x, w.y), and3(w.z, w.w, 1u)))) break;
            if (it > SPIN_LIMIT) __trap();
        }
        PROF(17);
        const float s0 = (__uint_as_float(v.x) + __uint_as_float(w.x)) + __shfl_xor_sync(0xffffffffu, __uint_as_float(v.z) + __uint_as_float(w.z), 8);
        const float s1 = (__uint_as_float(v.y) + __uint_as_float(w.y)) + __shfl_xor_sync(0xffffffffu, __uint_as_float(v.w) + __uint_as_float(w.w), 8);
        sts_f32(red_st + (SC_E6 - SC_E4), s0 + __shfl_xor_sync(0xffffffffu, s1, 16));
        if (warp != 0) {
            nbar_arrive<NB_E6, 288>();
        } else {
            nbar_sync<NB_E6, 288>();
            float2 a[8];
#pragma unroll
            for (int i = 0; i < 8; i++) a[i] = lds_f32x2(red_ld + (SC_E6 - SC_E4) + i * 128);
            const uint32_t gb_w = lds32(gb_ld);
            const uint32_t aw = pack_bf(((a[0].x + a[1].x) + (a[2].x + a[3].x)) + ((a[4].x + a[5].x) + (a[6].x + a[7].x)),
                                        ((a[0].y + a[1].y) + (a[2].y + a[3].y)) + ((a[4].y + a[5].y) + (a[6].y + a[7].y)));
            x1w = bf2_add(x1w, bf2_mul(gb_w, bf2_add(aw, b2w)));
            if (lane < 16) asm volatile("st.global.u32 [%0], %1;" ::"l"(out_dst), "r"(x1w) : "memory");
        }
    }
    PROF(18);
    PROF_DUMP;
}

typedef CUresult (*EncodeFn)(CUtensorMap*, CUtensorMapDataType, cuuint32_t, void*, const cuuint64_t*, const cuuint64_t*, const cuuint32_t*,
                             const cuuint32_t*, CUtensorMapInterleave, CUtensorMapSwizzle, CUtensorMapL2promotion, CUtensorMapFloatOOBfill);

static CUtensorMap make_map(EncodeFn enc, const void* ptr, int cols, int rows, int box_cols, int box_rows, CUtensorMapSwizzle sw,
                            CUtensorMapL2promotion promo = CU_TENSOR_MAP_L2_PROMOTION_NONE) {
    CUtensorMap m;
    cuuint64_t dims[2] = {(cuuint64_t)cols, (cuuint64_t)rows};
    cuuint64_t strides[1] = {(cuuint64_t)cols * 2};
    cuuint32_t box[2] = {(cuuint32_t)box_cols, (cuuint32_t)box_rows};
    cuuint32_t es[2] = {1, 1};
    enc(&m, CU_TENSOR_MAP_DATA_TYPE_BFLOAT16, 2, const_cast<void*>(ptr), dims, strides, box, es, CU_TENSOR_MAP_INTERLEAVE_NONE, sw,
        promo, CU_TENSOR_MAP_FLOAT_OOB_FILL_NONE);
    return m;
}

}

extern "C" void kernel_launch(void* const* d_in, const int* in_sizes, int n_in, void* d_out, int out_size) {
    (void)in_sizes; (void)n_in; (void)out_size;
    static EncodeFn enc = nullptr;
    if (!enc) {
        void* fn = nullptr;
        cudaDriverEntryPointQueryResult qr;
        cudaGetDriverEntryPoint("cuTensorMapEncodeTiled", &fn, cudaEnableDefault, &qr);
        enc = (EncodeFn)fn;
        cudaFuncSetAttribute(fused_kernel, cudaFuncAttributeMaxDynamicSharedMemorySize, SMEM_BYTES);
    }
    Params p;
    p.x = (const __nv_bfloat16*)d_in[0];
    p.kc = (const __nv_bfloat16*)d_in[1];
    p.vc = (const __nv_bfloat16*)d_in[2];
    p.b1 = (const __nv_bfloat16*)d_in[7];
    p.b2 = (const __nv_bfloat16*)d_in[9];
    p.c = (const __nv_bfloat16*)d_in[10];
    p.out = (__nv_bfloat16*)d_out;
    CUtensorMap tm_wmod = make_map(enc, d_in[11], NMOD, D, 32, 160, CU_TENSOR_MAP_SWIZZLE_64B);
    CUtensorMap tm_wq = make_map(enc, d_in[3], NH * DH, D, 32, 160, CU_TENSOR_MAP_SWIZZLE_64B);
    CUtensorMap tm_wo = make_map(enc, d_in[4], D, NH * DH, 32, 128, CU_TENSOR_MAP_SWIZZLE_64B);
    CUtensorMap tm_w1 = make_map(enc, d_in[6], FF, D, 32, 160, CU_TENSOR_MAP_SWIZZLE_64B);
    CUtensorMap tm_w2 = make_map(enc, d_in[8], D, FF, 64, 32, CU_TENSOR_MAP_SWIZZLE_128B);
    CUtensorMap tm_v = make_map(enc, d_in[2], DH, NB * NH * SK, 64, TILE_KEYS, CU_TENSOR_MAP_SWIZZLE_128B);
    CUtensorMap tm_gb = make_map(enc, d_in[11], NMOD, D, 8, 160, CU_TENSOR_MAP_SWIZZLE_NONE, CU_TENSOR_MAP_L2_PROMOTION_L2_128B);
    fused_kernel<<<NCTA, NTHREADS, SMEM_BYTES>>>(p, tm_wmod, tm_wq, tm_wo, tm_w1, tm_w2, tm_v, tm_gb);
}
```

```cpp
#include <cuda_runtime.h>
#include <cuda.h>
#include <cuda_bf16.h>
#include <stdint.h>

namespace {

constexpr int NB = 4, D = 640, NH = 32, DH = 128, SK = 8192, WIN = 2048, FF = 1728, NMOD = 6 * D;
constexpr int NCTA = 128;
constexpr int NOWN = 80;
constexpr int NF = 54;
constexpr int NTHREADS = 320;
constexpr int TILE_KEYS = 64;
constexpr int TILE_BYTES = TILE_KEYS * DH * 2;
constexpr int NITEM = 2 * WIN / TILE_KEYS;
constexpr int NS = 8;
constexpr int NMODC = 120;
constexpr int SPIN_LIMIT = 1 << 18;
#define INFLIGHT 3
#define WQ_DELAY 100
#define PACE_A 7500
#define PACE_TAU 635
#define PF_END 16
#define PH_FIRST 20
#define PH_LAG 5
#define LAT_T 2100
#define WO_T -1100
#define WO_S 300
#define W1_T 950
#define W2_T 1650
#define GB_T 2500
#define GB_EV 300
#define CLR_CHECK 28000
constexpr int NPROBE = 8, PROBE_END = 10000;
constexpr int SEG_J = 8;

constexpr int OFF_RING = 0;
constexpr int OFF_X = OFF_RING + NS * TILE_BYTES;
constexpr int X_WM = OFF_X;
constexpr int X_WQ = OFF_X + D * 64;
constexpr int X_WO = OFF_X;
constexpr int X_W1 = X_WO + 5 * DH * 64;
constexpr int X_END = X_W1 + D * 64;
constexpr int X_W2 = OFF_RING;
constexpr int X_GB = OFF_RING + 3 * TILE_BYTES;
static_assert(X_WQ + D * 64 <= X_END, "prologue weights must fit");
constexpr int VEC_STRIDE = 1296;
constexpr int OFF_VA = X_END;
constexpr int OFF_VB = OFF_VA + 4 * VEC_STRIDE;
constexpr int OFF_RED = OFF_VB + 4 * VEC_STRIDE;
constexpr int OFF_ML = OFF_RED + 4 * VEC_STRIDE;
constexpr int O_STRIDE = 288;
constexpr int OFF_O = OFF_ML + 64;
constexpr int OFF_Q = OFF_O + 4 * O_STRIDE;
constexpr int OFF_OWN = OFF_Q + 256;
constexpr int OWN_X = OFF_OWN, OWN_B2 = OWN_X + 64, OWN_GA = OWN_B2 + 64, OWN_GB = OWN_GA + 64, OWN_B1 = OWN_GB + 64;
constexpr int OFF_STAT = OWN_B1 + 128;
constexpr int OFF_TAB1 = OFF_STAT + 32;
constexpr int OFF_TAB2 = OFF_TAB1 + NOWN * 4;
constexpr int OFF_SIDE = OFF_TAB2 + NOWN * 4;
constexpr int OFF_BAR = OFF_SIDE + 8;
constexpr int NBAR = 2 * NS + 32;
constexpr int SMEM_BYTES = OFF_BAR + NBAR * 8;
constexpr int SC_OP = OFF_RING + 4 * TILE_BYTES;
constexpr int SC_AB = SC_OP + 4096;
constexpr int SC_Y = SC_AB + 8192;
constexpr int SC_ST = SC_Y + 4096;
constexpr int SC_E4 = SC_ST + 256;
constexpr int SC_E6 = SC_E4 + 1024;
constexpr int SC_P = SC_E6 + 1024;
constexpr int SC_H1 = SC_P + 256;
static_assert(SMEM_BYTES <= 232448, "smem");
static_assert(OFF_BAR % 8 == 0 && OFF_X % 1024 == 0 && X_WQ % 512 == 0 && X_W1 % 512 == 0 && OFF_VA % 16 == 0 && OFF_RED % 16 == 0 && OFF_ML % 16 == 0 && OFF_O % 16 == 0 && OFF_Q % 16 == 0, "align");
constexpr int NB_O = 2  , NB_E4 = 10, NB_E6 = 11, NB_AB = 12, NB_Y = 13;

__device__ uint32_t g_mod[NMODC * 64];
__device__ uint32_t g_q[NCTA * 64];
__device__ uint32_t g_clr[NCTA];
__device__ uint32_t g_phase[16 * 32];
constexpr int SL_P1 = 0;
constexpr int SL_P2 = SL_P1 + NOWN;
constexpr int SL_O = SL_P2 + 2 * NOWN;
constexpr int SL_X1 = SL_O + 8;
constexpr int SL_SIDE = SL_X1 + 3;
static_assert(SL_SIDE < 256, "one 2 MB page");
__device__ uint32_t g_slots[2 * 256 * 2048];
__device__ __forceinline__ uint32_t* slot(int i, int side) {
    const size_t base = ((size_t)g_slots + 0x1fffff) & ~(size_t)0x1fffff;
    return (uint32_t*)base + i * 2048 + (((__popc(i & 0x59) ^ side) & 1) << 10);
}
#define PROF_DECL
#define HPROF(i) do { } while (0)
#define PROF(i) do { } while (0)
#define PROF_DUMP do { } while (0)

__device__ __forceinline__ uint32_t smem_u32(const void* p) { return (uint32_t)__cvta_generic_to_shared(p); }
__device__ __forceinline__ void mbar_init(uint32_t bar, uint32_t cnt) { asm volatile("mbarrier.init.shared::cta.b64 [%0], %1;" ::"r"(bar), "r"(cnt) : "memory"); }
__device__ __forceinline__ void mbar_expect_tx(uint32_t bar, uint32_t bytes) { asm volatile("mbarrier.arrive.expect_tx.shared::cta.b64 _, [%0], %1;" ::"r"(bar), "r"(bytes) : "memory"); }
__device__ __forceinline__ void mbar_arrive(uint32_t bar) { asm volatile("mbarrier.arrive.shared::cta.b64 _, [%0];" ::"r"(bar) : "memory"); }
__device__ __forceinline__ void mbar_wait(uint32_t bar, uint32_t parity) {
    uint32_t ok;
    int it = 0;
    while (true) {
        asm volatile("{\n.reg .pred p;\nmbarrier.try_wait.parity.shared::cta.b64 p, [%1], %2;\nselp.u32 %0, 1, 0, p;\n}" : "=r"(ok) : "r"(bar), "r"(parity) : "memory");
        if (ok) break;
        if (++it > SPIN_LIMIT) __trap();
    }
}
__device__ __forceinline__ void bulk_load(uint32_t dst, const void* src, uint32_t bytes, uint32_t bar, uint64_t pol) {
    asm volatile("cp.async.bulk.shared::cluster.global.mbarrier::complete_tx::bytes.L2::cache_hint [%0], [%1], %2, [%3], %4;"
                 ::"r"(dst), "l"(src), "r"(bytes), "r"(bar), "l"(pol) : "memory");
}
__device__ __forceinline__ void bar_cons() { asm volatile("bar.sync 1, 256;" ::: "memory"); }
template <int ID, int N> __device__ __forceinline__ void nbar_sync() { asm volatile("bar.sync %0, %1;" ::"n"(ID), "n"(N) : "memory"); }
template <int ID, int N> __device__ __forceinline__ void nbar_arrive() { asm volatile("bar.arrive %0, %1;" ::"n"(ID), "n"(N) : "memory"); }
__device__ __forceinline__ bool mbar_test(uint32_t bar, uint32_t parity) {
    uint32_t ok;
    asm volatile("{\n.reg .pred p;\nmbarrier.test_wait.parity.shared::cta.b64 p, [%1], %2;\nselp.u32 %0, 1, 0, p;\n}" : "=r"(ok) : "r"(bar), "r"(parity) : "memory");
    return ok;
}
__device__ __forceinline__ uint32_t pin(uint32_t v) { asm volatile("" : "+r"(v)); return v; }
template <class T> __device__ __forceinline__ T pin_hard(T v) { return __shfl_sync(0xffffffffu, v, threadIdx.x & 31); }
template <class T> __device__ __forceinline__ T* pin(T* v) { asm volatile("" : "+l"(v)); return v; }
__device__ __forceinline__ void ldsm4(uint32_t (&a)[4], uint32_t addr) {
    asm volatile("ldmatrix.sync.aligned.m8n8.x4.shared.b16 {%0,%1,%2,%3}, [%4];" : "=r"(a[0]), "=r"(a[1]), "=r"(a[2]), "=r"(a[3]) : "r"(addr) : "memory");
}
__device__ __forceinline__ void ldsm4t(uint32_t (&a)[4], uint32_t addr) {
    asm volatile("ldmatrix.sync.aligned.m8n8.x4.trans.shared.b16 {%0,%1,%2,%3}, [%4];" : "=r"(a[0]), "=r"(a[1]), "=r"(a[2]), "=r"(a[3]) : "r"(addr) : "memory");
}
__device__ __forceinline__ void mma16816(float (&c)[4], const uint32_t (&a)[4], uint32_t b0, uint32_t b1) {
    asm volatile("mma.sync.aligned.m16n8k16.row.col.f32.bf16.bf16.f32 {%0,%1,%2,%3}, {%4,%5,%6,%7}, {%8,%9}, {%0,%1,%2,%3};"
                 : "+f"(c[0]), "+f"(c[1]), "+f"(c[2]), "+f"(c[3]) : "r"(a[0]), "r"(a[1]), "r"(a[2]), "r"(a[3]), "r"(b0), "r"(b1));
}
__device__ __forceinline__ uint32_t lds32(uint32_t addr) { uint32_t v; asm volatile("ld.shared.u32 %0, [%1];" : "=r"(v) : "r"(addr) : "memory"); return v; }
__device__ __forceinline__ float lds_f32(uint32_t addr) { float v; asm volatile("ld.shared.f32 %0, [%1];" : "=f"(v) : "r"(addr) : "memory"); return v; }
__device__ __forceinline__ float2 lds_f32x2(uint32_t addr) { float2 v; asm volatile("ld.shared.v2.f32 {%0,%1}, [%2];" : "=f"(v.x), "=f"(v.y) : "r"(addr) : "memory"); return v; }
__device__ __forceinline__ float4 lds_f32x4(uint32_t addr) { float4 v; asm volatile("ld.shared.v4.f32 {%0,%1,%2,%3}, [%4];" : "=f"(v.x), "=f"(v.y), "=f"(v.z), "=f"(v.w) : "r"(addr) : "memory"); return v; }
__device__ __forceinline__ uint2 lds64(uint32_t addr) { uint2 v; asm volatile("ld.shared.v2.u32 {%0,%1}, [%2];" : "=r"(v.x), "=r"(v.y) : "r"(addr) : "memory"); return v; }
__device__ __forceinline__ uint4 lds128(uint32_t addr) { uint4 v; asm volatile("ld.shared.v4.u32 {%0,%1,%2,%3}, [%4];" : "=r"(v.x), "=r"(v.y), "=r"(v.z), "=r"(v.w) : "r"(addr) : "memory"); return v; }
__device__ __forceinline__ void sts16(uint32_t addr, uint32_t v) { asm volatile("st.shared.b16 [%0], %1;" ::"r"(addr), "h"((unsigned short)v) : "memory"); }
__device__ __forceinline__ void sts32(uint32_t addr, uint32_t v) { asm volatile("st.shared.u32 [%0], %1;" ::"r"(addr), "r"(v) : "memory"); }
__device__ __forceinline__ void sts_f32(uint32_t addr, float v) { asm volatile("st.shared.f32 [%0], %1;" ::"r"(addr), "f"(v) : "memory"); }
__device__ __forceinline__ void sts_f32x2(uint32_t addr, float a, float b) { asm volatile("st.shared.v2.f32 [%0], {%1,%2};" ::"r"(addr), "f"(a), "f"(b) : "memory"); }
__device__ __forceinline__ void sts128(uint32_t addr, uint4 v) { asm volatile("st.shared.v4.u32 [%0], {%1,%2,%3,%4};" ::"r"(addr), "r"(v.x), "r"(v.y), "r"(v.z), "r"(v.w) : "memory"); }
__device__ __forceinline__ uint4 ldg_relaxed(const uint32_t* p) {
    uint4 v;
    asm volatile("ld.relaxed.gpu.global.v4.u32 {%0,%1,%2,%3}, [%4];" : "=r"(v.x), "=r"(v.y), "=r"(v.z), "=r"(v.w) : "l"(p) : "memory");
    return v;
}
__device__ __forceinline__ void ldg_relaxed_if(bool on, uint4& v, const uint32_t* p) {
    asm volatile("{\n.reg .pred q;\nsetp.ne.u32 q, %5, 0;\n@q ld.relaxed.gpu.global.v4.u32 {%0,%1,%2,%3}, [%4];\n}"
                 : "+r"(v.x), "+r"(v.y), "+r"(v.z), "+r"(v.w) : "l"(p), "r"((uint32_t)on) : "memory");
}
__device__ __forceinline__ void stg_relaxed2_if(bool on, uint32_t* p, uint32_t a, uint32_t b) {
    asm volatile("{\n.reg .pred q;\nsetp.ne.u32 q, %3, 0;\n@q st.relaxed.gpu.global.v2.u32 [%0], {%1,%2};\n}" ::"l"(p), "r"(a), "r"(b), "r"((uint32_t)on) : "memory");
}
__device__ __forceinline__ uint32_t ldg_relaxed32(const uint32_t* p) { uint32_t v; asm volatile("ld.relaxed.gpu.global.u32 %0, [%1];" : "=r"(v) : "l"(p) : "memory"); return v; }
__device__ __forceinline__ void stg_relaxed(uint32_t* p, uint32_t v) { asm volatile("st.relaxed.gpu.global.u32 [%0], %1;" ::"l"(p), "r"(v) : "memory"); }
__device__ __forceinline__ void stg_zero4(uint32_t* p) { asm volatile("st.relaxed.gpu.global.v4.u32 [%0], {%1,%1,%1,%1};" ::"l"(p), "r"(0u) : "memory"); }
__device__ __forceinline__ bool ready(const uint4& v) { return (v.x != 0u) & (v.y != 0u) & (v.z != 0u) & (v.w != 0u); }
__device__ __forceinline__ uint4 inv4(const uint4& v) { return make_uint4(~v.x, ~v.y, ~v.z, ~v.w); }
__device__ __forceinline__ uint32_t pack_bf(float lo, float hi) {
    uint32_t r;
    asm("cvt.rn.bf16x2.f32 %0, %1, %2;" : "=r"(r) : "f"(hi), "f"(lo));
    return r;
}
__device__ __forceinline__ float bfr(float x) { return __uint_as_float(pack_bf(0.f, x) & 0xffff0000u); }
__device__ __forceinline__ float bf_lo(uint32_t w) { return __uint_as_float(w << 16); }
__device__ __forceinline__ float bf_hi(uint32_t w) { return __uint_as_float(w & 0xffff0000u); }
__device__ __forceinline__ float bf2f(__nv_bfloat16 v) { return __bfloat162float(v); }
__device__ __forceinline__ float ex2(float x) { float y; asm("ex2.approx.ftz.f32 %0, %1;" : "=f"(y) : "f"(x)); return y; }
__device__ __forceinline__ float rcp_fast(float x) { float y; asm("rcp.approx.ftz.f32 %0, %1;" : "=f"(y) : "f"(x)); return y; }
__device__ __forceinline__ float rsqrt_fast(float x) { float y; asm("rsqrt.approx.ftz.f32 %0, %1;" : "=f"(y) : "f"(x)); return y; }
__device__ __forceinline__ float sqrt_fast(float x) { float y; asm("sqrt.approx.f32 %0, %1;" : "=f"(y) : "f"(x)); return y; }
__device__ __forceinline__ uint32_t bf2_add(uint32_t a, uint32_t b) { uint32_t r; asm("add.rn.bf16x2 %0, %1, %2;" : "=r"(r) : "r"(a), "r"(b)); return r; }
__device__ __forceinline__ uint32_t bf2_sub(uint32_t a, uint32_t b) { uint32_t r; asm("sub.rn.bf16x2 %0, %1, %2;" : "=r"(r) : "r"(a), "r"(b)); return r; }
__device__ __forceinline__ uint32_t bf2_mul(uint32_t a, uint32_t b) { uint32_t r; asm("mul.rn.bf16x2 %0, %1, %2;" : "=r"(r) : "r"(a), "r"(b)); return r; }
__device__ __forceinline__ uint32_t gtime32() { uint32_t c; asm volatile("mov.u32 %0, %%globaltimer_lo;" : "=r"(c)); return c; }
__device__ __forceinline__ uint32_t clock32() { uint32_t c; asm volatile("mov.u32 %0, %%clock;" : "=r"(c)); return c; }

__device__ __forceinline__ float warp_sum(float v) {
#pragma unroll
    for (int o = 16; o > 0; o >>= 1) v += __shfl_xor_sync(0xffffffffu, v, o);
    return v;
}

struct Params {
    const __nv_bfloat16 *x, *kc, *vc, *b1, *b2, *c;
    __nv_bfloat16* out;
};

__device__ __forceinline__ void tma2d(uint32_t dst, const CUtensorMap* tm, int x, int y, uint32_t bar) {
    asm volatile("cp.async.bulk.tensor.2d.shared::cluster.global.mbarrier::complete_tx::bytes [%0], [%1, {%2, %3}], [%4];"
                 ::"r"(dst), "l"(tm), "r"(x), "r"(y), "r"(bar) : "memory");
}

__device__ __forceinline__ void tma2d_hint(uint32_t dst, const CUtensorMap* tm, int x, int y, uint32_t bar, uint64_t pol) {
    asm volatile("cp.async.bulk.tensor.2d.shared::cluster.global.mbarrier::complete_tx::bytes.L2::cache_hint [%0], [%1, {%2, %3}], [%4], %5;"
                 ::"r"(dst), "l"(tm), "r"(x), "r"(y), "r"(bar), "l"(pol) : "memory");
}
__device__ __forceinline__ uint32_t flag(float v) { return __float_as_uint(v) | 1u; }
__device__ __forceinline__ uint32_t and3(uint32_t a, uint32_t b, uint32_t c) { uint32_t r; asm("lop3.b32 %0, %1, %2, %3, 0x80;" : "=r"(r) : "r"(a), "r"(b), "r"(c)); return r; }
__device__ __forceinline__ uint32_t* slot_ptr(uint32_t lo) {
    uint32_t* r;
    asm volatile("mov.b64 %0, {%1, %2};" : "=l"(r) : "r"(lo), "r"((uint32_t)((size_t)slot(0, 0) >> 32)));
    return r;
}

__device__ __forceinline__ void load_bfrag(uint32_t vec, int stride, int k0, int g, int t, uint32_t& b0, uint32_t& b1) {
    uint32_t a = vec + (g & 3) * stride + (k0 + 2 * t) * 2;
    b0 = lds32(a);
    b1 = lds32(a + 16);
}

__device__ __forceinline__ void ln_finish(float pivot, float sum, float sumsq, uint32_t& m2, float& rden) {
    float dm = sum * (1.f / D);
    float var = fmaxf(sumsq * (1.f / D) - dm * dm, 0.f);
    float mean = pivot + dm;
    m2 = pack_bf(mean, mean);
    rden = rcp_fast(bfr(sqrt_fast(bfr(bfr(var) + 1e-5f))));
}
__device__ __forceinline__ uint32_t ln_mod_pair(uint32_t xw, uint32_t cw, uint32_t sw, uint32_t m2, float rden) {
    uint32_t d = bf2_sub(xw, m2);
    uint32_t ln = pack_bf(bf_lo(d) * rden, bf_hi(d) * rden);
    return bf2_add(bf2_mul(ln, bf2_add(cw, 0x3f803f80u)), sw);
}
__device__ __forceinline__ uint4 ln_mod4(const uint4& x, const uint4& c, const uint4& s, uint32_t m2, float rden) {
    return make_uint4(ln_mod_pair(x.x, c.x, s.x, m2, rden), ln_mod_pair(x.y, c.y, s.y, m2, rden),
                      ln_mod_pair(x.z, c.z, s.z, m2, rden), ln_mod_pair(x.w, c.w, s.w, m2, rden));
}
__device__ __forceinline__ void acc_stats(const uint4& v, float pv, float& s, float& q) {
    const float a0 = bf_lo(v.x) - pv, a1 = bf_hi(v.x) - pv, a2 = bf_lo(v.y) - pv, a3 = bf_hi(v.y) - pv;
    const float a4 = bf_lo(v.z) - pv, a5 = bf_hi(v.z) - pv, a6 = bf_lo(v.w) - pv, a7 = bf_hi(v.w) - pv;
    s += ((a0 + a1) + (a2 + a3)) + ((a4 + a5) + (a6 + a7));
    q += (fmaf(a0, a0, a1 * a1) + fmaf(a2, a2, a3 * a3)) + (fmaf(a4, a4, a5 * a5) + fmaf(a6, a6, a7 * a7));
}
__device__ __forceinline__ uint32_t* mod_slot(int kind, int j, int b) { return g_mod + (kind * 20 + (j >> 2)) * 64 + b * 16 + (j & 3) * 4; }

template <int N>
__device__ __forceinline__ void poll_n(uint4 (&v)[N], const uint32_t* const* ptr, const bool* on) {
    bool pend[N];
#pragma unroll
    for (int i = 0; i < N; i++) pend[i] = on[i];
    int it = 0;
    while (true) {
#pragma unroll
        for (int i = 0; i < N; i++) if (pend[i]) v[i] = ldg_relaxed(ptr[i]);
        bool any = false;
#pragma unroll
        for (int i = 0; i < N; i++) { pend[i] = pend[i] && !ready(v[i]); any |= pend[i]; }
        if (!__any_sync(0xffffffffu, any)) break;
        if (++it > SPIN_LIMIT) __trap();
    }
#pragma unroll
    for (int i = 0; i < N; i++) v[i] = inv4(v[i]);
}
__device__ __forceinline__ uint4 poll1(const uint32_t* p, bool on) {
    uint4 v[1] = {make_uint4(0, 0, 0, 0)};
    const uint32_t* const ptr[1] = {p};
    const bool o[1] = {on};
    poll_n<1>(v, ptr, o);
    return v[0];
}

__device__ __forceinline__ void gelu_stage(uint32_t sb, int m, int lane) {
    const int g = lane >> 2, b = lane & 3;
    const uint32_t y_ld = pin_hard(sb + SC_Y + m * 256 + lane * 8), s_ld = pin_hard(sb + SC_ST + b * 64);
    const uint32_t h_st = pin_hard(sb + SC_H1 + b * 64 + (g >> 1) * 16 + m * 8 + (g & 1) * 2);
    float a0 = 0.f, b0 = lds_f32(sb + OWN_B1 + (16 * m + g) * 4), a1 = 0.f, b1 = lds_f32(sb + OWN_B1 + (16 * m + g + 8) * 4);
    const float piv = bf_hi(lds32(sb + OFF_STAT + b * 8));
    nbar_sync<NB_AB, 320>();
#pragma unroll
    for (int w = 0; w < 8; w++) {
        const float4 t = lds_f32x4(sb + SC_AB + w * 1024 + m * 512 + lane * 16);
        a0 += t.x; b0 += t.y; a1 += t.z; b1 += t.w;
    }
    sts128(sb + SC_AB + m * 512 + lane * 16, make_uint4(__float_as_uint(a0), __float_as_uint(b0), __float_as_uint(a1), __float_as_uint(b1)));
    nbar_sync<NB_Y, 320>();
    float4 q[4];
    float2 y[8];
#pragma unroll
    for (int i = 0; i < 4; i++) q[i] = lds_f32x4(s_ld + i * 16);
#pragma unroll
    for (int w = 0; w < 8; w++) y[w] = lds_f32x2(y_ld + w * 512);
    const float dm = (((q[0].y + q[0].w) + (q[1].y + q[1].w)) + ((q[2].y + q[2].w) + (q[3].y + q[3].w))) * (1.f / D);
    const float sq = ((q[0].x + q[0].z) + (q[1].x + q[1].z)) + ((q[2].x + q[2].z) + (q[3].x + q[3].z));
    const float r = rsqrt_fast(fmaxf(fmaf(-dm, dm, fmaf(sq, 1.f / D, 1e-5f)), 1e-5f));
    const float y0 = ((y[0].x + y[1].x) + (y[2].x + y[3].x)) + ((y[4].x + y[5].x) + (y[6].x + y[7].x));
    const float y1 = ((y[0].y + y[1].y) + (y[2].y + y[3].y)) + ((y[4].y + y[5].y) + (y[6].y + y[7].y));
    const float dmr = piv - bfr(piv - dm);
    const float u0 = fmaf(r, fmaf(dmr, a0, -y0), b0), u1 = fmaf(r, fmaf(dmr, a1, -y1), b1);
    const float e0 = ex2(u0 * fmaf(u0 * u0, -0.044715f * 2.302208198144325f, -2.302208198144325f));
    const float e1 = ex2(u1 * fmaf(u1 * u1, -0.044715f * 2.302208198144325f, -2.302208198144325f));
    sts16(h_st, pack_bf(u0 * rcp_fast(1.f + e0), 0.f));
    sts16(h_st + 4, pack_bf(u1 * rcp_fast(1.f + e1), 0.f));
#pragma unroll
    for (int w = 0; w < 8; w++) asm volatile("bar.arrive %0, 96;" ::"r"(NB_O + w) : "memory");
}

struct Roles { bool is_f, is_owner; int f, own; };
__device__ __forceinline__ Roles roles(int cta) {
    Roles r;
    r.f = (cta * 27) >> 6;
    r.is_f = (((cta + 1) * 27) >> 6) != r.f;
    r.is_owner = !r.is_f || r.f % 9 == 4;
    r.own = r.is_f ? 74 + r.f / 9 : cta - r.f;
    return r;
}

__global__ void __launch_bounds__(NTHREADS, 1)
fused_kernel(const Params p, const __grid_constant__ CUtensorMap tm_wmod, const __grid_constant__ CUtensorMap tm_wq,
             const __grid_constant__ CUtensorMap tm_wo, const __grid_constant__ CUtensorMap tm_w1, const __grid_constant__ CUtensorMap tm_w2,
             const __grid_constant__ CUtensorMap tm_v, const __grid_constant__ CUtensorMap tm_gb) {
    extern __shared__ __align__(1024) unsigned char smem[];
    const uint32_t t_start = gtime32();
    if (threadIdx.x == 0) {
        const uint32_t c_ = blockIdx.x;
        const uint32_t off = ((c_ & 3) << 26) + (c_ >> 2) * (1u << 21) + ((c_ & 12) << 15) + (SK - WIN) * DH * 2;
        asm volatile("cp.async.bulk.prefetch.L2.global.L2::cache_hint [%0], %1, %2;" ::"l"((const char*)p.kc + off), "r"(TILE_BYTES), "l"(0x12f0000000000000ull  ) : "memory");
    }
    const uint32_t sb = smem_u32(smem);
    const int cta = blockIdx.x;
    const int head = cta >> 2, bown = cta & 3;
    const int rot = (8 * head) & (NITEM / 2 - 1);
    const char* const kb = (const char*)(p.kc + ((size_t)(bown * NH + head) * SK + (SK - WIN)) * DH);
    uint64_t pol = 0;
    if (threadIdx.x == 256) {
        mbar_init(sb + OFF_BAR, 1);
        asm volatile("fence.mbarrier_init.release.cluster;" ::: "memory");
        asm volatile("createpolicy.fractional.L2::evict_first.b64 %0, 1.0;" : "=l"(pol));
        mbar_expect_tx(sb + OFF_BAR, TILE_BYTES);
        bulk_load(sb + OFF_RING, kb + (size_t)rot * TILE_BYTES, TILE_BYTES, sb + OFF_BAR, pol);
        if ((((cta + 1) * 5) >> 4) != ((cta * 5) >> 4)) {
            const uint32_t bar = sb + OFF_BAR + 2 * NS * 8;
            mbar_init(bar, 1);
            asm volatile("fence.mbarrier_init.release.cluster;" ::: "memory");
            mbar_expect_tx(bar, D * 64);
#pragma unroll 1
            for (int r = 0; r < D; r += 160) tma2d(sb + X_WM + r * 64, &tm_wmod, 32 * ((cta * 5) >> 4), r, bar);
        }
    }
    const uint32_t bar_full = sb + OFF_BAR, bar_empty = bar_full + NS * 8;
    const uint32_t bar_wm = bar_empty + NS * 8, bar_wq = bar_wm + 8, bar_xfree = bar_wq + 8, bar_wo = bar_xfree + 8  ;
    const uint32_t bar_w1 = bar_wo + 40  , bar_w2 = bar_w1 + 32  , bar_help = bar_w2 + 80, bar_v = bar_help + 8  ;
    const uint32_t bar_gb = bar_v + 32  , bar_x1 = bar_gb + 32;
    const int tid = threadIdx.x, warp = tid >> 5, lane = tid & 31;
    const Roles role = roles(cta);
    const bool is_f = role.is_f, is_owner = role.is_owner;
    const int f = role.f, own = role.own;
    const bool crit = (((cta + 1) * 5) >> 4) != ((cta * 5) >> 4);
    const int mr = cta - ((cta * 5) >> 4);
    const int ml = mr * 31 / 44;
    const bool late = !crit && (mr + 1) * 31 / 44 != ml;
    const int mc = crit ? (cta * 5) >> 4 : ml < 60 ? 40 + ml : 58 + ml;
    const bool gb_own = is_owner && own < 72;

    PROF_DECL
    PROF(0);
    uint4 xa = make_uint4(0, 0, 0, 0), xb = xa, ca0 = xa, ca1 = xa, xs[3] = {xa, xa, xa};
    uint32_t own0 = 0;
    __nv_bfloat16 own2 = __float2bfloat16(0.f);
    if (warp < 8) {
        xa = *(const uint4*)(p.x + (tid & 3) * D + (tid >> 2) * 8);
        ca0 = ((const uint4*)p.c)[tid];
        if (tid < 64) { xb = *(const uint4*)(p.x + (tid & 3) * D + (64 + (tid >> 2)) * 8); ca1 = ((const uint4*)p.c)[256 + tid]; }
        if (warp < 4) {
#pragma unroll
            for (int i = 0; i < 3; i++) if (lane + 32 * i < 80) xs[i] = ((const uint4*)p.x)[warp * 80 + lane + 32 * i];
        } else if (warp == 4) {
            if (is_owner) own0 = *(const uint32_t*)((lane < 16 ? p.x + (lane >> 2) * D : p.b2) + 8 * own + 2 * (lane & 3));
            if (is_f) own2 = p.b1[32 * f + lane];
        }
    }
    const char* const vb = (const char*)(p.vc + ((size_t)(bown * NH + head) * SK + (SK - WIN)) * DH);
    const uint32_t bar_first = crit ? bar_wm : bar_wq;
    if (threadIdx.x == 256) {
        if (!crit) {
            mbar_init(bar_wq, 1);
            asm volatile("fence.mbarrier_init.release.cluster;" ::: "memory");
            mbar_expect_tx(bar_wq, D * 64);
            const uint32_t c0 = clock32();
            while (clock32() - c0 < WQ_DELAY) { }
#pragma unroll
            for (int r = 0; r < D; r += 160) tma2d(sb + X_WQ + r * 64, &tm_wq, 32 * cta, r, bar_wq);
        }
    } else if (threadIdx.x == 0) {
#pragma unroll
        for (int s = 0; s < NS; s++) { if (s) mbar_init(bar_full + s * 8, 1); mbar_init(bar_empty + s * 8, 4); }
        mbar_init(crit ? bar_wq : bar_wm, 1);
        mbar_init(bar_xfree, 1);
#pragma unroll
        for (int i = 0; i < 5; i++) { mbar_init(bar_wo + i * 8, 1); mbar_init(bar_w2 + i * 16, 1); mbar_init(bar_w2 + i * 16 + 8, 1); }
        mbar_init(bar_help, 1); mbar_init(bar_x1, 1);
#pragma unroll
        for (int i = 0; i < 4; i++) { mbar_init(bar_v + i * 8, 1); mbar_init(bar_w1 + i * 8, 1); mbar_init(bar_gb + i * 8, 1); }
        asm volatile("fence.mbarrier_init.release.cluster;" ::: "memory");
    }
    __syncthreads();

    if (warp == 8) {
        if (lane == 0) {
            int tp = NS;
            int sched = PACE_A - NS * PACE_TAU;
#pragma unroll 1
            for (int t = 1; t <= NITEM; t++) {
                if (t == 1) mbar_wait(bar_full, 0);
                if (t == 2) {
                    mbar_wait(bar_first, 0);
                    if (crit) {
                        mbar_expect_tx(bar_wq, D * 64);
#pragma unroll 1
                        for (int r = 0; r < D; r += 160) tma2d(sb + X_WQ + r * 64, &tm_wq, 32 * cta, r, bar_wq);
                    }
                }
                if (t == 3) {
                    asm volatile("prefetch.tensormap [%0];" ::"l"(&tm_v) : "memory");
                    asm volatile("prefetch.tensormap [%0];" ::"l"(&tm_wo) : "memory");
                    asm volatile("prefetch.tensormap [%0];" ::"l"(&tm_w1) : "memory");
                    asm volatile("prefetch.tensormap [%0];" ::"l"(&tm_w2) : "memory");
                    asm volatile("prefetch.tensormap [%0];" ::"l"(&tm_gb) : "memory");
                }
                if (t == NS && late) {
                    mbar_wait(bar_full + (NS - INFLIGHT) * 8, 0);
                    mbar_expect_tx(bar_wm, D * 64);
#pragma unroll 1
                    for (int r = 0; r < D; r += 160) tma2d(sb + X_WM + r * 64, &tm_wmod, 32 * mc, r, bar_wm);
                }
                if (t >= NS && t < PF_END) {
                    int it = 0;
                    while (!mbar_test(bar_empty + (t & (NS - 1)) * 8, ((t >> 3) - 1) & 1)) {
                        if (tp < PF_END && (int)(gtime32() - t_start) >= PACE_A + (tp - NS) * PACE_TAU) {
                            asm volatile("cp.async.bulk.prefetch.L2.global.L2::cache_hint [%0], %1, %2;"
                                         ::"l"(((tp & 1) ? vb : kb) + (size_t)(((tp >> 1) + rot) & (NITEM / 2 - 1)) * TILE_BYTES), "r"(TILE_BYTES), "l"(pol) : "memory");
                            tp++;
                        }
                        if (++it > 16 * SPIN_LIMIT) __trap();
                    }
                    if (tp <= t) tp = t + 1;
                }
                if (t == NITEM) {
                    mbar_wait(bar_xfree, 0);
                    const uint32_t t_ref = t_start + sched + LAT_T + (NITEM - 1) * PACE_TAU;
#pragma unroll 1
                    for (int i = 0; i < 5; i++) {
                        while ((int)(gtime32() - t_ref) < WO_T + i * WO_S) { }
                        mbar_expect_tx(bar_wo + i * 8, DH * 64);
                        tma2d(sb + X_WO + i * (DH * 64), &tm_wo, bown * 160 + i * 32, head * DH, bar_wo + i * 8);
                    }
                    if (gb_own) {
                        mbar_wait(bar_empty + 3 * 8, ((NITEM >> 3) - 1) & 1);
                        mbar_wait(bar_x1, 0);
                        { const uint32_t c0 = clock32(); while (clock32() - c0 < GB_EV) { } }
                        while ((int)(gtime32() - t_ref) < GB_T) { }
#pragma unroll 1
                        for (int i = 0; i < 4; i++) {
                            mbar_expect_tx(bar_gb + i * 8, 160 * 16);
                            tma2d(sb + X_GB + i * (160 * 16), &tm_gb, 5 * D + 8 * own, 160 * i, bar_gb + i * 8);
                        }
                    }
                    if (is_f) {
#pragma unroll 1
                        for (int i = 0; i < 3; i++) mbar_wait(bar_empty + i * 8, ((NITEM >> 3) - 1) & 1);
                        while ((int)(gtime32() - t_ref) < W1_T) { }
#pragma unroll 1
                        for (int i = 0; i < 4; i++) {
                            mbar_expect_tx(bar_w1 + i * 8, 160 * 64);
                            tma2d(sb + X_W1 + i * (160 * 64), &tm_w1, 32 * f, 160 * i, bar_w1 + i * 8);
                        }
                        while ((int)(gtime32() - t_ref) < W2_T) { }
#pragma unroll 1
                        for (int i = 0; i < 10; i++) {
                            mbar_expect_tx(bar_w2 + i * 8, 4096);
                            tma2d(sb + X_W2 + i * 4096, &tm_w2, 64 * i, 32 * f, bar_w2 + i * 8);
                        }
                    }
                    break;
                }
                const int s = t & (NS - 1);
                if (t >= NS) {
                    mbar_wait(bar_empty + s * 8, ((t >> 3) - 1) & 1);
                    while ((int)(gtime32() - t_start) < sched + t * PACE_TAU) { }
                } else if (t >= INFLIGHT) {
                    mbar_wait(bar_full + (t - INFLIGHT) * 8, 0);
                }
                if (t < NITEM - 2) {
                    const int pair = t == NITEM - 3 ? NITEM / 2 - 1 : t >> 1;
                    mbar_expect_tx(bar_full + s * 8, TILE_BYTES);
                    bulk_load(sb + OFF_RING + s * TILE_BYTES, ((t & 1) && t != NITEM - 3 ? vb : kb) + (size_t)((pair + rot) & (NITEM / 2 - 1)) * TILE_BYTES, TILE_BYTES, bar_full + s * 8, pol);
                } else {
                    const int row = (bown * NH + head) * SK + (SK - WIN) + ((t - NITEM / 2 + rot) & (NITEM / 2 - 1)) * TILE_KEYS;
#pragma unroll 1
                    for (int i = 0; i < 2; i++) {
                        const uint32_t bar = bar_v + (2 * (t - (NITEM - 2)) + i) * 8;
                        mbar_expect_tx(bar, TILE_BYTES / 2);
                        tma2d_hint(sb + OFF_RING + s * TILE_BYTES + i * (TILE_BYTES / 2), &tm_v, 64 * i, row, bar, pol);
                    }
                }
                if (t >= PH_FIRST + PH_LAG && (t & 3) == (PH_LAG & 3)) {
                    const int now = (int)(gtime32() - t_start) - (t - PH_LAG) * PACE_TAU;
                    uint32_t ph;
                    asm volatile("atom.relaxed.gpu.global.add.u32 %0, [%1], 0;" : "=r"(ph) : "l"(g_phase + ((t - PH_LAG) >> 2) * 32) : "memory");
                    sched = (int)min(((ph & 0xffffffu) * 4 + (NCTA - (ph >> 24)) * now) >> 7, 65535u) - LAT_T;
                }
            }
        }
        __syncwarp();
    }

    if (warp == 9) {
        int side = 0;
        if (lane == 0) {
            uint32_t best[2] = {~0u, ~0u};
#pragma unroll 1
            for (int i = 0; i < 2 * NPROBE && ((i & 1) || (int)(gtime32() - t_start) < PROBE_END); i++) {
                uint32_t t0 = clock32(), v, t1;
                asm volatile("atom.relaxed.gpu.global.exch.b32 %0, [%1], %2;" : "=r"(v) : "l"(slot(SL_SIDE, i & 1) + cta * 8), "r"(0u) : "memory");
                asm volatile("{\n.reg .pred p;\nsetp.ne.u32 p, %1, 0xffffffff;\nmov.u32 %0, 0;\n@p mov.u32 %0, %%clock;\n}" : "=r"(t1) : "r"(v) : "memory");
                if (i & 1) best[1] = min(best[1], t1 - t0); else best[0] = min(best[0], t1 - t0);
            }
            side = best[1] < best[0];
        }
        side = __shfl_sync(0xffffffffu, side, 0);
        HPROF(1);
        mbar_wait(bar_full + (NS - 1) * 8, 0);
        stg_zero4(slot(SL_O + (cta >> 4), lane >> 4) + (cta & 15) * 64 + (lane & 15) * 4);
        if (is_owner) {
#pragma unroll 1
            for (int i = lane; i < NH * 8; i += 32) stg_zero4(slot(SL_P1 + own, side) + i * 4);
#pragma unroll 1
            for (int i = lane; i < NF * 8; i += 32) stg_zero4(slot(SL_P2 + 2 * own + (i >> 8), side) + (i & 255) * 4);
            if (lane < 8) stg_zero4(slot(SL_X1 + own / 30, lane >> 2) + (own % 30) * 32 + (lane & 3) * 4);
        }
        __threadfence();
        __syncwarp();
        if (lane == 0) stg_relaxed(g_clr + cta, 1u + side);
        HPROF(0);
        HPROF(2);
        while ((int)(gtime32() - t_start) < CLR_CHECK) __nanosleep(1000);
        mbar_wait(bar_xfree, 0);
        {
            uint4 v = make_uint4(1, 1, 1, 1), gv = v, mv[20];
#pragma unroll
            for (int i = 0; i < 20; i++) mv[i] = v;
#pragma unroll 1
            for (int it = 0;; it++) {
                v = ldg_relaxed(g_clr + lane * 4);

                ldg_relaxed_if(is_owner && lane < (gb_own ? 4 : 8), gv, mod_slot(lane < 4 ? 2 : 5, own, lane & 3));
#pragma unroll
                for (int i = 0; i < 20; i++) ldg_relaxed_if(is_f, mv[i], mod_slot(3, 8 * i + (lane >> 2), lane & 3));
                bool ok = ready(v) && ready(gv);
#pragma unroll
                for (int i = 0; i < 20; i++) ok = ok && ready(mv[i]);
                if (__all_sync(0xffffffffu, ok)) break;
                if (it > SPIN_LIMIT) __trap();
                __nanosleep(2000);
            }
            const uint32_t w[4] = {v.x, v.y, v.z, v.w};
#pragma unroll
            for (int i = 0; i < 4; i++) {
                const Roles r = roles(4 * lane + i);
                if (r.is_owner) {
                    sts32(sb + OFF_TAB1 + r.own * 4, (uint32_t)(size_t)(slot(SL_P1 + r.own, w[i] - 1) + head * 32));
                    sts32(sb + OFF_TAB2 + r.own * 4, (uint32_t)(size_t)(slot(SL_P2 + 2 * r.own + (f >> 5), w[i] - 1) + (f & 31) * 32));
                }
            }
            if (lane == 0) sts32(sb + OFF_SIDE, side);
            if (lane < 8) sts128(sb + OWN_GA + lane * 16, inv4(gv));
            const uint32_t dst = sb + OFF_VB + (lane & 3) * VEC_STRIDE + (lane >> 2) * 16;
#pragma unroll
            for (int i = 0; i < 10; i++) {
                const uint4 c = inv4(mv[10 + i]);
                sts128(dst + i * 128, make_uint4(bf2_add(c.x, 0x3f803f80u), bf2_add(c.y, 0x3f803f80u), bf2_add(c.z, 0x3f803f80u), bf2_add(c.w, 0x3f803f80u)));
                sts128(dst + (OFF_RED - OFF_VB) + i * 128, inv4(mv[i]));
            }
        }
        asm volatile("fence.acq_rel.gpu;" ::: "memory");
        __syncwarp();
        HPROF(3);
        if (lane == 0) mbar_arrive(bar_help);
        {
            const uint32_t* const src = pin(slot(SL_O + (cta >> 4), side) + (cta & 12) * 64 + lane * 4);
            const uint32_t dst = pin(sb + OFF_O + (lane >> 4) * O_STRIDE + (lane & 15) * 16);
            mbar_wait(bar_v + 16, 0);
            mbar_wait(bar_v + 24, 0);
            uint4 v[2];
            const uint32_t* const ptr[2] = {src, src + 128};
            const bool on[2] = {true, true};
            poll_n<2>(v, ptr, on);
            sts128(dst, v[0]);
            sts128(dst + 2 * O_STRIDE, v[1]);
#pragma unroll
            for (int w = 0; w < 8; w++) asm volatile("bar.arrive %0, 64;" ::"r"(NB_O + w) : "memory");
        }
        HPROF(4);
    }
    if (warp >= 8) {
        if (gb_own && warp == 9) {
            uint32_t a[20][4];
#pragma unroll
            for (int i = 0; i < 20; i++) ldsm4(a[i], sb + OFF_VA + (lane & 3) * VEC_STRIDE + (4 * i + (lane >> 3)) * 16);
            float c[4][4];
#pragma unroll
            for (int i = 0; i < 4; i++) c[i][0] = c[i][1] = c[i][2] = c[i][3] = 0.f;
#pragma unroll
            for (int bx = 0; bx < 4; bx++) {
                mbar_wait(bar_gb + bx * 8, 0);
#pragma unroll
                for (int i = 5 * bx; i < 5 * bx + 5; i++) {
                    uint32_t w[4];
                    ldsm4t(w, sb + X_GB + (32 * i + lane) * 16);
                    const uint32_t a0[4] = {a[i][0], 0u, a[i][1], 0u}, a1[4] = {a[i][2], 0u, a[i][3], 0u};
                    mma16816(c[(2 * i) & 3], a0, w[0], w[1]);
                    mma16816(c[(2 * i + 1) & 3], a1, w[2], w[3]);
                }
            }
            if (lane < 16) sts32(sb + OWN_GB + lane * 4, pack_bf((c[0][0] + c[1][0]) + (c[2][0] + c[3][0]), (c[0][1] + c[1][1]) + (c[2][1] + c[3][1])));
            HPROF(6);
        }
        if (is_owner && warp == 9) nbar_arrive<NB_E6, 288>();
        if (is_f) gelu_stage(sb, warp - 8, lane);
        return;
    }

    const int g = lane >> 2, t4 = lane & 3;
    const int mi = lane >> 3, r8 = lane & 7;

    {
        auto silu4 = [&](const uint4& cv) {
            uint32_t w4[4] = {cv.x, cv.y, cv.z, cv.w};
#pragma unroll
            for (int e = 0; e < 4; e++) {
                float c0 = bf_lo(w4[e]), c1 = bf_hi(w4[e]);
                w4[e] = pack_bf(c0 * rcp_fast(1.f + ex2(-1.4426950408889634f * c0)), c1 * rcp_fast(1.f + ex2(-1.4426950408889634f * c1)));
            }
            return make_uint4(w4[0], w4[1], w4[2], w4[3]);
        };
        {
            uint4 v = silu4(ca0);
            sts128(sb + OFF_VA + (tid / 80) * VEC_STRIDE + (tid % 80) * 16, v);
            if (tid < 64) { v = silu4(ca1); sts128(sb + OFF_VA + 3 * VEC_STRIDE + (16 + tid) * 16, v); }
        }
        if (warp < 4) {
            float s = 0.f, q = 0.f;
            const float pv = __shfl_sync(0xffffffffu, bf_lo(xs[0].x), 0);
#pragma unroll
            for (int i = 0; i < 3; i++) if (i < 2 || lane < 16) acc_stats(xs[i], pv, s, q);
#pragma unroll
            for (int of = 16; of > 0; of >>= 1) { s += __shfl_xor_sync(0xffffffffu, s, of); q += __shfl_xor_sync(0xffffffffu, q, of); }
            uint32_t m2; float rden;
            ln_finish(pv, s, q, m2, rden);
            if (lane == 0) { sts32(sb + OFF_STAT + warp * 8, m2); sts_f32(sb + OFF_STAT + warp * 8 + 4, rden); }
        } else if (warp == 4) {
            sts32(sb + OWN_X + lane * 4, bf2_add(own0, 0u));
            sts_f32(sb + OWN_B1 + lane * 4, bf2f(own2));
        }
    }
    bar_cons();
    PROF(24);
    uint32_t qf[8][2];
    float o[8][4];
#pragma unroll
    for (int c = 0; c < 8; c++) { o[c][0] = o[c][1] = o[c][2] = o[c][3] = 0.f; }
    float m_run = -INFINITY, l_run = 0.f;
    const bool diag = (t4 == (g >> 1));
    const bool odd = g & 1;
    const uint32_t koff = (warp & 3) * 4096 + (r8 + 8 * (mi & 1)) * 256 + (mi >> 1) * 128 + (r8 << 4);
    const uint32_t voff = TILE_BYTES + (warp & 3) * 4096 + (r8 + 8 * (mi >> 1)) * 256 + (mi & 1) * 128 + (r8 << 4);
    const int src0 = (2 * t4) * 4 + t4, src1 = (2 * t4 + 1) * 4 + t4;
#pragma unroll 1
    for (int step = crit ? 0 : 1; step < 3; step++) {
        if (step < 2 || late) {
            if (step == 1) {
                if (!crit) mbar_wait(bar_wq, 0);
                const uint32_t m2 = lds32(sb + OFF_STAT + (tid & 3) * 8);
                const float rden = lds_f32(sb + OFF_STAT + (tid & 3) * 8 + 4);
                uint4 v[4] = {xa, xa, xa, xa};
                const uint32_t* const ptr[4] = {mod_slot(0, tid >> 2, tid & 3), mod_slot(1, tid >> 2, tid & 3),
                                                mod_slot(0, 64 + ((tid & 63) >> 2), tid & 3), mod_slot(1, 64 + ((tid & 63) >> 2), tid & 3)};
                const bool on[4] = {true, true, tid < 64, tid < 64};
                poll_n<4>(v, ptr, on);
                uint4 h0 = ln_mod4(xa, v[1], v[0], m2, rden);
                sts128(sb + OFF_VB + (tid & 3) * VEC_STRIDE + (tid >> 2) * 16, h0);
                if (tid < 64) {
                    h0 = ln_mod4(xb, v[3], v[2], m2, rden);
                    sts128(sb + OFF_VB + (tid & 3) * VEC_STRIDE + (64 + (tid >> 2)) * 16, h0);
                }
            }
            mbar_wait(step == 1 ? bar_wq : bar_wm, 0);
            bar_cons();
            const uint32_t strip = sb + (step == 1 ? X_WQ : X_WM), vec = sb + (step == 1 ? OFF_VB : OFF_VA);
            float acc[2][4];
#pragma unroll
            for (int m = 0; m < 2; m++) { acc[m][0] = acc[m][1] = acc[m][2] = acc[m][3] = 0.f; }
#pragma unroll
            for (int i = 0; i < 5; i++) {
                int k0 = (warp * 5 + i) * 16;
                uint32_t b0, b1;
                load_bfrag(vec, VEC_STRIDE, k0, g, t4, b0, b1);
                int krow = k0 + r8 + 8 * (mi >> 1);
#pragma unroll
                for (int m = 0; m < 2; m++) {
                    uint32_t a[4];
                    int ch = 2 * m + (mi & 1);
                    ldsm4t(a, strip + krow * 64 + ((ch ^ ((krow >> 1) & 3)) << 4));
                    mma16816(acc[m], a, b0, b1);
                }
            }
            if (t4 < 2) {
#pragma unroll
                for (int m = 0; m < 2; m++) {
                    sts_f32x2(sb + OFF_RED + ((warp * 32 + m * 16 + g) * 4 + 2 * t4) * 4, acc[m][0], acc[m][1]);
                    sts_f32x2(sb + OFF_RED + ((warp * 32 + m * 16 + g + 8) * 4 + 2 * t4) * 4, acc[m][2], acc[m][3]);
                }
            }
            bar_cons();
            if (tid < 128) {
                float v = 0.f;
#pragma unroll
                for (int w = 0; w < 8; w++) v += lds_f32(sb + OFF_RED + (w * 128 + tid) * 4);
                float vn = __shfl_down_sync(0xffffffffu, v, 4);
                uint32_t* dst = step == 1 ? g_q + ((cta & ~3) + (tid & 3)) * 64 + bown * 16 + (tid >> 3) : g_mod + mc * 64 + (tid & 3) * 16 + (tid >> 3);
                if (!((tid >> 2) & 1)) stg_relaxed(dst, ~pack_bf(v, vn));
            }
        }
        if (step == 0) continue;
        if (step == 1) {
            if (warp == 0) {
                uint4 v = poll1(g_q + cta * 64 + (lane & 15) * 4, lane < 16);
                if (lane < 16) {
                    sts128(sb + OFF_Q + lane * 16, v);
                    stg_zero4(g_q + cta * 64 + lane * 4);
                }
            }
            bar_cons();
            PROF(4);

#pragma unroll
            for (int c = 0; c < 8; c++) {
                qf[c][0] = lds32(sb + OFF_Q + (((c ^ g) * 4 + t4) << 2));
                qf[c][1] = lds32(sb + OFF_Q + 128 + (((c ^ g) * 4 + t4) << 2));
            }
        } else {
            bar_cons();
            if (tid == 0) mbar_arrive(bar_xfree);
        }
#pragma unroll 1
        for (int j = (step == 1 ? 0 : SEG_J) + (warp >> 2); j < (step == 1 ? SEG_J : NITEM / 2 - 2); j += 2) {
            const int s = (2 * j) & (NS - 1);
            const uint32_t par = (j >> 2) & 1;
            mbar_wait(bar_full + s * 8, par);
            if (tid == 0 && 2 * j >= PH_FIRST) {
                const int x = min(max((int)(gtime32() - t_start) - 2 * j * PACE_TAU, 0), 65535);
                asm volatile("red.relaxed.gpu.global.add.u32 [%0], %1;" ::"l"(g_phase + (j >> 1) * 32), "r"((1u << 24) + (x >> 2)) : "memory");
            }
            const uint32_t base = sb + OFF_RING + s * TILE_BYTES;
            float sa[4] = {0.f, 0.f, 0.f, 0.f}, sb2[4] = {0.f, 0.f, 0.f, 0.f};
#pragma unroll
            for (int c = 0; c < 8; c += 2) {
                uint32_t a[4], a2[4];
                ldsm4(a, (base + koff) ^ (c << 4));
                ldsm4(a2, (base + koff) ^ ((c + 1) << 4));
                mma16816(sa, a, qf[c][0], qf[c][1]);
                mma16816(sb2, a2, qf[c + 1][0], qf[c + 1][1]);
            }
            const uint32_t sw = pack_bf(odd ? sa[1] + sb2[1] : sa[0] + sb2[0], odd ? sa[3] + sb2[3] : sa[2] + sb2[2]);
            const uint32_t sv = pack_bf(bf_lo(sw) * 0.08838834764831845f, bf_hi(sw) * 0.08838834764831845f);
            const float s0 = bf_lo(sv) * 1.4426950408889634f, s1 = bf_hi(sv) * 1.4426950408889634f;
            float m_new = fmaxf(m_run, fmaxf(s0, s1));
            const bool grow = __any_sync(0xffffffffu, (diag && (m_new > m_run)));
            if (lane == 0) mbar_arrive(bar_empty + s * 8);
            if (grow) {
                float al = ex2(m_run - m_new);
                float a0 = __shfl_sync(0xffffffffu, al, src0), a1 = __shfl_sync(0xffffffffu, al, src1);
#pragma unroll
                for (int c = 0; c < 8; c++) { o[c][0] *= a0; o[c][1] *= a1; o[c][2] *= a0; o[c][3] *= a1; }
                l_run *= al;
                m_run = m_new;
            }
            uint32_t pw = pack_bf(ex2(s0 - m_run), ex2(s1 - m_run));
            l_run += bf_lo(pw) + bf_hi(pw);
            uint32_t b0 = odd ? (pw << 16) : (pw & 0xffffu);
            uint32_t b1 = odd ? (pw & 0xffff0000u) : (pw >> 16);
            if (!diag) { b0 = 0u; b1 = 0u; }
            mbar_wait(bar_full + (s + 1) * 8, par);
#pragma unroll
            for (int c = 0; c < 8; c++) {
                uint32_t a[4];
                ldsm4t(a, (base + voff) ^ (c << 4));
                mma16816(o[c], a, b0, b1);
            }
            __syncwarp();
            if (lane == 0) mbar_arrive(bar_empty + (s + 1) * 8);
        }
    }
    PROF(5);
    float acc[4][4];
    uint32_t pa[8][2];
    float rinv;
    {
        const int s = 4 + (warp >> 2);
        mbar_wait(bar_full + s * 8, 1);
        const uint32_t base = sb + OFF_RING + s * TILE_BYTES;
        float sa[4] = {0.f, 0.f, 0.f, 0.f}, sb2[4] = {0.f, 0.f, 0.f, 0.f};
#pragma unroll
        for (int c = 0; c < 8; c += 2) {
            uint32_t a[4], a2[4];
            ldsm4(a, (base + koff) ^ (c << 4));
            ldsm4(a2, (base + koff) ^ ((c + 1) << 4));
            mma16816(sa, a, qf[c][0], qf[c][1]);
            mma16816(sb2, a2, qf[c + 1][0], qf[c + 1][1]);
        }
        const uint32_t sw = pack_bf(odd ? sa[1] + sb2[1] : sa[0] + sb2[0], odd ? sa[3] + sb2[3] : sa[2] + sb2[2]);
        const uint32_t sv = pack_bf(bf_lo(sw) * 0.08838834764831845f, bf_hi(sw) * 0.08838834764831845f);
        const float s0 = bf_lo(sv) * 1.4426950408889634f, s1 = bf_hi(sv) * 1.4426950408889634f;
        int mi_ = __float_as_int(diag ? fmaxf(m_run, fmaxf(s0, s1)) : -INFINITY);
        mi_ ^= (mi_ >> 31) & 0x7fffffff;
        mi_ = __reduce_max_sync(0xffffffffu, mi_);
        mi_ ^= (mi_ >> 31) & 0x7fffffff;
        if (lane == 0) sts32(sb + OFF_ML + warp * 4, mi_);
        bar_cons();
        const float4 m0 = lds_f32x4(sb + OFF_ML), m1 = lds_f32x4(sb + OFF_ML + 16);
        const float mx = fmaxf(fmaxf(fmaxf(m0.x, m0.y), fmaxf(m0.z, m0.w)), fmaxf(fmaxf(m1.x, m1.y), fmaxf(m1.z, m1.w)));
        const float scl = ex2(m_run - mx);
        const uint32_t pw = pack_bf(ex2(s0 - mx), ex2(s1 - mx));
        if (diag) { sts16(sb + SC_P + (warp * 16 + g) * 2, pw); sts16(sb + SC_P + (warp * 16 + g + 8) * 2, pw >> 16); }
        const float lw = warp_sum(diag ? fmaf(l_run, scl, bf_lo(pw) + bf_hi(pw)) : 0.f);
        const float a0 = __shfl_sync(0xffffffffu, scl, src0), a1 = __shfl_sync(0xffffffffu, scl, src1);
        float v[8], u[8];
#pragma unroll
        for (int c = 0; c < 8; c++) {
            v[c] = a0 * o[c][0] + a1 * o[c ^ 1][1];
            u[c] = a0 * o[c][2] + a1 * o[c ^ 1][3];
        }
#pragma unroll
        for (int c = 0; c < 8; c++) {
            if (!(c & 2)) {
                v[c] += __shfl_xor_sync(0xffffffffu, v[c ^ 2], 1);
                u[c] += __shfl_xor_sync(0xffffffffu, u[c ^ 2], 1);
            }
        }
#pragma unroll
        for (int c = 0; c < 2; c++) {
            v[c] += __shfl_xor_sync(0xffffffffu, v[c ^ 4], 2);
            u[c] += __shfl_xor_sync(0xffffffffu, u[c ^ 4], 2);
        }
        const uint32_t dst = sb + SC_OP + (warp * 128 + 16 * t4 + g) * 4;
        sts_f32(dst, v[0]); sts_f32(dst + 32, v[1]); sts_f32(dst + 256, u[0]); sts_f32(dst + 288, u[1]);
        if (lane == 0) sts_f32(sb + OFF_ML + 32 + warp * 4, lw);
        mbar_wait(bar_help, 0);
        bar_cons();
        const float4 l0 = lds_f32x4(sb + OFF_ML + 32), l1 = lds_f32x4(sb + OFF_ML + 48);
        rinv = rcp_fast(((l0.x + l0.y) + (l0.z + l0.w)) + ((l1.x + l1.y) + (l1.z + l1.w)));
#pragma unroll
        for (int i = 0; i < 4; i++) acc[i][0] = acc[i][1] = acc[i][2] = acc[i][3] = 0.f;
#pragma unroll
        for (int w = 0; w < 8; w++) {
            const float2 x0 = lds_f32x2(sb + SC_OP + (w * 128 + 16 * warp + 2 * t4) * 4), x1 = lds_f32x2(sb + SC_OP + (w * 128 + 16 * warp + 8 + 2 * t4) * 4);
            acc[2 * (w & 1)][0] += x0.x; acc[2 * (w & 1)][1] += x0.y;
            acc[2 * (w & 1) + 1][0] += x1.x; acc[2 * (w & 1) + 1][1] += x1.y;
        }
#pragma unroll
        for (int ks = 0; ks < 8; ks++) { pa[ks][0] = lds32(sb + SC_P + (8 * ks + t4) * 4); pa[ks][1] = lds32(sb + SC_P + (8 * ks + 4 + t4) * 4); }
    }
    PROF(20);
    const int mt = warp < 2 ? warp : warp + 2;
    {
        const uint32_t va = pin(sb + OFF_RING + 6 * TILE_BYTES + (warp >> 2) * (TILE_BYTES / 2) + (8 * (mi & 1) + r8) * 128 + (((2 * (warp & 3) + (mi >> 1)) ^ r8) << 4));
        const uint32_t vbar = pin(bar_v + (warp >> 2) * 8);
        uint32_t* const o_dst = pin(slot(SL_O + (cta >> 4), g) + (cta & 15) * 64 + warp * 8 + 2 * t4);
#pragma unroll
        for (int tl = 0; tl < 2; tl++) {
            mbar_wait(vbar + tl * 16, 0);
            uint32_t r[4][4];
#pragma unroll
            for (int ks = 0; ks < 4; ks++) ldsm4t(r[ks], va + tl * TILE_BYTES + ks * 2048);
#pragma unroll
            for (int ks = 0; ks < 4; ks++) {
                const uint32_t a[4] = {pa[4 * tl + ks][0], 0u, pa[4 * tl + ks][1], 0u};
                mma16816(acc[2 * (ks & 1)], a, r[ks][0], r[ks][1]);
                mma16816(acc[2 * (ks & 1) + 1], a, r[ks][2], r[ks][3]);
            }
        }
        stg_relaxed2_if(g < 2, o_dst, ~pack_bf((acc[0][0] + acc[2][0]) * rinv, (acc[0][1] + acc[2][1]) * rinv),
                        ~pack_bf((acc[1][0] + acc[3][0]) * rinv, (acc[1][1] + acc[3][1]) * rinv));
    }
    PROF(7);
    const int side = lds32(sb + OFF_SIDE);
    const uint32_t red_st = pin(sb + SC_E4 + ((warp * 4 + 2 * ((lane >> 3) & 1) + (lane >> 4)) * 8 + (lane & 7)) * 4);
    const uint32_t red_ld = pin(sb + SC_E4 + (lane & 15) * 8);
    const uint32_t* const in1 = pin(slot(SL_P1 + own, side) + tid * 4);
    const uint32_t* const in2a = pin(slot(SL_P2 + 2 * own, side) + tid * 4);
    const uint32_t* const in2b = pin(slot(SL_P2 + 2 * own + 1, side) + tid * 4);
    uint32_t* const out_dst = pin((uint32_t*)(p.out + ((lane >> 2) & 3) * D + 8 * own) + t4);
    uint32_t* const x1_dst = pin(slot(SL_X1 + own / 30, lane >> 4) + (own % 30) * 32 + (lane & 15));
    uint32_t* const rst = pin(tid >= 32 && tid < 56 ? mod_slot(lane >> 2, own, lane & 3) : own < 32 && tid == 64 ? g_clr + own * 4 : own < 16 && tid == 96 ? g_phase + own * 32 : nullptr);
    const uint32_t xw = lds32(sb + OWN_X + (lane & 15) * 4), ga_w = lds32(sb + OWN_GA + (lane & 15) * 4);
    uint32_t cs[15];
    uint32_t* dst2[5];
    uint32_t w2a[5];
#pragma unroll
    for (int j = 0; j < 10; j++) cs[j] = lds32(sb + OFF_VB + ((g & 1) * 4 + (g >> 1)) * VEC_STRIDE + warp * 160 + t4 * 4 + j * 16);
#pragma unroll
    for (int i = 0; i < 5; i++) {
        cs[10 + i] = lds32(sb + OFF_VB + (g >> 1) * VEC_STRIDE + warp * 160 + (g & 1) * 16 + t4 * 4 + i * 32);
        const uint2 t = lds64(sb + OFF_TAB2 + warp * 40 + i * 8);
        dst2[i] = slot_ptr((t4 < 2 ? t.x : t.y) + g * 16 + (t4 & 1) * 8);
        const int cc = 2 * (warp * 5 + i) + (mi & 1);
        w2a[i] = pin(sb + X_W2 + (cc >> 3) * 4096 + (r8 + 8 * (mi >> 1)) * 128 + (((cc & 7) ^ r8) << 4));
    }
    const uint32_t piv = lds32(sb + OFF_STAT + (g >> 1) * 8);
    const uint32_t* const xin = pin(slot(SL_X1 + warp / 3, side) + ((warp % 3) * 10 + (g & 1)) * 32 + (g >> 1) * 4 + t4);
    const uint32_t w1a = pin(sb + X_W1 + (warp * 80 + r8 + 8 * (mi >> 1)) * 64 + (((mi & 1) ^ ((r8 >> 1) & 3)) << 4));
    const uint32_t w1bar = pin(bar_w1 + (warp >> 1) * 8), w2bar = pin(bar_w2 + (warp + (warp >> 2)) * 8);
    const uint32_t wbar = pin(NB_O + warp);
    const uint32_t ab_st = pin(sb + SC_AB + warp * 1024 + lane * 16), y_st = pin(sb + SC_Y + warp * 512 + lane * 8), s_st = pin(sb + SC_ST + (t4 * 8 + warp) * 8);
    const uint32_t h_ld = pin(sb + SC_H1 + ((g & 3) ^ (2 * (f & 1) + ((f >> 1) & 1))) * 64 + t4 * 16);
    {
        const int kap = 2 * (head & 1) + ((head >> 1) & 1);
        const uint32_t wa = pin(sb + X_WO + (mt >> 1) * (DH * 64) + (r8 + 8 * (mi >> 1)) * 64 + ((((mt & 1) * 2 + (mi & 1)) ^ ((r8 >> 1) & 3)) << 4));
        const uint32_t oa = pin(sb + OFF_O + ((g & 3) ^ kap) * O_STRIDE + t4 * 8);
        uint32_t* dst[4];
#pragma unroll
        for (int i = 0; i < 2; i++) {
            const uint2 t = lds64(sb + OFF_TAB1 + (bown * 20 + 2 * mt + (warp < 2 ? 4 * i : 0)) * 4);
            dst[2 * i] = slot_ptr(t.x + g * 16 + t4 * 8);
            dst[2 * i + 1] = slot_ptr(t.y + g * 16 + t4 * 8);
        }
        PROF(6);
        const uint32_t wobar = pin(bar_wo + (mt >> 1) * 8);
        asm volatile("bar.sync %0, 64;" ::"r"(wbar) : "memory");
        uint2 ob[8];
#pragma unroll
        for (int ks = 0; ks < 8; ks++) ob[ks] = lds64(oa + ks * 32);
#pragma unroll
        for (int m = 0; m < 2; m++) {
            if (m == 0 || warp < 2) {
                mbar_wait(wobar + m * 8, 0);
                PROF(8);
                uint32_t wf[8][4];
#pragma unroll
                for (int ks = 0; ks < 8; ks++) ldsm4t(wf[ks], wa + m * (DH * 64) + ks * 1024);
                float c[4][4];
#pragma unroll
                for (int ks = 0; ks < 8; ks++) {
                    if (ks < 4) c[ks][0] = c[ks][1] = c[ks][2] = c[ks][3] = 0.f;
                    mma16816(c[ks & 3], wf[ks], ob[ks].x, ob[ks].y);
                }
                stg_relaxed2_if(t4 < 2, dst[2 * m], flag((c[0][0] + c[1][0]) + (c[2][0] + c[3][0])), flag((c[0][1] + c[1][1]) + (c[2][1] + c[3][1])));
                stg_relaxed2_if(t4 < 2, dst[2 * m + 1], flag((c[0][2] + c[1][2]) + (c[2][2] + c[3][2])), flag((c[0][3] + c[1][3]) + (c[2][3] + c[3][3])));
            }
        }
    }
    PROF(9);
    uint32_t x1w = 0;
    if (is_owner) {
        uint4 v;
        for (int it = 0;; it++) {
            v = ldg_relaxed(in1);
            if (__all_sync(0xffffffffu, and3(and3(v.x, v.y, v.z), v.w, 1u))) break;
            if (it > SPIN_LIMIT) __trap();
        }
        PROF(11);
        const float s0 = __uint_as_float(v.x) + __shfl_xor_sync(0xffffffffu, __uint_as_float(v.z), 8);
        const float s1 = __uint_as_float(v.y) + __shfl_xor_sync(0xffffffffu, __uint_as_float(v.w), 8);
        sts_f32(red_st, s0 + __shfl_xor_sync(0xffffffffu, s1, 16));
        nbar_sync<NB_E4, 256>();
        if (warp == 0) {
            float2 a[8];
#pragma unroll
            for (int w = 0; w < 8; w++) a[w] = lds_f32x2(red_ld + w * 128);
            const uint32_t aw = pack_bf(((a[0].x + a[1].x) + (a[2].x + a[3].x)) + ((a[4].x + a[5].x) + (a[6].x + a[7].x)),
                                        ((a[0].y + a[1].y) + (a[2].y + a[3].y)) + ((a[4].y + a[5].y) + (a[6].y + a[7].y)));
            x1w = bf2_add(xw, bf2_mul(ga_w, aw));
            stg_relaxed(x1_dst, x1w ^ 0x80008000u);
            if (lane == 0) mbar_arrive(bar_x1);
        }
        if (rst) stg_zero4(rst);
    }
    PROF(12);
    if (is_f) {
        uint32_t f1[5][2][4], f2[5][2][4];
        uint32_t d[6];
        auto load_x1 = [&] {
#pragma unroll
            for (int i = 0; i < 5; i++) d[i] = ldg_relaxed32(xin + i * 64);
        };
        auto have_x1 = [&] { return __all_sync(0xffffffffu, __vimin3_u32(__vimin3_u32(d[0], d[1], d[2]), d[3], d[4]) != 0u); };
        mbar_wait(w1bar, 0);
        load_x1();
        {
#pragma unroll
            for (int i = 0; i < 5; i++) { ldsm4t(f1[i][0], w1a + i * 1024); ldsm4t(f1[i][1], (w1a ^ 32) + i * 1024); }
            float c[2][4];
#pragma unroll
            for (int m = 0; m < 2; m++) c[m][0] = c[m][1] = c[m][2] = c[m][3] = 0.f;
#pragma unroll
            for (int i = 0; i < 5; i++) { mma16816(c[0], f1[i][0], cs[2 * i], cs[2 * i + 1]); mma16816(c[1], f1[i][1], cs[2 * i], cs[2 * i + 1]); }
#pragma unroll
            for (int i = 0; i < 5; i++) { cs[2 * i] = pin(odd ? 0u : cs[10 + i]); cs[2 * i + 1] = pin(odd ? cs[10 + i] : 0u); }
#pragma unroll
            for (int m = 0; m < 2; m++) sts128(ab_st + m * 512, make_uint4(__float_as_uint(c[m][0]), __float_as_uint(c[m][1]), __float_as_uint(c[m][2]), __float_as_uint(c[m][3])));
            nbar_arrive<NB_AB, 320>();
            d[0] |= __float_as_uint(c[1][3]) & (side >> 1);
        }
        PROF(10);
#pragma unroll 1
        for (int it = 0; !have_x1(); it++) {
            load_x1();
            if (it > SPIN_LIMIT) __trap();
        }
        PROF(13);
        {
            float y[2][4], st[4] = {0.f, 0.f, 0.f, 0.f};
#pragma unroll
            for (int m = 0; m < 2; m++) y[m][0] = y[m][1] = y[m][2] = y[m][3] = 0.f;
#pragma unroll
            for (int i = 0; i < 5; i++) d[i] = bf2_add(d[i], piv);
            d[5] = 0u;
#pragma unroll
            for (int i = 0; i < 5; i++) {
                if (i < 3) {
                    const uint32_t a[4] = {d[2 * i], 0x3f803f80u, d[2 * i + 1], 0x3f803f80u};
                    mma16816(st, a, d[2 * i], d[2 * i + 1]);
                }
                const uint32_t y0 = bf2_mul(d[i], cs[2 * i]), y1 = bf2_mul(d[i], cs[2 * i + 1]);
                mma16816(y[0], f1[i][0], y0, y1);
                mma16816(y[1], f1[i][1], y0, y1);
            }
            const float q = odd ? st[1] : st[0];
            const float q2 = q + __shfl_xor_sync(0xffffffffu, q, 4);
            if (diag && !odd) sts_f32x2(s_st, q2, st[2] + st[3]);
#pragma unroll
            for (int m = 0; m < 2; m++) sts_f32x2(y_st + m * 256, y[m][0] + y[m][1], y[m][2] + y[m][3]);
        }
        nbar_arrive<NB_Y, 320>();
        PROF(14);
        mbar_wait(w2bar, 0);
        mbar_wait(w2bar + 8, 0);
#pragma unroll
        for (int i = 0; i < 5; i++) { ldsm4t(f2[i][0], w2a[i]); ldsm4t(f2[i][1], w2a[i] + 2048); }
        asm volatile("bar.sync %0, 96;" ::"r"(wbar) : "memory");
        PROF(15);
        {
            const uint4 hb = lds128(h_ld);
            float c[5][4];
#pragma unroll
            for (int i = 0; i < 5; i++) { c[i][0] = c[i][1] = c[i][2] = c[i][3] = 0.f; mma16816(c[i], f2[i][0], hb.x, hb.y); }
#pragma unroll
            for (int i = 0; i < 5; i++) {
                mma16816(c[i], f2[i][1], hb.z, hb.w);
                stg_relaxed2_if(true, dst2[i], flag(t4 < 2 ? c[i][0] : c[i][2]), flag(t4 < 2 ? c[i][1] : c[i][3]));
            }
        }
    }
    PROF(16);
    if (is_owner) {
        const uint32_t b2w = lds32(sb + OWN_B2 + (lane & 15) * 4), gb_ld = pin(sb + OWN_GB + (lane & 15) * 4);
        const bool two = tid < NF * 8 - 256;
        uint4 v, w = make_uint4(1, 1, 1, 1);
        for (int it = 0;; it++) {
            ldg_relaxed_if(two, w, in2b);
            v = ldg_relaxed(in2a);
            if (__all_sync(0xffffffffu, and3(and3(v.x, v.y, v.z), and3(v.w, w.x, w.y), and3(w.z, w.w, 1u)))) break;
            if (it > SPIN_LIMIT) __trap();
        }
        PROF(17);
        const float s0 = (__uint_as_float(v.x) + __uint_as_float(w.x)) + __shfl_xor_sync(0xffffffffu, __uint_as_float(v.z) + __uint_as_float(w.z), 8);
        const float s1 = (__uint_as_float(v.y) + __uint_as_float(w.y)) + __shfl_xor_sync(0xffffffffu, __uint_as_float(v.w) + __uint_as_float(w.w), 8);
        sts_f32(red_st + (SC_E6 - SC_E4), s0 + __shfl_xor_sync(0xffffffffu, s1, 16));
        if (warp != 0) {
            nbar_arrive<NB_E6, 288>();
        } else {
            nbar_sync<NB_E6, 288>();
            float2 a[8];
#pragma unroll
            for (int i = 0; i < 8; i++) a[i] = lds_f32x2(red_ld + (SC_E6 - SC_E4) + i * 128);
            const uint32_t gb_w = lds32(gb_ld);
            const uint32_t aw = pack_bf(((a[0].x + a[1].x) + (a[2].x + a[3].x)) + ((a[4].x + a[5].x) + (a[6].x + a[7].x)),
                                        ((a[0].y + a[1].y) + (a[2].y + a[3].y)) + ((a[4].y + a[5].y) + (a[6].y + a[7].y)));
            x1w = bf2_add(x1w, bf2_mul(gb_w, bf2_add(aw, b2w)));
            if (lane < 16) asm volatile("st.global.u32 [%0], %1;" ::"l"(out_dst), "r"(x1w) : "memory");
        }
    }
    PROF(18);
    PROF_DUMP;
}

typedef CUresult (*EncodeFn)(CUtensorMap*, CUtensorMapDataType, cuuint32_t, void*, const cuuint64_t*, const cuuint64_t*, const cuuint32_t*,
                             const cuuint32_t*, CUtensorMapInterleave, CUtensorMapSwizzle, CUtensorMapL2promotion, CUtensorMapFloatOOBfill);

static CUtensorMap make_map(EncodeFn enc, const void* ptr, int cols, int rows, int box_cols, int box_rows, CUtensorMapSwizzle sw,
                            CUtensorMapL2promotion promo = CU_TENSOR_MAP_L2_PROMOTION_NONE) {
    CUtensorMap m;
    cuuint64_t dims[2] = {(cuuint64_t)cols, (cuuint64_t)rows};
    cuuint64_t strides[1] = {(cuuint64_t)cols * 2};
    cuuint32_t box[2] = {(cuuint32_t)box_cols, (cuuint32_t)box_rows};
    cuuint32_t es[2] = {1, 1};
    enc(&m, CU_TENSOR_MAP_DATA_TYPE_BFLOAT16, 2, const_cast<void*>(ptr), dims, strides, box, es, CU_TENSOR_MAP_INTERLEAVE_NONE, sw,
        promo, CU_TENSOR_MAP_FLOAT_OOB_FILL_NONE);
    return m;
}

}

extern "C" void kernel_launch(void* const* d_in, const int* in_sizes, int n_in, void* d_out, int out_size) {
    (void)in_sizes; (void)n_in; (void)out_size;
    static EncodeFn enc = nullptr;
    if (!enc) {
        void* fn = nullptr;
        cudaDriverEntryPointQueryResult qr;
        cudaGetDriverEntryPoint("cuTensorMapEncodeTiled", &fn, cudaEnableDefault, &qr);
        enc = (EncodeFn)fn;
        cudaFuncSetAttribute(fused_kernel, cudaFuncAttributeMaxDynamicSharedMemorySize, SMEM_BYTES);
    }
    Params p;
    p.x = (const __nv_bfloat16*)d_in[0];
    p.kc = (const __nv_bfloat16*)d_in[1];
    p.vc = (const __nv_bfloat16*)d_in[2];
    p.b1 = (const __nv_bfloat16*)d_in[7];
    p.b2 = (const __nv_bfloat16*)d_in[9];
    p.c = (const __nv_bfloat16*)d_in[10];
    p.out = (__nv_bfloat16*)d_out;
    CUtensorMap tm_wmod = make_map(enc, d_in[11], NMOD, D, 32, 160, CU_TENSOR_MAP_SWIZZLE_64B);
    CUtensorMap tm_wq = make_map(enc, d_in[3], NH * DH, D, 32, 160, CU_TENSOR_MAP_SWIZZLE_64B);
    CUtensorMap tm_wo = make_map(enc, d_in[4], D, NH * DH, 32, 128, CU_TENSOR_MAP_SWIZZLE_64B);
    CUtensorMap tm_w1 = make_map(enc, d_in[6], FF, D, 32, 160, CU_TENSOR_MAP_SWIZZLE_64B);
    CUtensorMap tm_w2 = make_map(enc, d_in[8], D, FF, 64, 32, CU_TENSOR_MAP_SWIZZLE_128B);
    CUtensorMap tm_v = make_map(enc, d_in[2], DH, NB * NH * SK, 64, TILE_KEYS, CU_TENSOR_MAP_SWIZZLE_128B);
    CUtensorMap tm_gb = make_map(enc, d_in[11], NMOD, D, 8, 160, CU_TENSOR_MAP_SWIZZLE_NONE, CU_TENSOR_MAP_L2_PROMOTION_L2_128B);
    fused_kernel<<<NCTA, NTHREADS, SMEM_BYTES>>>(p, tm_wmod, tm_wq, tm_wo, tm_w1, tm_w2, tm_v, tm_gb);
}
```

```cpp
#include <cuda_runtime.h>
#include <cuda.h>
#include <cuda_bf16.h>
#include <stdint.h>

namespace {

constexpr int NB = 4, D = 640, NH = 32, DH = 128, SK = 8192, WIN = 2048, FF = 1728, NMOD = 6 * D;
constexpr int NCTA = 128;
constexpr int NOWN = 80;
constexpr int NF = 54;
constexpr int NTHREADS = 320;
constexpr int TILE_KEYS = 64;
constexpr int TILE_BYTES = TILE_KEYS * DH * 2;
constexpr int NITEM = 2 * WIN / TILE_KEYS;
constexpr int NS = 8;
constexpr int NMODC = 120;
constexpr int SPIN_LIMIT = 1 << 18;
#define INFLIGHT 3
#define WQ_DELAY 500
#define MOD_T 3600
#define Q_PAUSE 600
#define PACE_A 7500
#define PACE_TAU 635
#define WQ2_AT 1
#define LATE_AT 4
#define PF_END 16
#define PH_FIRST 20
#define PH_LAG 5
#define LAT_T 2100
#define WO_T -1100
#define WO_S 300
#define W1_T 950
#define W2_T 1650
#define GB_T 2500
#define GB_EV 300
#define CLR_CHECK 28000
constexpr int NPROBE = 8, PROBE_END = 10000;
constexpr int SEG_J = 8;

constexpr int OFF_RING = 0;
constexpr int OFF_X = OFF_RING + NS * TILE_BYTES;
constexpr int X_WM = OFF_X;
constexpr int X_WQ = OFF_X + D * 64;
constexpr int X_WO = OFF_X;
constexpr int X_W1 = X_WO + 5 * DH * 64;
constexpr int X_END = X_W1 + D * 64;
constexpr int X_W2 = OFF_RING;
constexpr int X_GB = OFF_RING + 3 * TILE_BYTES;
static_assert(X_WQ + D * 64 <= X_END, "prologue weights must fit");
constexpr int VEC_STRIDE = 1296;
constexpr int OFF_VA = X_END;
constexpr int OFF_VB = OFF_VA + 4 * VEC_STRIDE;
constexpr int OFF_RED = OFF_VB + 4 * VEC_STRIDE;
constexpr int OFF_ML = OFF_RED + 4 * VEC_STRIDE;
constexpr int O_STRIDE = 288;
constexpr int OFF_O = OFF_ML + 64;
constexpr int OFF_Q = OFF_O + 4 * O_STRIDE;
constexpr int OFF_OWN = OFF_Q + 256;
constexpr int OWN_X = OFF_OWN, OWN_B2 = OWN_X + 64, OWN_GA = OWN_B2 + 64, OWN_GB = OWN_GA + 64, OWN_B1 = OWN_GB + 64;
constexpr int OFF_STAT = OWN_B1 + 128;
constexpr int OFF_TAB1 = OFF_STAT + 32;
constexpr int OFF_TAB2 = OFF_TAB1 + NOWN * 4;
constexpr int OFF_SIDE = OFF_TAB2 + NOWN * 4;
constexpr int OFF_BAR = OFF_SIDE + 8;
constexpr int NBAR = 2 * NS + 32;
constexpr int SMEM_BYTES = OFF_BAR + NBAR * 8;
constexpr int SC_OP = OFF_RING + 4 * TILE_BYTES;
constexpr int SC_AB = SC_OP + 4096;
constexpr int SC_Y = SC_AB + 8192;
constexpr int SC_ST = SC_Y + 4096;
constexpr int SC_E4 = SC_ST + 256;
constexpr int SC_E6 = SC_E4 + 1024;
constexpr int SC_P = SC_E6 + 1024;
constexpr int SC_H1 = SC_P + 256;
static_assert(SMEM_BYTES <= 232448, "smem");
static_assert(OFF_BAR % 8 == 0 && OFF_X % 1024 == 0 && X_WQ % 512 == 0 && X_W1 % 512 == 0 && OFF_VA % 16 == 0 && OFF_RED % 16 == 0 && OFF_ML % 16 == 0 && OFF_O % 16 == 0 && OFF_Q % 16 == 0, "align");
constexpr int NB_O = 2  , NB_E4 = 10, NB_E6 = 11, NB_AB = 12, NB_Y = 13;

__device__ __align__(128) uint32_t g_mod[NMODC * 64];
__device__ __align__(128) uint32_t g_q[NCTA * 128];
__device__ uint32_t g_clr[NCTA];
__device__ uint32_t g_phase[16 * 32];
constexpr int SL_P1 = 0;
constexpr int SL_P2 = SL_P1 + NOWN;
constexpr int SL_O = SL_P2 + 2 * NOWN;
constexpr int SL_X1 = SL_O + 8;
constexpr int SL_SIDE = SL_X1 + 3;
static_assert(SL_SIDE < 256, "one 2 MB page");
__device__ uint32_t g_slots[2 * 256 * 2048];
__device__ __forceinline__ uint32_t* slot(int i, int side) {
    const size_t base = ((size_t)g_slots + 0x1fffff) & ~(size_t)0x1fffff;
    return (uint32_t*)base + i * 2048 + (((__popc(i & 0x59) ^ side) & 1) << 10);
}
#define PROF_DECL
#define HPROF(i) do { } while (0)
#define PROF(i) do { } while (0)
#define PROF_DUMP do { } while (0)

__device__ __forceinline__ uint32_t smem_u32(const void* p) { return (uint32_t)__cvta_generic_to_shared(p); }
__device__ __forceinline__ void mbar_init(uint32_t bar, uint32_t cnt) { asm volatile("mbarrier.init.shared::cta.b64 [%0], %1;" ::"r"(bar), "r"(cnt) : "memory"); }
__device__ __forceinline__ void mbar_expect_tx(uint32_t bar, uint32_t bytes) { asm volatile("mbarrier.arrive.expect_tx.shared::cta.b64 _, [%0], %1;" ::"r"(bar), "r"(bytes) : "memory"); }
__device__ __forceinline__ void mbar_arrive(uint32_t bar) { asm volatile("mbarrier.arrive.shared::cta.b64 _, [%0];" ::"r"(bar) : "memory"); }
__device__ __forceinline__ void mbar_wait(uint32_t bar, uint32_t parity) {
    uint32_t ok;
    int it = 0;
    while (true) {
        asm volatile("{\n.reg .pred p;\nmbarrier.try_wait.parity.shared::cta.b64 p, [%1], %2;\nselp.u32 %0, 1, 0, p;\n}" : "=r"(ok) : "r"(bar), "r"(parity) : "memory");
        if (ok) break;
        if (++it > SPIN_LIMIT) __trap();
    }
}
__device__ __forceinline__ void bulk_load(uint32_t dst, const void* src, uint32_t bytes, uint32_t bar, uint64_t pol) {
    asm volatile("cp.async.bulk.shared::cluster.global.mbarrier::complete_tx::bytes.L2::cache_hint [%0], [%1], %2, [%3], %4;"
                 ::"r"(dst), "l"(src), "r"(bytes), "r"(bar), "l"(pol) : "memory");
}
__device__ __forceinline__ void bar_cons() { asm volatile("bar.sync 1, 256;" ::: "memory"); }
template <int ID, int N> __device__ __forceinline__ void nbar_sync() { asm volatile("bar.sync %0, %1;" ::"n"(ID), "n"(N) : "memory"); }
template <int ID, int N> __device__ __forceinline__ void nbar_arrive() { asm volatile("bar.arrive %0, %1;" ::"n"(ID), "n"(N) : "memory"); }
__device__ __forceinline__ bool mbar_test(uint32_t bar, uint32_t parity) {
    uint32_t ok;
    asm volatile("{\n.reg .pred p;\nmbarrier.test_wait.parity.shared::cta.b64 p, [%1], %2;\nselp.u32 %0, 1, 0, p;\n}" : "=r"(ok) : "r"(bar), "r"(parity) : "memory");
    return ok;
}
__device__ __forceinline__ uint32_t pin(uint32_t v) { asm volatile("" : "+r"(v)); return v; }
template <class T> __device__ __forceinline__ T pin_hard(T v) { return __shfl_sync(0xffffffffu, v, threadIdx.x & 31); }
template <class T> __device__ __forceinline__ T* pin(T* v) { asm volatile("" : "+l"(v)); return v; }
__device__ __forceinline__ void ldsm4(uint32_t (&a)[4], uint32_t addr) {
    asm volatile("ldmatrix.sync.aligned.m8n8.x4.shared.b16 {%0,%1,%2,%3}, [%4];" : "=r"(a[0]), "=r"(a[1]), "=r"(a[2]), "=r"(a[3]) : "r"(addr) : "memory");
}
__device__ __forceinline__ void ldsm4t(uint32_t (&a)[4], uint32_t addr) {
    asm volatile("ldmatrix.sync.aligned.m8n8.x4.trans.shared.b16 {%0,%1,%2,%3}, [%4];" : "=r"(a[0]), "=r"(a[1]), "=r"(a[2]), "=r"(a[3]) : "r"(addr) : "memory");
}
__device__ __forceinline__ void mma16816(float (&c)[4], const uint32_t (&a)[4], uint32_t b0, uint32_t b1) {
    asm volatile("mma.sync.aligned.m16n8k16.row.col.f32.bf16.bf16.f32 {%0,%1,%2,%3}, {%4,%5,%6,%7}, {%8,%9}, {%0,%1,%2,%3};"
                 : "+f"(c[0]), "+f"(c[1]), "+f"(c[2]), "+f"(c[3]) : "r"(a[0]), "r"(a[1]), "r"(a[2]), "r"(a[3]), "r"(b0), "r"(b1));
}
__device__ __forceinline__ uint32_t lds32(uint32_t addr) { uint32_t v; asm volatile("ld.shared.u32 %0, [%1];" : "=r"(v) : "r"(addr) : "memory"); return v; }
__device__ __forceinline__ float lds_f32(uint32_t addr) { float v; asm volatile("ld.shared.f32 %0, [%1];" : "=f"(v) : "r"(addr) : "memory"); return v; }
__device__ __forceinline__ float2 lds_f32x2(uint32_t addr) { float2 v; asm volatile("ld.shared.v2.f32 {%0,%1}, [%2];" : "=f"(v.x), "=f"(v.y) : "r"(addr) : "memory"); return v; }
__device__ __forceinline__ float4 lds_f32x4(uint32_t addr) { float4 v; asm volatile("ld.shared.v4.f32 {%0,%1,%2,%3}, [%4];" : "=f"(v.x), "=f"(v.y), "=f"(v.z), "=f"(v.w) : "r"(addr) : "memory"); return v; }
__device__ __forceinline__ uint2 lds64(uint32_t addr) { uint2 v; asm volatile("ld.shared.v2.u32 {%0,%1}, [%2];" : "=r"(v.x), "=r"(v.y) : "r"(addr) : "memory"); return v; }
__device__ __forceinline__ uint4 lds128(uint32_t addr) { uint4 v; asm volatile("ld.shared.v4.u32 {%0,%1,%2,%3}, [%4];" : "=r"(v.x), "=r"(v.y), "=r"(v.z), "=r"(v.w) : "r"(addr) : "memory"); return v; }
__device__ __forceinline__ void sts16(uint32_t addr, uint32_t v) { asm volatile("st.shared.b16 [%0], %1;" ::"r"(addr), "h"((unsigned short)v) : "memory"); }
__device__ __forceinline__ void sts32(uint32_t addr, uint32_t v) { asm volatile("st.shared.u32 [%0], %1;" ::"r"(addr), "r"(v) : "memory"); }
__device__ __forceinline__ void sts_f32(uint32_t addr, float v) { asm volatile("st.shared.f32 [%0], %1;" ::"r"(addr), "f"(v) : "memory"); }
__device__ __forceinline__ void sts_f32x2(uint32_t addr, float a, float b) { asm volatile("st.shared.v2.f32 [%0], {%1,%2};" ::"r"(addr), "f"(a), "f"(b) : "memory"); }
__device__ __forceinline__ void sts128(uint32_t addr, uint4 v) { asm volatile("st.shared.v4.u32 [%0], {%1,%2,%3,%4};" ::"r"(addr), "r"(v.x), "r"(v.y), "r"(v.z), "r"(v.w) : "memory"); }
__device__ __forceinline__ uint4 ldg_relaxed(const uint32_t* p) {
    uint4 v;
    asm volatile("ld.relaxed.gpu.global.v4.u32 {%0,%1,%2,%3}, [%4];" : "=r"(v.x), "=r"(v.y), "=r"(v.z), "=r"(v.w) : "l"(p) : "memory");
    return v;
}
__device__ __forceinline__ void ldg_relaxed_if(bool on, uint4& v, const uint32_t* p) {
    asm volatile("{\n.reg .pred q;\nsetp.ne.u32 q, %5, 0;\n@q ld.relaxed.gpu.global.v4.u32 {%0,%1,%2,%3}, [%4];\n}"
                 : "+r"(v.x), "+r"(v.y), "+r"(v.z), "+r"(v.w) : "l"(p), "r"((uint32_t)on) : "memory");
}
__device__ __forceinline__ void stg_relaxed2_if(bool on, uint32_t* p, uint32_t a, uint32_t b) {
    asm volatile("{\n.reg .pred q;\nsetp.ne.u32 q, %3, 0;\n@q st.relaxed.gpu.global.v2.u32 [%0], {%1,%2};\n}" ::"l"(p), "r"(a), "r"(b), "r"((uint32_t)on) : "memory");
}
__device__ __forceinline__ uint32_t ldg_relaxed32(const uint32_t* p) { uint32_t v; asm volatile("ld.relaxed.gpu.global.u32 %0, [%1];" : "=r"(v) : "l"(p) : "memory"); return v; }
__device__ __forceinline__ void stg_relaxed(uint32_t* p, uint32_t v) { asm volatile("st.relaxed.gpu.global.u32 [%0], %1;" ::"l"(p), "r"(v) : "memory"); }
__device__ __forceinline__ void stg_zero4(uint32_t* p) { asm volatile("st.relaxed.gpu.global.v4.u32 [%0], {%1,%1,%1,%1};" ::"l"(p), "r"(0u) : "memory"); }
__device__ __forceinline__ bool ready(const uint4& v) { return (v.x != 0u) & (v.y != 0u) & (v.z != 0u) & (v.w != 0u); }
__device__ __forceinline__ uint4 inv4(const uint4& v) { return make_uint4(~v.x, ~v.y, ~v.z, ~v.w); }
__device__ __forceinline__ uint32_t pack_bf(float lo, float hi) {
    uint32_t r;
    asm("cvt.rn.bf16x2.f32 %0, %1, %2;" : "=r"(r) : "f"(hi), "f"(lo));
    return r;
}
__device__ __forceinline__ float bfr(float x) { return __uint_as_float(pack_bf(0.f, x) & 0xffff0000u); }
__device__ __forceinline__ float bf_lo(uint32_t w) { return __uint_as_float(w << 16); }
__device__ __forceinline__ float bf_hi(uint32_t w) { return __uint_as_float(w & 0xffff0000u); }
__device__ __forceinline__ float bf2f(__nv_bfloat16 v) { return __bfloat162float(v); }
__device__ __forceinline__ float ex2(float x) { float y; asm("ex2.approx.ftz.f32 %0, %1;" : "=f"(y) : "f"(x)); return y; }
__device__ __forceinline__ float rcp_fast(float x) { float y; asm("rcp.approx.ftz.f32 %0, %1;" : "=f"(y) : "f"(x)); return y; }
__device__ __forceinline__ float rsqrt_fast(float x) { float y; asm("rsqrt.approx.ftz.f32 %0, %1;" : "=f"(y) : "f"(x)); return y; }
__device__ __forceinline__ float sqrt_fast(float x) { float y; asm("sqrt.approx.f32 %0, %1;" : "=f"(y) : "f"(x)); return y; }
__device__ __forceinline__ uint32_t bf2_add(uint32_t a, uint32_t b) { uint32_t r; asm("add.rn.bf16x2 %0, %1, %2;" : "=r"(r) : "r"(a), "r"(b)); return r; }
__device__ __forceinline__ uint32_t bf2_sub(uint32_t a, uint32_t b) { uint32_t r; asm("sub.rn.bf16x2 %0, %1, %2;" : "=r"(r) : "r"(a), "r"(b)); return r; }
__device__ __forceinline__ uint32_t bf2_mul(uint32_t a, uint32_t b) { uint32_t r; asm("mul.rn.bf16x2 %0, %1, %2;" : "=r"(r) : "r"(a), "r"(b)); return r; }
__device__ __forceinline__ uint32_t gtime32() { uint32_t c; asm volatile("mov.u32 %0, %%globaltimer_lo;" : "=r"(c)); return c; }
__device__ __forceinline__ uint32_t clock32() { uint32_t c; asm volatile("mov.u32 %0, %%clock;" : "=r"(c)); return c; }

__device__ __forceinline__ float warp_sum(float v) {
#pragma unroll
    for (int o = 16; o > 0; o >>= 1) v += __shfl_xor_sync(0xffffffffu, v, o);
    return v;
}

struct Params {
    const __nv_bfloat16 *x, *kc, *vc, *b1, *b2, *c;
    __nv_bfloat16* out;
};

__device__ __forceinline__ void tma2d(uint32_t dst, const CUtensorMap* tm, int x, int y, uint32_t bar) {
    asm volatile("cp.async.bulk.tensor.2d.shared::cluster.global.mbarrier::complete_tx::bytes [%0], [%1, {%2, %3}], [%4];"
                 ::"r"(dst), "l"(tm), "r"(x), "r"(y), "r"(bar) : "memory");
}

__device__ __forceinline__ void tma2d_hint(uint32_t dst, const CUtensorMap* tm, int x, int y, uint32_t bar, uint64_t pol) {
    asm volatile("cp.async.bulk.tensor.2d.shared::cluster.global.mbarrier::complete_tx::bytes.L2::cache_hint [%0], [%1, {%2, %3}], [%4], %5;"
                 ::"r"(dst), "l"(tm), "r"(x), "r"(y), "r"(bar), "l"(pol) : "memory");
}
__device__ __forceinline__ uint32_t flag(float v) { return __float_as_uint(v) | 1u; }
__device__ __forceinline__ uint32_t and3(uint32_t a, uint32_t b, uint32_t c) { uint32_t r; asm("lop3.b32 %0, %1, %2, %3, 0x80;" : "=r"(r) : "r"(a), "r"(b), "r"(c)); return r; }
__device__ __forceinline__ uint32_t* slot_ptr(uint32_t lo) {
    uint32_t* r;
    asm volatile("mov.b64 %0, {%1, %2};" : "=l"(r) : "r"(lo), "r"((uint32_t)((size_t)slot(0, 0) >> 32)));
    return r;
}

__device__ __forceinline__ void load_bfrag(uint32_t vec, int stride, int k0, int g, int t, uint32_t& b0, uint32_t& b1) {
    uint32_t a = vec + (g & 3) * stride + (k0 + 2 * t) * 2;
    b0 = lds32(a);
    b1 = lds32(a + 16);
}

__device__ __forceinline__ void ln_finish(float pivot, float sum, float sumsq, uint32_t& m2, float& rden) {
    float dm = sum * (1.f / D);
    float var = fmaxf(sumsq * (1.f / D) - dm * dm, 0.f);
    float mean = pivot + dm;
    m2 = pack_bf(mean, mean);
    rden = rcp_fast(bfr(sqrt_fast(bfr(bfr(var) + 1e-5f))));
}
__device__ __forceinline__ uint32_t ln_mod_pair(uint32_t xw, uint32_t cw, uint32_t sw, uint32_t m2, float rden) {
    uint32_t d = bf2_sub(xw, m2);
    uint32_t ln = pack_bf(bf_lo(d) * rden, bf_hi(d) * rden);
    return bf2_add(bf2_mul(ln, bf2_add(cw, 0x3f803f80u)), sw);
}
__device__ __forceinline__ uint4 ln_mod4(const uint4& x, const uint4& c, const uint4& s, uint32_t m2, float rden) {
    return make_uint4(ln_mod_pair(x.x, c.x, s.x, m2, rden), ln_mod_pair(x.y, c.y, s.y, m2, rden),
                      ln_mod_pair(x.z, c.z, s.z, m2, rden), ln_mod_pair(x.w, c.w, s.w, m2, rden));
}
__device__ __forceinline__ void acc_stats(const uint4& v, float pv, float& s, float& q) {
    const float a0 = bf_lo(v.x) - pv, a1 = bf_hi(v.x) - pv, a2 = bf_lo(v.y) - pv, a3 = bf_hi(v.y) - pv;
    const float a4 = bf_lo(v.z) - pv, a5 = bf_hi(v.z) - pv, a6 = bf_lo(v.w) - pv, a7 = bf_hi(v.w) - pv;
    s += ((a0 + a1) + (a2 + a3)) + ((a4 + a5) + (a6 + a7));
    q += (fmaf(a0, a0, a1 * a1) + fmaf(a2, a2, a3 * a3)) + (fmaf(a4, a4, a5 * a5) + fmaf(a6, a6, a7 * a7));
}
__device__ __forceinline__ uint32_t* mod_slot(int kind, int j, int b) { return g_mod + (kind * 20 + (j >> 2)) * 64 + b * 16 + (j & 3) * 4; }

template <int N>
__device__ __forceinline__ void poll_n(uint4 (&v)[N], const uint32_t* const* ptr, const bool* on) {
    bool pend[N];
#pragma unroll
    for (int i = 0; i < N; i++) pend[i] = on[i];
    int it = 0;
    while (true) {
#pragma unroll
        for (int i = 0; i < N; i++) if (pend[i]) v[i] = ldg_relaxed(ptr[i]);
        bool any = false;
#pragma unroll
        for (int i = 0; i < N; i++) { pend[i] = pend[i] && !ready(v[i]); any |= pend[i]; }
        if (!__any_sync(0xffffffffu, any)) break;
        if (++it > SPIN_LIMIT) __trap();
    }
#pragma unroll
    for (int i = 0; i < N; i++) v[i] = inv4(v[i]);
}
__device__ __forceinline__ uint4 poll1(const uint32_t* p, bool on) {
    uint4 v[1] = {make_uint4(0, 0, 0, 0)};
    const uint32_t* const ptr[1] = {p};
    const bool o[1] = {on};
    poll_n<1>(v, ptr, o);
    return v[0];
}

__device__ __forceinline__ void gelu_stage(uint32_t sb, int m, int lane) {
    const int g = lane >> 2, b = lane & 3;
    const uint32_t y_ld = pin_hard(sb + SC_Y + m * 256 + lane * 8), s_ld = pin_hard(sb + SC_ST + b * 64);
    const uint32_t h_st = pin_hard(sb + SC_H1 + b * 64 + (g >> 1) * 16 + m * 8 + (g & 1) * 2);
    float a0 = 0.f, b0 = lds_f32(sb + OWN_B1 + (16 * m + g) * 4), a1 = 0.f, b1 = lds_f32(sb + OWN_B1 + (16 * m + g + 8) * 4);
    const float piv = bf_hi(lds32(sb + OFF_STAT + b * 8));
    nbar_sync<NB_AB, 320>();
#pragma unroll
    for (int w = 0; w < 8; w++) {
        const float4 t = lds_f32x4(sb + SC_AB + w * 1024 + m * 512 + lane * 16);
        a0 += t.x; b0 += t.y; a1 += t.z; b1 += t.w;
    }
    sts128(sb + SC_AB + m * 512 + lane * 16, make_uint4(__float_as_uint(a0), __float_as_uint(b0), __float_as_uint(a1), __float_as_uint(b1)));
    nbar_sync<NB_Y, 320>();
    float4 q[4];
    float2 y[8];
#pragma unroll
    for (int i = 0; i < 4; i++) q[i] = lds_f32x4(s_ld + i * 16);
#pragma unroll
    for (int w = 0; w < 8; w++) y[w] = lds_f32x2(y_ld + w * 512);
    const float dm = (((q[0].y + q[0].w) + (q[1].y + q[1].w)) + ((q[2].y + q[2].w) + (q[3].y + q[3].w))) * (1.f / D);
    const float sq = ((q[0].x + q[0].z) + (q[1].x + q[1].z)) + ((q[2].x + q[2].z) + (q[3].x + q[3].z));
    const float r = rsqrt_fast(fmaxf(fmaf(-dm, dm, fmaf(sq, 1.f / D, 1e-5f)), 1e-5f));
    const float y0 = ((y[0].x + y[1].x) + (y[2].x + y[3].x)) + ((y[4].x + y[5].x) + (y[6].x + y[7].x));
    const float y1 = ((y[0].y + y[1].y) + (y[2].y + y[3].y)) + ((y[4].y + y[5].y) + (y[6].y + y[7].y));
    const float dmr = piv - bfr(piv - dm);
    const float u0 = fmaf(r, fmaf(dmr, a0, -y0), b0), u1 = fmaf(r, fmaf(dmr, a1, -y1), b1);
    const float e0 = ex2(u0 * fmaf(u0 * u0, -0.044715f * 2.302208198144325f, -2.302208198144325f));
    const float e1 = ex2(u1 * fmaf(u1 * u1, -0.044715f * 2.302208198144325f, -2.302208198144325f));
    sts16(h_st, pack_bf(u0 * rcp_fast(1.f + e0), 0.f));
    sts16(h_st + 4, pack_bf(u1 * rcp_fast(1.f + e1), 0.f));
#pragma unroll
    for (int w = 0; w < 8; w++) asm volatile("bar.arrive %0, 96;" ::"r"(NB_O + w) : "memory");
}

struct Roles { bool is_f, is_owner; int f, own; };
__device__ __forceinline__ Roles roles(int cta) {
    Roles r;
    r.f = (cta * 27) >> 6;
    r.is_f = (((cta + 1) * 27) >> 6) != r.f;
    r.is_owner = !r.is_f || r.f % 9 == 4;
    r.own = r.is_f ? 74 + r.f / 9 : cta - r.f;
    return r;
}

__global__ void __launch_bounds__(NTHREADS, 1)
fused_kernel(const Params p, const __grid_constant__ CUtensorMap tm_wmod, const __grid_constant__ CUtensorMap tm_wq,
             const __grid_constant__ CUtensorMap tm_wo, const __grid_constant__ CUtensorMap tm_w1, const __grid_constant__ CUtensorMap tm_w2,
             const __grid_constant__ CUtensorMap tm_v, const __grid_constant__ CUtensorMap tm_gb) {
    extern __shared__ __align__(1024) unsigned char smem[];
    const uint32_t t_start = gtime32();
    if (threadIdx.x == 0) {
        const uint32_t c_ = blockIdx.x;
        const uint32_t off = ((c_ & 3) << 26) + (c_ >> 2) * (1u << 21) + ((c_ & 12) << 15) + (SK - WIN) * DH * 2;
        asm volatile("cp.async.bulk.prefetch.L2.global.L2::cache_hint [%0], %1, %2;" ::"l"((const char*)p.kc + off), "r"(TILE_BYTES), "l"(0x12f0000000000000ull  ) : "memory");
    }
    const uint32_t sb = smem_u32(smem);
    const int cta = blockIdx.x;
    const int head = cta >> 2, bown = cta & 3;
    const int rot = (8 * head) & (NITEM / 2 - 1);
    const char* const kb = (const char*)(p.kc + ((size_t)(bown * NH + head) * SK + (SK - WIN)) * DH);
    uint64_t pol = 0;
    if (threadIdx.x == 256) {
        mbar_init(sb + OFF_BAR, 1);
        asm volatile("fence.mbarrier_init.release.cluster;" ::: "memory");
        asm volatile("createpolicy.fractional.L2::evict_first.b64 %0, 1.0;" : "=l"(pol));
        mbar_expect_tx(sb + OFF_BAR, TILE_BYTES);
        bulk_load(sb + OFF_RING, kb + (size_t)rot * TILE_BYTES, TILE_BYTES, sb + OFF_BAR, pol);
        if ((((head + 1) * 5) >> 4) != ((head * 5) >> 4)) {
            const uint32_t bar = sb + OFF_BAR + 2 * NS * 8;
            mbar_init(bar, 1);
            asm volatile("fence.mbarrier_init.release.cluster;" ::: "memory");
            mbar_expect_tx(bar, D * 64);
#pragma unroll 1
            for (int r = 0; r < D; r += 160) tma2d(sb + X_WM + r * 64, &tm_wmod, 32 * (((head * 5) >> 4) * 4 + bown), r, bar);
        }
    }
    const uint32_t bar_full = sb + OFF_BAR, bar_empty = bar_full + NS * 8;
    const uint32_t bar_wm = bar_empty + NS * 8, bar_wq = bar_wm + 8, bar_xfree = bar_wq + 8, bar_wo = bar_xfree + 8  ;
    const uint32_t bar_w1 = bar_wo + 40  , bar_w2 = bar_w1 + 32  , bar_help = bar_w2 + 80, bar_v = bar_help + 8  ;
    const uint32_t bar_gb = bar_v + 32  , bar_x1 = bar_gb + 32;
    const int tid = threadIdx.x, warp = tid >> 5, lane = tid & 31;
    const Roles role = roles(cta);
    const bool is_f = role.is_f, is_owner = role.is_owner;
    const int f = role.f, own = role.own;
    const bool crit = (((head + 1) * 5) >> 4) != ((head * 5) >> 4);
    const int mr = cta - ((head * 5) >> 4) * 4, mq = ((head * 5) >> 4) * 4 + bown;
    const int ml = mr * 31 / 44;
    const bool late = !crit && (mr + 1) * 31 / 44 != ml;
    const int mc = crit ? mq : ml < 60 ? 40 + ml : 58 + ml;
    const bool gb_own = is_owner && own < 72;

    PROF_DECL
    PROF(0);
    uint4 xa = make_uint4(0, 0, 0, 0), xb = xa, ca0 = xa, ca1 = xa, xs[3] = {xa, xa, xa};
    uint32_t own0 = 0;
    __nv_bfloat16 own2 = __float2bfloat16(0.f);
    if (warp < 8) {
        xa = *(const uint4*)(p.x + (tid & 3) * D + (tid >> 2) * 8);
        ca0 = ((const uint4*)p.c)[tid];
        if (tid < 64) { xb = *(const uint4*)(p.x + (tid & 3) * D + (64 + (tid >> 2)) * 8); ca1 = ((const uint4*)p.c)[256 + tid]; }
        if (warp < 4) {
#pragma unroll
            for (int i = 0; i < 3; i++) if (lane + 32 * i < 80) xs[i] = ((const uint4*)p.x)[warp * 80 + lane + 32 * i];
        } else if (warp == 4) {
            if (is_owner) own0 = *(const uint32_t*)((lane < 16 ? p.x + (lane >> 2) * D : p.b2) + 8 * own + 2 * (lane & 3));
            if (is_f) own2 = p.b1[32 * f + lane];
        }
    }
    const char* const vb = (const char*)(p.vc + ((size_t)(bown * NH + head) * SK + (SK - WIN)) * DH);
    const uint32_t bar_first = crit ? bar_wm : bar_wq;
    if (threadIdx.x == 256) {
        if (!crit) {
            mbar_init(bar_wq, 1);
            asm volatile("fence.mbarrier_init.release.cluster;" ::: "memory");
            mbar_expect_tx(bar_wq, D * 64);
            const uint32_t c0 = clock32();
            while (clock32() - c0 < WQ_DELAY) { }
#pragma unroll
            for (int r = 0; r < D; r += 160) tma2d(sb + X_WQ + r * 64, &tm_wq, 32 * cta, r, bar_wq);
        }
    } else if (threadIdx.x == 0) {
#pragma unroll
        for (int s = 0; s < NS; s++) { if (s) mbar_init(bar_full + s * 8, 1); mbar_init(bar_empty + s * 8, 4); }
        mbar_init(crit ? bar_wq : bar_wm, 1);
        mbar_init(bar_xfree, 1);
#pragma unroll
        for (int i = 0; i < 5; i++) { mbar_init(bar_wo + i * 8, 1); mbar_init(bar_w2 + i * 16, 1); mbar_init(bar_w2 + i * 16 + 8, 1); }
        mbar_init(bar_help, 1); mbar_init(bar_x1, 1);
#pragma unroll
        for (int i = 0; i < 4; i++) { mbar_init(bar_v + i * 8, 1); mbar_init(bar_w1 + i * 8, 1); mbar_init(bar_gb + i * 8, 1); }
        asm volatile("fence.mbarrier_init.release.cluster;" ::: "memory");
    }
    __syncthreads();

    if (warp == 8) {
        if (lane == 0) {
            int tp = NS;
            int sched = PACE_A - NS * PACE_TAU;
#pragma unroll 1
            for (int t = 1; t <= NITEM; t++) {
                if (t == 1) mbar_wait(bar_full, 0);
                if (t == 2) {
                    mbar_wait(bar_first, 0);
                    if (crit) {
                        mbar_expect_tx(bar_wq, D * 64);
#pragma unroll 1
                        for (int r = 0; r < D; r += 160) tma2d(sb + X_WQ + r * 64, &tm_wq, 32 * cta, r, bar_wq);
                    }
                }
                if (t == 3) {
                    asm volatile("prefetch.tensormap [%0];" ::"l"(&tm_v) : "memory");
                    asm volatile("prefetch.tensormap [%0];" ::"l"(&tm_wo) : "memory");
                    asm volatile("prefetch.tensormap [%0];" ::"l"(&tm_w1) : "memory");
                    asm volatile("prefetch.tensormap [%0];" ::"l"(&tm_w2) : "memory");
                    asm volatile("prefetch.tensormap [%0];" ::"l"(&tm_gb) : "memory");
                }
                if (t == NS && late) {
                    mbar_wait(bar_full + (NS - INFLIGHT) * 8, 0);
                    mbar_expect_tx(bar_wm, D * 64);
#pragma unroll 1
                    for (int r = 0; r < D; r += 160) tma2d(sb + X_WM + r * 64, &tm_wmod, 32 * mc, r, bar_wm);
                }
                if (t >= NS && t < PF_END) {
                    int it = 0;
                    while (!mbar_test(bar_empty + (t & (NS - 1)) * 8, ((t >> 3) - 1) & 1)) {
                        if (tp < PF_END && (int)(gtime32() - t_start) >= PACE_A + (tp - NS) * PACE_TAU) {
                            asm volatile("cp.async.bulk.prefetch.L2.global.L2::cache_hint [%0], %1, %2;"
                                         ::"l"(((tp & 1) ? vb : kb) + (size_t)(((tp >> 1) + rot) & (NITEM / 2 - 1)) * TILE_BYTES), "r"(TILE_BYTES), "l"(pol) : "memory");
                            tp++;
                        }
                        if (++it > 16 * SPIN_LIMIT) __trap();
                    }
                    if (tp <= t) tp = t + 1;
                }
                if (t == NITEM) {
                    mbar_wait(bar_xfree, 0);
                    const uint32_t t_ref = t_start + sched + LAT_T + (NITEM - 1) * PACE_TAU;
#pragma unroll 1
                    for (int i = 0; i < 5; i++) {
                        while ((int)(gtime32() - t_ref) < WO_T + i * WO_S) { }
                        mbar_expect_tx(bar_wo + i * 8, DH * 64);
                        tma2d(sb + X_WO + i * (DH * 64), &tm_wo, bown * 160 + i * 32, head * DH, bar_wo + i * 8);
                    }
                    if (gb_own) {
                        mbar_wait(bar_empty + 3 * 8, ((NITEM >> 3) - 1) & 1);
                        mbar_wait(bar_x1, 0);
                        { const uint32_t c0 = clock32(); while (clock32() - c0 < GB_EV) { } }
                        while ((int)(gtime32() - t_ref) < GB_T) { }
#pragma unroll 1
                        for (int i = 0; i < 4; i++) {
                            mbar_expect_tx(bar_gb + i * 8, 160 * 16);
                            tma2d(sb + X_GB + i * (160 * 16), &tm_gb, 5 * D + 8 * own, 160 * i, bar_gb + i * 8);
                        }
                    }
                    if (is_f) {
#pragma unroll 1
                        for (int i = 0; i < 3; i++) mbar_wait(bar_empty + i * 8, ((NITEM >> 3) - 1) & 1);
                        while ((int)(gtime32() - t_ref) < W1_T) { }
#pragma unroll 1
                        for (int i = 0; i < 4; i++) {
                            mbar_expect_tx(bar_w1 + i * 8, 160 * 64);
                            tma2d(sb + X_W1 + i * (160 * 64), &tm_w1, 32 * f, 160 * i, bar_w1 + i * 8);
                        }
                        while ((int)(gtime32() - t_ref) < W2_T) { }
#pragma unroll 1
                        for (int i = 0; i < 10; i++) {
                            mbar_expect_tx(bar_w2 + i * 8, 4096);
                            tma2d(sb + X_W2 + i * 4096, &tm_w2, 64 * i, 32 * f, bar_w2 + i * 8);
                        }
                    }
                    break;
                }
                const int s = t & (NS - 1);
                if (t >= NS) {
                    mbar_wait(bar_empty + s * 8, ((t >> 3) - 1) & 1);
                    while ((int)(gtime32() - t_start) < sched + t * PACE_TAU) { }
                } else if (t >= INFLIGHT) {
                    mbar_wait(bar_full + (t - INFLIGHT) * 8, 0);
                }
                if (t < NITEM - 2) {
                    const int pair = t == NITEM - 3 ? NITEM / 2 - 1 : t >> 1;
                    mbar_expect_tx(bar_full + s * 8, TILE_BYTES);
                    bulk_load(sb + OFF_RING + s * TILE_BYTES, ((t & 1) && t != NITEM - 3 ? vb : kb) + (size_t)((pair + rot) & (NITEM / 2 - 1)) * TILE_BYTES, TILE_BYTES, bar_full + s * 8, pol);
                } else {
                    const int row = (bown * NH + head) * SK + (SK - WIN) + ((t - NITEM / 2 + rot) & (NITEM / 2 - 1)) * TILE_KEYS;
#pragma unroll 1
                    for (int i = 0; i < 2; i++) {
                        const uint32_t bar = bar_v + (2 * (t - (NITEM - 2)) + i) * 8;
                        mbar_expect_tx(bar, TILE_BYTES / 2);
                        tma2d_hint(sb + OFF_RING + s * TILE_BYTES + i * (TILE_BYTES / 2), &tm_v, 64 * i, row, bar, pol);
                    }
                }
                if (t >= PH_FIRST + PH_LAG && (t & 3) == (PH_LAG & 3)) {
                    const int now = (int)(gtime32() - t_start) - (t - PH_LAG) * PACE_TAU;
                    uint32_t ph;
                    asm volatile("atom.relaxed.gpu.global.add.u32 %0, [%1], 0;" : "=r"(ph) : "l"(g_phase + ((t - PH_LAG) >> 2) * 32) : "memory");
                    sched = (int)min(((ph & 0xffffffu) * 4 + (NCTA - (ph >> 24)) * now) >> 7, 65535u) - LAT_T;
                }
            }
        }
        __syncwarp();
    }

    if (warp == 9) {
        int side = 0;
        if (lane == 0) {
            uint32_t best[2] = {~0u, ~0u};
#pragma unroll 1
            for (int i = 0; i < 2 * NPROBE && ((i & 1) || (int)(gtime32() - t_start) < PROBE_END); i++) {
                uint32_t t0 = clock32(), v, t1;
                asm volatile("atom.relaxed.gpu.global.exch.b32 %0, [%1], %2;" : "=r"(v) : "l"(slot(SL_SIDE, i & 1) + cta * 8), "r"(0u) : "memory");
                asm volatile("{\n.reg .pred p;\nsetp.ne.u32 p, %1, 0xffffffff;\nmov.u32 %0, 0;\n@p mov.u32 %0, %%clock;\n}" : "=r"(t1) : "r"(v) : "memory");
                if (i & 1) best[1] = min(best[1], t1 - t0); else best[0] = min(best[0], t1 - t0);
            }
            side = best[1] < best[0];
        }
        side = __shfl_sync(0xffffffffu, side, 0);
        HPROF(1);
        mbar_wait(bar_full + (NS - 1) * 8, 0);
        stg_zero4(slot(SL_O + (cta >> 4), lane >> 4) + (cta & 15) * 64 + (lane & 15) * 4);
        if (is_owner) {
#pragma unroll 1
            for (int i = lane; i < NH * 8; i += 32) stg_zero4(slot(SL_P1 + own, side) + i * 4);
#pragma unroll 1
            for (int i = lane; i < NF * 8; i += 32) stg_zero4(slot(SL_P2 + 2 * own + (i >> 8), side) + (i & 255) * 4);
            if (lane < 8) stg_zero4(slot(SL_X1 + own / 30, lane >> 2) + (own % 30) * 32 + (lane & 3) * 4);
        }
        __threadfence();
        __syncwarp();
        if (lane == 0) stg_relaxed(g_clr + cta, 1u + side);
        HPROF(0);
        HPROF(2);
        while ((int)(gtime32() - t_start) < CLR_CHECK) __nanosleep(1000);
        mbar_wait(bar_xfree, 0);
        {
            uint4 v = make_uint4(1, 1, 1, 1), gv = v, mv[20];
#pragma unroll
            for (int i = 0; i < 20; i++) mv[i] = v;
#pragma unroll 1
            for (int it = 0;; it++) {
                v = ldg_relaxed(g_clr + lane * 4);

                ldg_relaxed_if(is_owner && lane < (gb_own ? 4 : 8), gv, mod_slot(lane < 4 ? 2 : 5, own, lane & 3));
#pragma unroll
                for (int i = 0; i < 20; i++) ldg_relaxed_if(is_f, mv[i], mod_slot(3, 8 * i + (lane >> 2), lane & 3));
                bool ok = ready(v) && ready(gv);
#pragma unroll
                for (int i = 0; i < 20; i++) ok = ok && ready(mv[i]);
                if (__all_sync(0xffffffffu, ok)) break;
                if (it > SPIN_LIMIT) __trap();
                __nanosleep(2000);
            }
            const uint32_t w[4] = {v.x, v.y, v.z, v.w};
#pragma unroll
            for (int i = 0; i < 4; i++) {
                const Roles r = roles(4 * lane + i);
                if (r.is_owner) {
                    sts32(sb + OFF_TAB1 + r.own * 4, (uint32_t)(size_t)(slot(SL_P1 + r.own, w[i] - 1) + head * 32));
                    sts32(sb + OFF_TAB2 + r.own * 4, (uint32_t)(size_t)(slot(SL_P2 + 2 * r.own + (f >> 5), w[i] - 1) + (f & 31) * 32));
                }
            }
            if (lane == 0) sts32(sb + OFF_SIDE, side);
            if (lane < 8) sts128(sb + OWN_GA + lane * 16, inv4(gv));
            const uint32_t dst = sb + OFF_VB + (lane & 3) * VEC_STRIDE + (lane >> 2) * 16;
#pragma unroll
            for (int i = 0; i < 10; i++) {
                const uint4 c = inv4(mv[10 + i]);
                sts128(dst + i * 128, make_uint4(bf2_add(c.x, 0x3f803f80u), bf2_add(c.y, 0x3f803f80u), bf2_add(c.z, 0x3f803f80u), bf2_add(c.w, 0x3f803f80u)));
                sts128(dst + (OFF_RED - OFF_VB) + i * 128, inv4(mv[i]));
            }
        }
        asm volatile("fence.acq_rel.gpu;" ::: "memory");
        __syncwarp();
        HPROF(3);
        if (lane == 0) mbar_arrive(bar_help);
        {
            const uint32_t* const src = pin(slot(SL_O + (cta >> 4), side) + (cta & 12) * 64 + lane * 4);
            const uint32_t dst = pin(sb + OFF_O + (lane >> 4) * O_STRIDE + (lane & 15) * 16);
            mbar_wait(bar_v + 16, 0);
            mbar_wait(bar_v + 24, 0);
            uint4 v[2];
            const uint32_t* const ptr[2] = {src, src + 128};
            const bool on[2] = {true, true};
            poll_n<2>(v, ptr, on);
            sts128(dst, v[0]);
            sts128(dst + 2 * O_STRIDE, v[1]);
#pragma unroll
            for (int w = 0; w < 8; w++) asm volatile("bar.arrive %0, 64;" ::"r"(NB_O + w) : "memory");
        }
        HPROF(4);
    }
    if (warp >= 8) {
        if (gb_own && warp == 9) {
            uint32_t a[20][4];
#pragma unroll
            for (int i = 0; i < 20; i++) ldsm4(a[i], sb + OFF_VA + (lane & 3) * VEC_STRIDE + (4 * i + (lane >> 3)) * 16);
            float c[4][4];
#pragma unroll
            for (int i = 0; i < 4; i++) c[i][0] = c[i][1] = c[i][2] = c[i][3] = 0.f;
#pragma unroll
            for (int bx = 0; bx < 4; bx++) {
                mbar_wait(bar_gb + bx * 8, 0);
#pragma unroll
                for (int i = 5 * bx; i < 5 * bx + 5; i++) {
                    uint32_t w[4];
                    ldsm4t(w, sb + X_GB + (32 * i + lane) * 16);
                    const uint32_t a0[4] = {a[i][0], 0u, a[i][1], 0u}, a1[4] = {a[i][2], 0u, a[i][3], 0u};
                    mma16816(c[(2 * i) & 3], a0, w[0], w[1]);
                    mma16816(c[(2 * i + 1) & 3], a1, w[2], w[3]);
                }
            }
            if (lane < 16) sts32(sb + OWN_GB + lane * 4, pack_bf((c[0][0] + c[1][0]) + (c[2][0] + c[3][0]), (c[0][1] + c[1][1]) + (c[2][1] + c[3][1])));
            HPROF(6);
        }
        if (is_owner && warp == 9) nbar_arrive<NB_E6, 288>();
        if (is_f) gelu_stage(sb, warp - 8, lane);
        return;
    }

    const int g = lane >> 2, t4 = lane & 3;
    const int mi = lane >> 3, r8 = lane & 7;

    {
        auto silu4 = [&](const uint4& cv) {
            uint32_t w4[4] = {cv.x, cv.y, cv.z, cv.w};
#pragma unroll
            for (int e = 0; e < 4; e++) {
                float c0 = bf_lo(w4[e]), c1 = bf_hi(w4[e]);
                w4[e] = pack_bf(c0 * rcp_fast(1.f + ex2(-1.4426950408889634f * c0)), c1 * rcp_fast(1.f + ex2(-1.4426950408889634f * c1)));
            }
            return make_uint4(w4[0], w4[1], w4[2], w4[3]);
        };
        {
            uint4 v = silu4(ca0);
            sts128(sb + OFF_VA + (tid / 80) * VEC_STRIDE + (tid % 80) * 16, v);
            if (tid < 64) { v = silu4(ca1); sts128(sb + OFF_VA + 3 * VEC_STRIDE + (16 + tid) * 16, v); }
        }
        if (warp < 4) {
            float s = 0.f, q = 0.f;
            const float pv = __shfl_sync(0xffffffffu, bf_lo(xs[0].x), 0);
#pragma unroll
            for (int i = 0; i < 3; i++) if (i < 2 || lane < 16) acc_stats(xs[i], pv, s, q);
#pragma unroll
            for (int of = 16; of > 0; of >>= 1) { s += __shfl_xor_sync(0xffffffffu, s, of); q += __shfl_xor_sync(0xffffffffu, q, of); }
            uint32_t m2; float rden;
            ln_finish(pv, s, q, m2, rden);
            if (lane == 0) { sts32(sb + OFF_STAT + warp * 8, m2); sts_f32(sb + OFF_STAT + warp * 8 + 4, rden); }
        } else if (warp == 4) {
            sts32(sb + OWN_X + lane * 4, bf2_add(own0, 0u));
            sts_f32(sb + OWN_B1 + lane * 4, bf2f(own2));
        }
    }
    bar_cons();
    PROF(24);
    uint32_t qf[8][2];
    float o[8][4];
#pragma unroll
    for (int c = 0; c < 8; c++) { o[c][0] = o[c][1] = o[c][2] = o[c][3] = 0.f; }
    float m_run = -INFINITY, l_run = 0.f;
    const bool diag = (t4 == (g >> 1));
    const bool odd = g & 1;
    const uint32_t koff = (warp & 3) * 4096 + (r8 + 8 * (mi & 1)) * 256 + (mi >> 1) * 128 + (r8 << 4);
    const uint32_t voff = TILE_BYTES + (warp & 3) * 4096 + (r8 + 8 * (mi >> 1)) * 256 + (mi & 1) * 128 + (r8 << 4);
    const int src0 = (2 * t4) * 4 + t4, src1 = (2 * t4 + 1) * 4 + t4;
#pragma unroll 1
    for (int step = crit ? 0 : 1; step < 3; step++) {
        if (step < 2 || late) {
            if (step == 1) {
                if (!crit) mbar_wait(bar_wq, 0);
                const uint32_t m2 = lds32(sb + OFF_STAT + (tid & 3) * 8);
                const float rden = lds_f32(sb + OFF_STAT + (tid & 3) * 8 + 4);
                uint4 v[4] = {xa, xa, xa, xa};
                const uint32_t* const ptr[4] = {mod_slot(0, tid >> 2, tid & 3), mod_slot(1, tid >> 2, tid & 3),
                                                mod_slot(0, 64 + ((tid & 63) >> 2), tid & 3), mod_slot(1, 64 + ((tid & 63) >> 2), tid & 3)};
                const bool on[4] = {true, true, tid < 64, tid < 64};
                while ((int)(gtime32() - t_start) < MOD_T) { }
                PROF(2);
                poll_n<4>(v, ptr, on);
                PROF(3);
                uint4 h0 = ln_mod4(xa, v[1], v[0], m2, rden);
                sts128(sb + OFF_VB + (tid & 3) * VEC_STRIDE + (tid >> 2) * 16, h0);
                if (tid < 64) {
                    h0 = ln_mod4(xb, v[3], v[2], m2, rden);
                    sts128(sb + OFF_VB + (tid & 3) * VEC_STRIDE + (64 + (tid >> 2)) * 16, h0);
                }
            }
            mbar_wait(step == 1 ? bar_wq : bar_wm, 0);
            bar_cons();
            const uint32_t strip = sb + (step == 1 ? X_WQ : X_WM), vec = sb + (step == 1 ? OFF_VB : OFF_VA);
            float acc[2][4];
#pragma unroll
            for (int m = 0; m < 2; m++) { acc[m][0] = acc[m][1] = acc[m][2] = acc[m][3] = 0.f; }
#pragma unroll
            for (int i = 0; i < 5; i++) {
                int k0 = (warp * 5 + i) * 16;
                uint32_t b0, b1;
                load_bfrag(vec, VEC_STRIDE, k0, g, t4, b0, b1);
                int krow = k0 + r8 + 8 * (mi >> 1);
#pragma unroll
                for (int m = 0; m < 2; m++) {
                    uint32_t a[4];
                    int ch = 2 * m + (mi & 1);
                    ldsm4t(a, strip + krow * 64 + ((ch ^ ((krow >> 1) & 3)) << 4));
                    mma16816(acc[m], a, b0, b1);
                }
            }
            if (t4 < 2) {
#pragma unroll
                for (int m = 0; m < 2; m++) {
                    sts_f32x2(sb + OFF_RED + ((warp * 32 + m * 16 + g) * 4 + 2 * t4) * 4, acc[m][0], acc[m][1]);
                    sts_f32x2(sb + OFF_RED + ((warp * 32 + m * 16 + g + 8) * 4 + 2 * t4) * 4, acc[m][2], acc[m][3]);
                }
            }
            bar_cons();
            if (tid < 64) {
                float v0 = 0.f, v1 = 0.f;
#pragma unroll
                for (int w = 0; w < 8; w++) {
                    v0 += lds_f32(sb + OFF_RED + (w * 128 + (tid & 15) * 8 + (tid >> 4)) * 4);
                    v1 += lds_f32(sb + OFF_RED + (w * 128 + (tid & 15) * 8 + 4 + (tid >> 4)) * 4);
                }
                stg_relaxed(step == 1 ? g_q + (((cta & ~3) + (tid >> 4)) * 4 + bown) * 32 + (tid & 15) : g_mod + mc * 64 + tid, ~pack_bf(v0, v1));
            }
        }
        if (step == 0) continue;
        if (step == 1) {
            if (warp == 0) {
                { const uint32_t c0 = clock32(); while (clock32() - c0 < Q_PAUSE) { } }
                uint4 v = poll1(g_q + (cta * 4 + ((lane >> 2) & 3)) * 32 + (lane & 3) * 4, lane < 16);
                if (lane < 16) {
                    sts128(sb + OFF_Q + lane * 16, v);
                    stg_zero4(g_q + (cta * 4 + (lane >> 2)) * 32 + (lane & 3) * 4);
                }
            }
            bar_cons();
            PROF(4);

#pragma unroll
            for (int c = 0; c < 8; c++) {
                qf[c][0] = lds32(sb + OFF_Q + (((c ^ g) * 4 + t4) << 2));
                qf[c][1] = lds32(sb + OFF_Q + 128 + (((c ^ g) * 4 + t4) << 2));
            }
        } else {
            bar_cons();
            if (tid == 0) mbar_arrive(bar_xfree);
        }
#pragma unroll 1
        for (int j = (step == 1 ? 0 : SEG_J) + (warp >> 2); j < (step == 1 ? SEG_J : NITEM / 2 - 2); j += 2) {
            const int s = (2 * j) & (NS - 1);
            const uint32_t par = (j >> 2) & 1;
            mbar_wait(bar_full + s * 8, par);
            if (tid == 0 && 2 * j >= PH_FIRST) {
                const int x = min(max((int)(gtime32() - t_start) - 2 * j * PACE_TAU, 0), 65535);
                asm volatile("red.relaxed.gpu.global.add.u32 [%0], %1;" ::"l"(g_phase + (j >> 1) * 32), "r"((1u << 24) + (x >> 2)) : "memory");
            }
            const uint32_t base = sb + OFF_RING + s * TILE_BYTES;
            float sa[4] = {0.f, 0.f, 0.f, 0.f}, sb2[4] = {0.f, 0.f, 0.f, 0.f};
#pragma unroll
            for (int c = 0; c < 8; c += 2) {
                uint32_t a[4], a2[4];
                ldsm4(a, (base + koff) ^ (c << 4));
                ldsm4(a2, (base + koff) ^ ((c + 1) << 4));
                mma16816(sa, a, qf[c][0], qf[c][1]);
                mma16816(sb2, a2, qf[c + 1][0], qf[c + 1][1]);
            }
            const uint32_t sw = pack_bf(odd ? sa[1] + sb2[1] : sa[0] + sb2[0], odd ? sa[3] + sb2[3] : sa[2] + sb2[2]);
            const uint32_t sv = pack_bf(bf_lo(sw) * 0.08838834764831845f, bf_hi(sw) * 0.08838834764831845f);
            const float s0 = bf_lo(sv) * 1.4426950408889634f, s1 = bf_hi(sv) * 1.4426950408889634f;
            float m_new = fmaxf(m_run, fmaxf(s0, s1));
            const bool grow = __any_sync(0xffffffffu, (diag && (m_new > m_run)));
            if (lane == 0) mbar_arrive(bar_empty + s * 8);
            if (grow) {
                float al = ex2(m_run - m_new);
                float a0 = __shfl_sync(0xffffffffu, al, src0), a1 = __shfl_sync(0xffffffffu, al, src1);
#pragma unroll
                for (int c = 0; c < 8; c++) { o[c][0] *= a0; o[c][1] *= a1; o[c][2] *= a0; o[c][3] *= a1; }
                l_run *= al;
                m_run = m_new;
            }
            uint32_t pw = pack_bf(ex2(s0 - m_run), ex2(s1 - m_run));
            l_run += bf_lo(pw) + bf_hi(pw);
            uint32_t b0 = odd ? (pw << 16) : (pw & 0xffffu);
            uint32_t b1 = odd ? (pw & 0xffff0000u) : (pw >> 16);
            if (!diag) { b0 = 0u; b1 = 0u; }
            mbar_wait(bar_full + (s + 1) * 8, par);
#pragma unroll
            for (int c = 0; c < 8; c++) {
                uint32_t a[4];
                ldsm4t(a, (base + voff) ^ (c << 4));
                mma16816(o[c], a, b0, b1);
            }
            __syncwarp();
            if (lane == 0) mbar_arrive(bar_empty + (s + 1) * 8);
        }
    }
    PROF(5);
    float acc[4][4];
    uint32_t pa[8][2];
    float rinv;
    {
        const int s = 4 + (warp >> 2);
        mbar_wait(bar_full + s * 8, 1);
        const uint32_t base = sb + OFF_RING + s * TILE_BYTES;
        float sa[4] = {0.f, 0.f, 0.f, 0.f}, sb2[4] = {0.f, 0.f, 0.f, 0.f};
#pragma unroll
        for (int c = 0; c < 8; c += 2) {
            uint32_t a[4], a2[4];
            ldsm4(a, (base + koff) ^ (c << 4));
            ldsm4(a2, (base + koff) ^ ((c + 1) << 4));
            mma16816(sa, a, qf[c][0], qf[c][1]);
            mma16816(sb2, a2, qf[c + 1][0], qf[c + 1][1]);
        }
        const uint32_t sw = pack_bf(odd ? sa[1] + sb2[1] : sa[0] + sb2[0], odd ? sa[3] + sb2[3] : sa[2] + sb2[2]);
        const uint32_t sv = pack_bf(bf_lo(sw) * 0.08838834764831845f, bf_hi(sw) * 0.08838834764831845f);
        const float s0 = bf_lo(sv) * 1.4426950408889634f, s1 = bf_hi(sv) * 1.4426950408889634f;
        int mi_ = __float_as_int(diag ? fmaxf(m_run, fmaxf(s0, s1)) : -INFINITY);
        mi_ ^= (mi_ >> 31) & 0x7fffffff;
        mi_ = __reduce_max_sync(0xffffffffu, mi_);
        mi_ ^= (mi_ >> 31) & 0x7fffffff;
        if (lane == 0) sts32(sb + OFF_ML + warp * 4, mi_);
        bar_cons();
        const float4 m0 = lds_f32x4(sb + OFF_ML), m1 = lds_f32x4(sb + OFF_ML + 16);
        const float mx = fmaxf(fmaxf(fmaxf(m0.x, m0.y), fmaxf(m0.z, m0.w)), fmaxf(fmaxf(m1.x, m1.y), fmaxf(m1.z, m1.w)));
        const float scl = ex2(m_run - mx);
        const uint32_t pw = pack_bf(ex2(s0 - mx), ex2(s1 - mx));
        if (diag) { sts16(sb + SC_P + (warp * 16 + g) * 2, pw); sts16(sb + SC_P + (warp * 16 + g + 8) * 2, pw >> 16); }
        const float lw = warp_sum(diag ? fmaf(l_run, scl, bf_lo(pw) + bf_hi(pw)) : 0.f);
        const float a0 = __shfl_sync(0xffffffffu, scl, src0), a1 = __shfl_sync(0xffffffffu, scl, src1);
        float v[8], u[8];
#pragma unroll
        for (int c = 0; c < 8; c++) {
            v[c] = a0 * o[c][0] + a1 * o[c ^ 1][1];
            u[c] = a0 * o[c][2] + a1 * o[c ^ 1][3];
        }
#pragma unroll
        for (int c = 0; c < 8; c++) {
            if (!(c & 2)) {
                v[c] += __shfl_xor_sync(0xffffffffu, v[c ^ 2], 1);
                u[c] += __shfl_xor_sync(0xffffffffu, u[c ^ 2], 1);
            }
        }
#pragma unroll
        for (int c = 0; c < 2; c++) {
            v[c] += __shfl_xor_sync(0xffffffffu, v[c ^ 4], 2);
            u[c] += __shfl_xor_sync(0xffffffffu, u[c ^ 4], 2);
        }
        const uint32_t dst = sb + SC_OP + (warp * 128 + 16 * t4 + g) * 4;
        sts_f32(dst, v[0]); sts_f32(dst + 32, v[1]); sts_f32(dst + 256, u[0]); sts_f32(dst + 288, u[1]);
        if (lane == 0) sts_f32(sb + OFF_ML + 32 + warp * 4, lw);
        mbar_wait(bar_help, 0);
        bar_cons();
        const float4 l0 = lds_f32x4(sb + OFF_ML + 32), l1 = lds_f32x4(sb + OFF_ML + 48);
        rinv = rcp_fast(((l0.x + l0.y) + (l0.z + l0.w)) + ((l1.x + l1.y) + (l1.z + l1.w)));
#pragma unroll
        for (int i = 0; i < 4; i++) acc[i][0] = acc[i][1] = acc[i][2] = acc[i][3] = 0.f;
#pragma unroll
        for (int w = 0; w < 8; w++) {
            const float2 x0 = lds_f32x2(sb + SC_OP + (w * 128 + 16 * warp + 2 * t4) * 4), x1 = lds_f32x2(sb + SC_OP + (w * 128 + 16 * warp + 8 + 2 * t4) * 4);
            acc[2 * (w & 1)][0] += x0.x; acc[2 * (w & 1)][1] += x0.y;
            acc[2 * (w & 1) + 1][0] += x1.x; acc[2 * (w & 1) + 1][1] += x1.y;
        }
#pragma unroll
        for (int ks = 0; ks < 8; ks++) { pa[ks][0] = lds32(sb + SC_P + (8 * ks + t4) * 4); pa[ks][1] = lds32(sb + SC_P + (8 * ks + 4 + t4) * 4); }
    }
    PROF(20);
    const int mt = warp < 2 ? warp : warp + 2;
    {
        const uint32_t va = pin(sb + OFF_RING + 6 * TILE_BYTES + (warp >> 2) * (TILE_BYTES / 2) + (8 * (mi & 1) + r8) * 128 + (((2 * (warp & 3) + (mi >> 1)) ^ r8) << 4));
        const uint32_t vbar = pin(bar_v + (warp >> 2) * 8);
        uint32_t* const o_dst = pin(slot(SL_O + (cta >> 4), g) + (cta & 15) * 64 + warp * 8 + 2 * t4);
#pragma unroll
        for (int tl = 0; tl < 2; tl++) {
            mbar_wait(vbar + tl * 16, 0);
            uint32_t r[4][4];
#pragma unroll
            for (int ks = 0; ks < 4; ks++) ldsm4t(r[ks], va + tl * TILE_BYTES + ks * 2048);
#pragma unroll
            for (int ks = 0; ks < 4; ks++) {
                const uint32_t a[4] = {pa[4 * tl + ks][0], 0u, pa[4 * tl + ks][1], 0u};
                mma16816(acc[2 * (ks & 1)], a, r[ks][0], r[ks][1]);
                mma16816(acc[2 * (ks & 1) + 1], a, r[ks][2], r[ks][3]);
            }
        }
        stg_relaxed2_if(g < 2, o_dst, ~pack_bf((acc[0][0] + acc[2][0]) * rinv, (acc[0][1] + acc[2][1]) * rinv),
                        ~pack_bf((acc[1][0] + acc[3][0]) * rinv, (acc[1][1] + acc[3][1]) * rinv));
    }
    PROF(7);
    const int side = lds32(sb + OFF_SIDE);
    const uint32_t red_st = pin(sb + SC_E4 + ((warp * 4 + 2 * ((lane >> 3) & 1) + (lane >> 4)) * 8 + (lane & 7)) * 4);
    const uint32_t red_ld = pin(sb + SC_E4 + (lane & 15) * 8);
    const uint32_t* const in1 = pin(slot(SL_P1 + own, side) + tid * 4);
    const uint32_t* const in2a = pin(slot(SL_P2 + 2 * own, side) + tid * 4);
    const uint32_t* const in2b = pin(slot(SL_P2 + 2 * own + 1, side) + tid * 4);
    uint32_t* const out_dst = pin((uint32_t*)(p.out + ((lane >> 2) & 3) * D + 8 * own) + t4);
    uint32_t* const x1_dst = pin(slot(SL_X1 + own / 30, lane >> 4) + (own % 30) * 32 + (lane & 15));
    uint32_t* const rst = pin(tid >= 32 && tid < 56 ? mod_slot(lane >> 2, own, lane & 3) : own < 32 && tid == 64 ? g_clr + own * 4 : own < 16 && tid == 96 ? g_phase + own * 32 : nullptr);
    const uint32_t xw = lds32(sb + OWN_X + (lane & 15) * 4), ga_w = lds32(sb + OWN_GA + (lane & 15) * 4);
    uint32_t cs[15];
    uint32_t* dst2[5];
    uint32_t w2a[5];
#pragma unroll
    for (int j = 0; j < 10; j++) cs[j] = lds32(sb + OFF_VB + ((g & 1) * 4 + (g >> 1)) * VEC_STRIDE + warp * 160 + t4 * 4 + j * 16);
#pragma unroll
    for (int i = 0; i < 5; i++) {
        cs[10 + i] = lds32(sb + OFF_VB + (g >> 1) * VEC_STRIDE + warp * 160 + (g & 1) * 16 + t4 * 4 + i * 32);
        const uint2 t = lds64(sb + OFF_TAB2 + warp * 40 + i * 8);
        dst2[i] = slot_ptr((t4 < 2 ? t.x : t.y) + g * 16 + (t4 & 1) * 8);
        const int cc = 2 * (warp * 5 + i) + (mi & 1);
        w2a[i] = pin(sb + X_W2 + (cc >> 3) * 4096 + (r8 + 8 * (mi >> 1)) * 128 + (((cc & 7) ^ r8) << 4));
    }
    const uint32_t piv = lds32(sb + OFF_STAT + (g >> 1) * 8);
    const uint32_t* const xin = pin(slot(SL_X1 + warp / 3, side) + ((warp % 3) * 10 + (g & 1)) * 32 + (g >> 1) * 4 + t4);
    const uint32_t w1a = pin(sb + X_W1 + (warp * 80 + r8 + 8 * (mi >> 1)) * 64 + (((mi & 1) ^ ((r8 >> 1) & 3)) << 4));
    const uint32_t w1bar = pin(bar_w1 + (warp >> 1) * 8), w2bar = pin(bar_w2 + (warp + (warp >> 2)) * 8);
    const uint32_t wbar = pin(NB_O + warp);
    const uint32_t ab_st = pin(sb + SC_AB + warp * 1024 + lane * 16), y_st = pin(sb + SC_Y + warp * 512 + lane * 8), s_st = pin(sb + SC_ST + (t4 * 8 + warp) * 8);
    const uint32_t h_ld = pin(sb + SC_H1 + ((g & 3) ^ (2 * (f & 1) + ((f >> 1) & 1))) * 64 + t4 * 16);
    {
        const int kap = 2 * (head & 1) + ((head >> 1) & 1);
        const uint32_t wa = pin(sb + X_WO + (mt >> 1) * (DH * 64) + (r8 + 8 * (mi >> 1)) * 64 + ((((mt & 1) * 2 + (mi & 1)) ^ ((r8 >> 1) & 3)) << 4));
        const uint32_t oa = pin(sb + OFF_O + ((g & 3) ^ kap) * O_STRIDE + t4 * 8);
        uint32_t* dst[4];
#pragma unroll
        for (int i = 0; i < 2; i++) {
            const uint2 t = lds64(sb + OFF_TAB1 + (bown * 20 + 2 * mt + (warp < 2 ? 4 * i : 0)) * 4);
            dst[2 * i] = slot_ptr(t.x + g * 16 + t4 * 8);
            dst[2 * i + 1] = slot_ptr(t.y + g * 16 + t4 * 8);
        }
        PROF(6);
        const uint32_t wobar = pin(bar_wo + (mt >> 1) * 8);
        asm volatile("bar.sync %0, 64;" ::"r"(wbar) : "memory");
        uint2 ob[8];
#pragma unroll
        for (int ks = 0; ks < 8; ks++) ob[ks] = lds64(oa + ks * 32);
#pragma unroll
        for (int m = 0; m < 2; m++) {
            if (m == 0 || warp < 2) {
                mbar_wait(wobar + m * 8, 0);
                PROF(8);
                uint32_t wf[8][4];
#pragma unroll
                for (int ks = 0; ks < 8; ks++) ldsm4t(wf[ks], wa + m * (DH * 64) + ks * 1024);
                float c[4][4];
#pragma unroll
                for (int ks = 0; ks < 8; ks++) {
                    if (ks < 4) c[ks][0] = c[ks][1] = c[ks][2] = c[ks][3] = 0.f;
                    mma16816(c[ks & 3], wf[ks], ob[ks].x, ob[ks].y);
                }
                stg_relaxed2_if(t4 < 2, dst[2 * m], flag((c[0][0] + c[1][0]) + (c[2][0] + c[3][0])), flag((c[0][1] + c[1][1]) + (c[2][1] + c[3][1])));
                stg_relaxed2_if(t4 < 2, dst[2 * m + 1], flag((c[0][2] + c[1][2]) + (c[2][2] + c[3][2])), flag((c[0][3] + c[1][3]) + (c[2][3] + c[3][3])));
            }
        }
    }
    PROF(9);
    uint32_t x1w = 0;
    if (is_owner) {
        uint4 v;
        for (int it = 0;; it++) {
            v = ldg_relaxed(in1);
            if (__all_sync(0xffffffffu, and3(and3(v.x, v.y, v.z), v.w, 1u))) break;
            if (it > SPIN_LIMIT) __trap();
        }
        PROF(11);
        const float s0 = __uint_as_float(v.x) + __shfl_xor_sync(0xffffffffu, __uint_as_float(v.z), 8);
        const float s1 = __uint_as_float(v.y) + __shfl_xor_sync(0xffffffffu, __uint_as_float(v.w), 8);
        sts_f32(red_st, s0 + __shfl_xor_sync(0xffffffffu, s1, 16));
        nbar_sync<NB_E4, 256>();
        if (warp == 0) {
            float2 a[8];
#pragma unroll
            for (int w = 0; w < 8; w++) a[w] = lds_f32x2(red_ld + w * 128);
            const uint32_t aw = pack_bf(((a[0].x + a[1].x) + (a[2].x + a[3].x)) + ((a[4].x + a[5].x) + (a[6].x + a[7].x)),
                                        ((a[0].y + a[1].y) + (a[2].y + a[3].y)) + ((a[4].y + a[5].y) + (a[6].y + a[7].y)));
            x1w = bf2_add(xw, bf2_mul(ga_w, aw));
            stg_relaxed(x1_dst, x1w ^ 0x80008000u);
            if (lane == 0) mbar_arrive(bar_x1);
        }
        if (rst) stg_zero4(rst);
    }
    PROF(12);
    if (is_f) {
        uint32_t f1[5][2][4], f2[5][2][4];
        uint32_t d[6];
        auto load_x1 = [&] {
#pragma unroll
            for (int i = 0; i < 5; i++) d[i] = ldg_relaxed32(xin + i * 64);
        };
        auto have_x1 = [&] { return __all_sync(0xffffffffu, __vimin3_u32(__vimin3_u32(d[0], d[1], d[2]), d[3], d[4]) != 0u); };
        mbar_wait(w1bar, 0);
        load_x1();
        {
#pragma unroll
            for (int i = 0; i < 5; i++) { ldsm4t(f1[i][0], w1a + i * 1024); ldsm4t(f1[i][1], (w1a ^ 32) + i * 1024); }
            float c[2][4];
#pragma unroll
            for (int m = 0; m < 2; m++) c[m][0] = c[m][1] = c[m][2] = c[m][3] = 0.f;
#pragma unroll
            for (int i = 0; i < 5; i++) { mma16816(c[0], f1[i][0], cs[2 * i], cs[2 * i + 1]); mma16816(c[1], f1[i][1], cs[2 * i], cs[2 * i + 1]); }
#pragma unroll
            for (int i = 0; i < 5; i++) { cs[2 * i] = pin(odd ? 0u : cs[10 + i]); cs[2 * i + 1] = pin(odd ? cs[10 + i] : 0u); }
#pragma unroll
            for (int m = 0; m < 2; m++) sts128(ab_st + m * 512, make_uint4(__float_as_uint(c[m][0]), __float_as_uint(c[m][1]), __float_as_uint(c[m][2]), __float_as_uint(c[m][3])));
            nbar_arrive<NB_AB, 320>();
            d[0] |= __float_as_uint(c[1][3]) & (side >> 1);
        }
        PROF(10);
#pragma unroll 1
        for (int it = 0; !have_x1(); it++) {
            load_x1();
            if (it > SPIN_LIMIT) __trap();
        }
        PROF(13);
        {
            float y[2][4], st[4] = {0.f, 0.f, 0.f, 0.f};
#pragma unroll
            for (int m = 0; m < 2; m++) y[m][0] = y[m][1] = y[m][2] = y[m][3] = 0.f;
#pragma unroll
            for (int i = 0; i < 5; i++) d[i] = bf2_add(d[i], piv);
            d[5] = 0u;
#pragma unroll
            for (int i = 0; i < 5; i++) {
                if (i < 3) {
                    const uint32_t a[4] = {d[2 * i], 0x3f803f80u, d[2 * i + 1], 0x3f803f80u};
                    mma16816(st, a, d[2 * i], d[2 * i + 1]);
                }
                const uint32_t y0 = bf2_mul(d[i], cs[2 * i]), y1 = bf2_mul(d[i], cs[2 * i + 1]);
                mma16816(y[0], f1[i][0], y0, y1);
                mma16816(y[1], f1[i][1], y0, y1);
            }
            const float q = odd ? st[1] : st[0];
            const float q2 = q + __shfl_xor_sync(0xffffffffu, q, 4);
            if (diag && !odd) sts_f32x2(s_st, q2, st[2] + st[3]);
#pragma unroll
            for (int m = 0; m < 2; m++) sts_f32x2(y_st + m * 256, y[m][0] + y[m][1], y[m][2] + y[m][3]);
        }
        nbar_arrive<NB_Y, 320>();
        PROF(14);
        mbar_wait(w2bar, 0);
        mbar_wait(w2bar + 8, 0);
#pragma unroll
        for (int i = 0; i < 5; i++) { ldsm4t(f2[i][0], w2a[i]); ldsm4t(f2[i][1], w2a[i] + 2048); }
        asm volatile("bar.sync %0, 96;" ::"r"(wbar) : "memory");
        PROF(15);
        {
            const uint4 hb = lds128(h_ld);
            float c[5][4];
#pragma unroll
            for (int i = 0; i < 5; i++) { c[i][0] = c[i][1] = c[i][2] = c[i][3] = 0.f; mma16816(c[i], f2[i][0], hb.x, hb.y); }
#pragma unroll
            for (int i = 0; i < 5; i++) {
                mma16816(c[i], f2[i][1], hb.z, hb.w);
                stg_relaxed2_if(true, dst2[i], flag(t4 < 2 ? c[i][0] : c[i][2]), flag(t4 < 2 ? c[i][1] : c[i][3]));
            }
        }
    }
    PROF(16);
    if (is_owner) {
        const uint32_t b2w = lds32(sb + OWN_B2 + (lane & 15) * 4), gb_ld = pin(sb + OWN_GB + (lane & 15) * 4);
        const bool two = tid < NF * 8 - 256;
        uint4 v, w = make_uint4(1, 1, 1, 1);
        for (int it = 0;; it++) {
            ldg_relaxed_if(two, w, in2b);
            v = ldg_relaxed(in2a);
            if (__all_sync(0xffffffffu, and3(and3(v.x, v.y, v.z), and3(v.w, w.x, w.y), and3(w.z, w.w, 1u)))) break;
            if (it > SPIN_LIMIT) __trap();
        }
        PROF(17);
        const float s0 = (__uint_as_float(v.x) + __uint_as_float(w.x)) + __shfl_xor_sync(0xffffffffu, __uint_as_float(v.z) + __uint_as_float(w.z), 8);
        const float s1 = (__uint_as_float(v.y) + __uint_as_float(w.y)) + __shfl_xor_sync(0xffffffffu, __uint_as_float(v.w) + __uint_as_float(w.w), 8);
        sts_f32(red_st + (SC_E6 - SC_E4), s0 + __shfl_xor_sync(0xffffffffu, s1, 16));
        if (warp != 0) {
            nbar_arrive<NB_E6, 288>();
        } else {
            nbar_sync<NB_E6, 288>();
            float2 a[8];
#pragma unroll
            for (int i = 0; i < 8; i++) a[i] = lds_f32x2(red_ld + (SC_E6 - SC_E4) + i * 128);
            const uint32_t gb_w = lds32(gb_ld);
            const uint32_t aw = pack_bf(((a[0].x + a[1].x) + (a[2].x + a[3].x)) + ((a[4].x + a[5].x) + (a[6].x + a[7].x)),
                                        ((a[0].y + a[1].y) + (a[2].y + a[3].y)) + ((a[4].y + a[5].y) + (a[6].y + a[7].y)));
            x1w = bf2_add(x1w, bf2_mul(gb_w, bf2_add(aw, b2w)));
            if (lane < 16) asm volatile("st.global.u32 [%0], %1;" ::"l"(out_dst), "r"(x1w) : "memory");
        }
    }
    PROF(18);
    PROF_DUMP;
}

typedef CUresult (*EncodeFn)(CUtensorMap*, CUtensorMapDataType, cuuint32_t, void*, const cuuint64_t*, const cuuint64_t*, const cuuint32_t*,
                             const cuuint32_t*, CUtensorMapInterleave, CUtensorMapSwizzle, CUtensorMapL2promotion, CUtensorMapFloatOOBfill);

static CUtensorMap make_map(EncodeFn enc, const void* ptr, int cols, int rows, int box_cols, int box_rows, CUtensorMapSwizzle sw,
                            CUtensorMapL2promotion promo = CU_TENSOR_MAP_L2_PROMOTION_NONE) {
    CUtensorMap m;
    cuuint64_t dims[2] = {(cuuint64_t)cols, (cuuint64_t)rows};
    cuuint64_t strides[1] = {(cuuint64_t)cols * 2};
    cuuint32_t box[2] = {(cuuint32_t)box_cols, (cuuint32_t)box_rows};
    cuuint32_t es[2] = {1, 1};
    enc(&m, CU_TENSOR_MAP_DATA_TYPE_BFLOAT16, 2, const_cast<void*>(ptr), dims, strides, box, es, CU_TENSOR_MAP_INTERLEAVE_NONE, sw,
        promo, CU_TENSOR_MAP_FLOAT_OOB_FILL_NONE);
    return m;
}

}

extern "C" void kernel_launch(void* const* d_in, const int* in_sizes, int n_in, void* d_out, int out_size) {
    (void)in_sizes; (void)n_in; (void)out_size;
    static EncodeFn enc = nullptr;
    if (!enc) {
        void* fn = nullptr;
        cudaDriverEntryPointQueryResult qr;
        cudaGetDriverEntryPoint("cuTensorMapEncodeTiled", &fn, cudaEnableDefault, &qr);
        enc = (EncodeFn)fn;
        cudaFuncSetAttribute(fused_kernel, cudaFuncAttributeMaxDynamicSharedMemorySize, SMEM_BYTES);
    }
    Params p;
    p.x = (const __nv_bfloat16*)d_in[0];
    p.kc = (const __nv_bfloat16*)d_in[1];
    p.vc = (const __nv_bfloat16*)d_in[2];
    p.b1 = (const __nv_bfloat16*)d_in[7];
    p.b2 = (const __nv_bfloat16*)d_in[9];
    p.c = (const __nv_bfloat16*)d_in[10];
    p.out = (__nv_bfloat16*)d_out;
    CUtensorMap tm_wmod = make_map(enc, d_in[11], NMOD, D, 32, 160, CU_TENSOR_MAP_SWIZZLE_64B);
    CUtensorMap tm_wq = make_map(enc, d_in[3], NH * DH, D, 32, 160, CU_TENSOR_MAP_SWIZZLE_64B);
    CUtensorMap tm_wo = make_map(enc, d_in[4], D, NH * DH, 32, 128, CU_TENSOR_MAP_SWIZZLE_64B);
    CUtensorMap tm_w1 = make_map(enc, d_in[6], FF, D, 32, 160, CU_TENSOR_MAP_SWIZZLE_64B);
    CUtensorMap tm_w2 = make_map(enc, d_in[8], D, FF, 64, 32, CU_TENSOR_MAP_SWIZZLE_128B);
    CUtensorMap tm_v = make_map(enc, d_in[2], DH, NB * NH * SK, 64, TILE_KEYS, CU_TENSOR_MAP_SWIZZLE_128B);
    CUtensorMap tm_gb = make_map(enc, d_in[11], NMOD, D, 8, 160, CU_TENSOR_MAP_SWIZZLE_NONE, CU_TENSOR_MAP_L2_PROMOTION_L2_128B);
    fused_kernel<<<NCTA, NTHREADS, SMEM_BYTES>>>(p, tm_wmod, tm_wq, tm_wo, tm_w1, tm_w2, tm_v, tm_gb);
}
```

```cpp
#include <cuda_runtime.h>
#include <cuda.h>
#include <cuda_bf16.h>
#include <stdint.h>

namespace {

constexpr int NB = 4, D = 640, NH = 32, DH = 128, SK = 8192, WIN = 2048, FF = 1728, NMOD = 6 * D;
constexpr int NCTA = 128;
constexpr int NOWN = 80;
constexpr int NF = 54;
constexpr int NTHREADS = 320;
constexpr int TILE_KEYS = 64;
constexpr int TILE_BYTES = TILE_KEYS * DH * 2;
constexpr int NITEM = 2 * WIN / TILE_KEYS;
constexpr int NS = 8;
constexpr int NMODC = 120;
constexpr int SPIN_LIMIT = 1 << 18;
#define INFLIGHT 3
#define WQ_DELAY 500
#define MOD_T 4200
#define Q_PAUSE 1100
#define PACE_A 7500
#define PACE_TAU 635
#define ROTA 8
#define ROTB 0
#define PF_END 16
#define PH_FIRST 20
#define PH_LAG 5
#define LAT_T 2100
#define WO_T -1100
#define WO_S 300
#define W1_T 950
#define W2_T 1650
#define GB_T 2500
#define GB_EV 300
#define CLR_CHECK 28000
constexpr int NPROBE = 8, PROBE_END = 10000;
constexpr int SEG_J = 8;

constexpr int OFF_RING = 0;
constexpr int OFF_X = OFF_RING + NS * TILE_BYTES;
constexpr int X_WM = OFF_X;
constexpr int X_WQ = OFF_X + D * 64;
constexpr int X_WO = OFF_X;
constexpr int X_W1 = X_WO + 5 * DH * 64;
constexpr int X_END = X_W1 + D * 64;
constexpr int X_W2 = OFF_RING;
constexpr int X_GB = OFF_RING + 3 * TILE_BYTES;
static_assert(X_WQ + D * 64 <= X_END, "prologue weights must fit");
constexpr int VEC_STRIDE = 1296;
constexpr int OFF_VA = X_END;
constexpr int OFF_VB = OFF_VA + 4 * VEC_STRIDE;
constexpr int OFF_RED = OFF_VB + 4 * VEC_STRIDE;
constexpr int OFF_ML = OFF_RED + 4 * VEC_STRIDE;
constexpr int O_STRIDE = 288;
constexpr int OFF_O = OFF_ML + 64;
constexpr int OFF_Q = OFF_O + 4 * O_STRIDE;
constexpr int OFF_OWN = OFF_Q + 256;
constexpr int OWN_X = OFF_OWN, OWN_B2 = OWN_X + 64, OWN_GA = OWN_B2 + 64, OWN_GB = OWN_GA + 64, OWN_B1 = OWN_GB + 64;
constexpr int OFF_STAT = OWN_B1 + 128;
constexpr int OFF_TAB1 = OFF_STAT + 32;
constexpr int OFF_TAB2 = OFF_TAB1 + NOWN * 4;
constexpr int OFF_SIDE = OFF_TAB2 + NOWN * 4;
constexpr int OFF_BAR = OFF_SIDE + 8;
constexpr int NBAR = 2 * NS + 32;
constexpr int SMEM_BYTES = OFF_BAR + NBAR * 8;
constexpr int SC_OP = OFF_RING + 4 * TILE_BYTES;
constexpr int SC_AB = SC_OP + 4096;
constexpr int SC_Y = SC_AB + 8192;
constexpr int SC_ST = SC_Y + 4096;
constexpr int SC_E4 = SC_ST + 256;
constexpr int SC_E6 = SC_E4 + 1024;
constexpr int SC_P = SC_E6 + 1024;
constexpr int SC_H1 = SC_P + 256;
static_assert(SMEM_BYTES <= 232448, "smem");
static_assert(OFF_BAR % 8 == 0 && OFF_X % 1024 == 0 && X_WQ % 512 == 0 && X_W1 % 512 == 0 && OFF_VA % 16 == 0 && OFF_RED % 16 == 0 && OFF_ML % 16 == 0 && OFF_O % 16 == 0 && OFF_Q % 16 == 0, "align");
constexpr int NB_O = 2  , NB_E4 = 10, NB_E6 = 11, NB_AB = 12, NB_Y = 13;

__device__ __align__(128) uint32_t g_mod[NMODC * 64];
__device__ __align__(128) uint32_t g_q[NCTA * 128];
__device__ uint32_t g_clr[NCTA];
__device__ uint32_t g_phase[16 * 32];
constexpr int SL_P1 = 0;
constexpr int SL_P2 = SL_P1 + NOWN;
constexpr int SL_O = SL_P2 + 2 * NOWN;
constexpr int SL_X1 = SL_O + 8;
constexpr int SL_SIDE = SL_X1 + 3;
static_assert(SL_SIDE < 256, "one 2 MB page");
__device__ uint32_t g_slots[2 * 256 * 2048];
__device__ __forceinline__ uint32_t* slot(int i, int side) {
    const size_t base = ((size_t)g_slots + 0x1fffff) & ~(size_t)0x1fffff;
    return (uint32_t*)base + i * 2048 + (((__popc(i & 0x59) ^ side) & 1) << 10);
}
#define PROF_DECL
#define HPROF(i) do { } while (0)
#define PROF(i) do { } while (0)
#define PROF_DUMP do { } while (0)

__device__ __forceinline__ uint32_t smem_u32(const void* p) { return (uint32_t)__cvta_generic_to_shared(p); }
__device__ __forceinline__ void mbar_init(uint32_t bar, uint32_t cnt) { asm volatile("mbarrier.init.shared::cta.b64 [%0], %1;" ::"r"(bar), "r"(cnt) : "memory"); }
__device__ __forceinline__ void mbar_expect_tx(uint32_t bar, uint32_t bytes) { asm volatile("mbarrier.arrive.expect_tx.shared::cta.b64 _, [%0], %1;" ::"r"(bar), "r"(bytes) : "memory"); }
__device__ __forceinline__ void mbar_arrive(uint32_t bar) { asm volatile("mbarrier.arrive.shared::cta.b64 _, [%0];" ::"r"(bar) : "memory"); }
__device__ __forceinline__ void mbar_wait(uint32_t bar, uint32_t parity) {
    uint32_t ok;
    int it = 0;
    while (true) {
        asm volatile("{\n.reg .pred p;\nmbarrier.try_wait.parity.shared::cta.b64 p, [%1], %2;\nselp.u32 %0, 1, 0, p;\n}" : "=r"(ok) : "r"(bar), "r"(parity) : "memory");
        if (ok) break;
        if (++it > SPIN_LIMIT) __trap();
    }
}
__device__ __forceinline__ void bulk_load(uint32_t dst, const void* src, uint32_t bytes, uint32_t bar, uint64_t pol) {
    asm volatile("cp.async.bulk.shared::cluster.global.mbarrier::complete_tx::bytes.L2::cache_hint [%0], [%1], %2, [%3], %4;"
                 ::"r"(dst), "l"(src), "r"(bytes), "r"(bar), "l"(pol) : "memory");
}
__device__ __forceinline__ void bar_cons() { asm volatile("bar.sync 1, 256;" ::: "memory"); }
template <int ID, int N> __device__ __forceinline__ void nbar_sync() { asm volatile("bar.sync %0, %1;" ::"n"(ID), "n"(N) : "memory"); }
template <int ID, int N> __device__ __forceinline__ void nbar_arrive() { asm volatile("bar.arrive %0, %1;" ::"n"(ID), "n"(N) : "memory"); }
__device__ __forceinline__ bool mbar_test(uint32_t bar, uint32_t parity) {
    uint32_t ok;
    asm volatile("{\n.reg .pred p;\nmbarrier.test_wait.parity.shared::cta.b64 p, [%1], %2;\nselp.u32 %0, 1, 0, p;\n}" : "=r"(ok) : "r"(bar), "r"(parity) : "memory");
    return ok;
}
__device__ __forceinline__ uint32_t pin(uint32_t v) { asm volatile("" : "+r"(v)); return v; }
template <class T> __device__ __forceinline__ T pin_hard(T v) { return __shfl_sync(0xffffffffu, v, threadIdx.x & 31); }
template <class T> __device__ __forceinline__ T* pin(T* v) { asm volatile("" : "+l"(v)); return v; }
__device__ __forceinline__ void ldsm4(uint32_t (&a)[4], uint32_t addr) {
    asm volatile("ldmatrix.sync.aligned.m8n8.x4.shared.b16 {%0,%1,%2,%3}, [%4];" : "=r"(a[0]), "=r"(a[1]), "=r"(a[2]), "=r"(a[3]) : "r"(addr) : "memory");
}
__device__ __forceinline__ void ldsm4t(uint32_t (&a)[4], uint32_t addr) {
    asm volatile("ldmatrix.sync.aligned.m8n8.x4.trans.shared.b16 {%0,%1,%2,%3}, [%4];" : "=r"(a[0]), "=r"(a[1]), "=r"(a[2]), "=r"(a[3]) : "r"(addr) : "memory");
}
__device__ __forceinline__ void mma16816(float (&c)[4], const uint32_t (&a)[4], uint32_t b0, uint32_t b1) {
    asm volatile("mma.sync.aligned.m16n8k16.row.col.f32.bf16.bf16.f32 {%0,%1,%2,%3}, {%4,%5,%6,%7}, {%8,%9}, {%0,%1,%2,%3};"
                 : "+f"(c[0]), "+f"(c[1]), "+f"(c[2]), "+f"(c[3]) : "r"(a[0]), "r"(a[1]), "r"(a[2]), "r"(a[3]), "r"(b0), "r"(b1));
}
__device__ __forceinline__ uint32_t lds32(uint32_t addr) { uint32_t v; asm volatile("ld.shared.u32 %0, [%1];" : "=r"(v) : "r"(addr) : "memory"); return v; }
__device__ __forceinline__ float lds_f32(uint32_t addr) { float v; asm volatile("ld.shared.f32 %0, [%1];" : "=f"(v) : "r"(addr) : "memory"); return v; }
__device__ __forceinline__ float2 lds_f32x2(uint32_t addr) { float2 v; asm volatile("ld.shared.v2.f32 {%0,%1}, [%2];" : "=f"(v.x), "=f"(v.y) : "r"(addr) : "memory"); return v; }
__device__ __forceinline__ float4 lds_f32x4(uint32_t addr) { float4 v; asm volatile("ld.shared.v4.f32 {%0,%1,%2,%3}, [%4];" : "=f"(v.x), "=f"(v.y), "=f"(v.z), "=f"(v.w) : "r"(addr) : "memory"); return v; }
__device__ __forceinline__ uint2 lds64(uint32_t addr) { uint2 v; asm volatile("ld.shared.v2.u32 {%0,%1}, [%2];" : "=r"(v.x), "=r"(v.y) : "r"(addr) : "memory"); return v; }
__device__ __forceinline__ uint4 lds128(uint32_t addr) { uint4 v; asm volatile("ld.shared.v4.u32 {%0,%1,%2,%3}, [%4];" : "=r"(v.x), "=r"(v.y), "=r"(v.z), "=r"(v.w) : "r"(addr) : "memory"); return v; }
__device__ __forceinline__ void sts16(uint32_t addr, uint32_t v) { asm volatile("st.shared.b16 [%0], %1;" ::"r"(addr), "h"((unsigned short)v) : "memory"); }
__device__ __forceinline__ void sts32(uint32_t addr, uint32_t v) { asm volatile("st.shared.u32 [%0], %1;" ::"r"(addr), "r"(v) : "memory"); }
__device__ __forceinline__ void sts_f32(uint32_t addr, float v) { asm volatile("st.shared.f32 [%0], %1;" ::"r"(addr), "f"(v) : "memory"); }
__device__ __forceinline__ void sts_f32x2(uint32_t addr, float a, float b) { asm volatile("st.shared.v2.f32 [%0], {%1,%2};" ::"r"(addr), "f"(a), "f"(b) : "memory"); }
__device__ __forceinline__ void sts128(uint32_t addr, uint4 v) { asm volatile("st.shared.v4.u32 [%0], {%1,%2,%3,%4};" ::"r"(addr), "r"(v.x), "r"(v.y), "r"(v.z), "r"(v.w) : "memory"); }
__device__ __forceinline__ uint4 ldg_relaxed(const uint32_t* p) {
    uint4 v;
    asm volatile("ld.relaxed.gpu.global.v4.u32 {%0,%1,%2,%3}, [%4];" : "=r"(v.x), "=r"(v.y), "=r"(v.z), "=r"(v.w) : "l"(p) : "memory");
    return v;
}
__device__ __forceinline__ void ldg_relaxed_if(bool on, uint4& v, const uint32_t* p) {
    asm volatile("{\n.reg .pred q;\nsetp.ne.u32 q, %5, 0;\n@q ld.relaxed.gpu.global.v4.u32 {%0,%1,%2,%3}, [%4];\n}"
                 : "+r"(v.x), "+r"(v.y), "+r"(v.z), "+r"(v.w) : "l"(p), "r"((uint32_t)on) : "memory");
}
__device__ __forceinline__ void stg_relaxed2_if(bool on, uint32_t* p, uint32_t a, uint32_t b) {
    asm volatile("{\n.reg .pred q;\nsetp.ne.u32 q, %3, 0;\n@q st.relaxed.gpu.global.v2.u32 [%0], {%1,%2};\n}" ::"l"(p), "r"(a), "r"(b), "r"((uint32_t)on) : "memory");
}
__device__ __forceinline__ uint32_t ldg_relaxed32(const uint32_t* p) { uint32_t v; asm volatile("ld.relaxed.gpu.global.u32 %0, [%1];" : "=r"(v) : "l"(p) : "memory"); return v; }
__device__ __forceinline__ void stg_relaxed(uint32_t* p, uint32_t v) { asm volatile("st.relaxed.gpu.global.u32 [%0], %1;" ::"l"(p), "r"(v) : "memory"); }
__device__ __forceinline__ void stg_zero4(uint32_t* p) { asm volatile("st.relaxed.gpu.global.v4.u32 [%0], {%1,%1,%1,%1};" ::"l"(p), "r"(0u) : "memory"); }
__device__ __forceinline__ bool ready(const uint4& v) { return (v.x != 0u) & (v.y != 0u) & (v.z != 0u) & (v.w != 0u); }
__device__ __forceinline__ uint32_t min4(const uint4& v) { return min(__vimin3_u32(v.x, v.y, v.z), v.w); }
__device__ __forceinline__ uint4 inv4(const uint4& v) { return make_uint4(~v.x, ~v.y, ~v.z, ~v.w); }
__device__ __forceinline__ uint32_t pack_bf(float lo, float hi) {
    uint32_t r;
    asm("cvt.rn.bf16x2.f32 %0, %1, %2;" : "=r"(r) : "f"(hi), "f"(lo));
    return r;
}
__device__ __forceinline__ float bfr(float x) { return __uint_as_float(pack_bf(0.f, x) & 0xffff0000u); }
__device__ __forceinline__ float bf_lo(uint32_t w) { return __uint_as_float(w << 16); }
__device__ __forceinline__ float bf_hi(uint32_t w) { return __uint_as_float(w & 0xffff0000u); }
__device__ __forceinline__ float bf2f(__nv_bfloat16 v) { return __bfloat162float(v); }
__device__ __forceinline__ float ex2(float x) { float y; asm("ex2.approx.ftz.f32 %0, %1;" : "=f"(y) : "f"(x)); return y; }
__device__ __forceinline__ float rcp_fast(float x) { float y; asm("rcp.approx.ftz.f32 %0, %1;" : "=f"(y) : "f"(x)); return y; }
__device__ __forceinline__ float rsqrt_fast(float x) { float y; asm("rsqrt.approx.ftz.f32 %0, %1;" : "=f"(y) : "f"(x)); return y; }
__device__ __forceinline__ float sqrt_fast(float x) { float y; asm("sqrt.approx.f32 %0, %1;" : "=f"(y) : "f"(x)); return y; }
__device__ __forceinline__ uint32_t bf2_add(uint32_t a, uint32_t b) { uint32_t r; asm("add.rn.bf16x2 %0, %1, %2;" : "=r"(r) : "r"(a), "r"(b)); return r; }
__device__ __forceinline__ uint32_t bf2_sub(uint32_t a, uint32_t b) { uint32_t r; asm("sub.rn.bf16x2 %0, %1, %2;" : "=r"(r) : "r"(a), "r"(b)); return r; }
__device__ __forceinline__ uint32_t bf2_mul(uint32_t a, uint32_t b) { uint32_t r; asm("mul.rn.bf16x2 %0, %1, %2;" : "=r"(r) : "r"(a), "r"(b)); return r; }
__device__ __forceinline__ uint32_t gtime32() { uint32_t c; asm volatile("mov.u32 %0, %%globaltimer_lo;" : "=r"(c)); return c; }
__device__ __forceinline__ uint32_t clock32() { uint32_t c; asm volatile("mov.u32 %0, %%clock;" : "=r"(c)); return c; }

__device__ __forceinline__ float warp_sum(float v) {
#pragma unroll
    for (int o = 16; o > 0; o >>= 1) v += __shfl_xor_sync(0xffffffffu, v, o);
    return v;
}

struct Params {
    const __nv_bfloat16 *x, *kc, *vc, *b1, *b2, *c;
    __nv_bfloat16* out;
};

__device__ __forceinline__ void tma2d(uint32_t dst, const CUtensorMap* tm, int x, int y, uint32_t bar) {
    asm volatile("cp.async.bulk.tensor.2d.shared::cluster.global.mbarrier::complete_tx::bytes [%0], [%1, {%2, %3}], [%4];"
                 ::"r"(dst), "l"(tm), "r"(x), "r"(y), "r"(bar) : "memory");
}

__device__ __forceinline__ void tma2d_hint(uint32_t dst, const CUtensorMap* tm, int x, int y, uint32_t bar, uint64_t pol) {
    asm volatile("cp.async.bulk.tensor.2d.shared::cluster.global.mbarrier::complete_tx::bytes.L2::cache_hint [%0], [%1, {%2, %3}], [%4], %5;"
                 ::"r"(dst), "l"(tm), "r"(x), "r"(y), "r"(bar), "l"(pol) : "memory");
}
__device__ __forceinline__ uint32_t flag(float v) { return __float_as_uint(v) | 1u; }
__device__ __forceinline__ uint32_t and3(uint32_t a, uint32_t b, uint32_t c) { uint32_t r; asm("lop3.b32 %0, %1, %2, %3, 0x80;" : "=r"(r) : "r"(a), "r"(b), "r"(c)); return r; }
__device__ __forceinline__ uint32_t* slot_ptr(uint32_t lo) {
    uint32_t* r;
    asm volatile("mov.b64 %0, {%1, %2};" : "=l"(r) : "r"(lo), "r"((uint32_t)((size_t)slot(0, 0) >> 32)));
    return r;
}

__device__ __forceinline__ void load_bfrag(uint32_t vec, int stride, int k0, int g, int t, uint32_t& b0, uint32_t& b1) {
    uint32_t a = vec + (g & 3) * stride + (k0 + 2 * t) * 2;
    b0 = lds32(a);
    b1 = lds32(a + 16);
}

__device__ __forceinline__ void ln_finish(float pivot, float sum, float sumsq, uint32_t& m2, float& rden) {
    float dm = sum * (1.f / D);
    float var = fmaxf(sumsq * (1.f / D) - dm * dm, 0.f);
    float mean = pivot + dm;
    m2 = pack_bf(mean, mean);
    rden = rcp_fast(bfr(sqrt_fast(bfr(bfr(var) + 1e-5f))));
}
__device__ __forceinline__ uint32_t ln_mod_pair(uint32_t xw, uint32_t cw, uint32_t sw, uint32_t m2, float rden) {
    uint32_t d = bf2_sub(xw, m2);
    uint32_t ln = pack_bf(bf_lo(d) * rden, bf_hi(d) * rden);
    return bf2_add(bf2_mul(ln, bf2_add(cw, 0x3f803f80u)), sw);
}
__device__ __forceinline__ uint4 ln_mod4(const uint4& x, const uint4& c, const uint4& s, uint32_t m2, float rden) {
    return make_uint4(ln_mod_pair(x.x, c.x, s.x, m2, rden), ln_mod_pair(x.y, c.y, s.y, m2, rden),
                      ln_mod_pair(x.z, c.z, s.z, m2, rden), ln_mod_pair(x.w, c.w, s.w, m2, rden));
}
__device__ __forceinline__ void acc_stats(const uint4& v, float pv, float& s, float& q) {
    const float a0 = bf_lo(v.x) - pv, a1 = bf_hi(v.x) - pv, a2 = bf_lo(v.y) - pv, a3 = bf_hi(v.y) - pv;
    const float a4 = bf_lo(v.z) - pv, a5 = bf_hi(v.z) - pv, a6 = bf_lo(v.w) - pv, a7 = bf_hi(v.w) - pv;
    s += ((a0 + a1) + (a2 + a3)) + ((a4 + a5) + (a6 + a7));
    q += (fmaf(a0, a0, a1 * a1) + fmaf(a2, a2, a3 * a3)) + (fmaf(a4, a4, a5 * a5) + fmaf(a6, a6, a7 * a7));
}
__device__ __forceinline__ uint32_t* mod_slot(int kind, int j, int b) { return g_mod + (kind * 20 + (j >> 2)) * 64 + b * 16 + (j & 3) * 4; }

template <int N>
__device__ __forceinline__ void poll_n(uint4 (&v)[N], const uint32_t* const* ptr, const bool* on) {
    bool pend[N];
#pragma unroll
    for (int i = 0; i < N; i++) pend[i] = on[i];
    int it = 0;
    while (true) {
#pragma unroll
        for (int i = 0; i < N; i++) if (pend[i]) v[i] = ldg_relaxed(ptr[i]);
        bool any = false;
#pragma unroll
        for (int i = 0; i < N; i++) { pend[i] = pend[i] && !ready(v[i]); any |= pend[i]; }
        if (!__any_sync(0xffffffffu, any)) break;
        if (++it > SPIN_LIMIT) __trap();
    }
#pragma unroll
    for (int i = 0; i < N; i++) v[i] = inv4(v[i]);
}
__device__ __forceinline__ uint4 poll1(const uint32_t* p, bool on) {
    uint4 v[1] = {make_uint4(0, 0, 0, 0)};
    const uint32_t* const ptr[1] = {p};
    const bool o[1] = {on};
    poll_n<1>(v, ptr, o);
    return v[0];
}

__device__ __forceinline__ void gelu_stage(uint32_t sb, int m, int lane) {
    const int g = lane >> 2, b = lane & 3;
    const uint32_t y_ld = pin_hard(sb + SC_Y + m * 256 + lane * 8), s_ld = pin_hard(sb + SC_ST + b * 64);
    const uint32_t h_st = pin_hard(sb + SC_H1 + b * 64 + (g >> 1) * 16 + m * 8 + (g & 1) * 2);
    float a0 = 0.f, b0 = lds_f32(sb + OWN_B1 + (16 * m + g) * 4), a1 = 0.f, b1 = lds_f32(sb + OWN_B1 + (16 * m + g + 8) * 4);
    const float piv = bf_hi(lds32(sb + OFF_STAT + b * 8));
    nbar_sync<NB_AB, 320>();
#pragma unroll
    for (int w = 0; w < 8; w++) {
        const float4 t = lds_f32x4(sb + SC_AB + w * 1024 + m * 512 + lane * 16);
        a0 += t.x; b0 += t.y; a1 += t.z; b1 += t.w;
    }
    sts128(sb + SC_AB + m * 512 + lane * 16, make_uint4(__float_as_uint(a0), __float_as_uint(b0), __float_as_uint(a1), __float_as_uint(b1)));
    nbar_sync<NB_Y, 320>();
    float4 q[4];
    float2 y[8];
#pragma unroll
    for (int i = 0; i < 4; i++) q[i] = lds_f32x4(s_ld + i * 16);
#pragma unroll
    for (int w = 0; w < 8; w++) y[w] = lds_f32x2(y_ld + w * 512);
    const float dm = (((q[0].y + q[0].w) + (q[1].y + q[1].w)) + ((q[2].y + q[2].w) + (q[3].y + q[3].w))) * (1.f / D);
    const float sq = ((q[0].x + q[0].z) + (q[1].x + q[1].z)) + ((q[2].x + q[2].z) + (q[3].x + q[3].z));
    const float r = rsqrt_fast(fmaxf(fmaf(-dm, dm, fmaf(sq, 1.f / D, 1e-5f)), 1e-5f));
    const float y0 = ((y[0].x + y[1].x) + (y[2].x + y[3].x)) + ((y[4].x + y[5].x) + (y[6].x + y[7].x));
    const float y1 = ((y[0].y + y[1].y) + (y[2].y + y[3].y)) + ((y[4].y + y[5].y) + (y[6].y + y[7].y));
    const float dmr = piv - bfr(piv - dm);
    const float u0 = fmaf(r, fmaf(dmr, a0, -y0), b0), u1 = fmaf(r, fmaf(dmr, a1, -y1), b1);
    const float e0 = ex2(u0 * fmaf(u0 * u0, -0.044715f * 2.302208198144325f, -2.302208198144325f));
    const float e1 = ex2(u1 * fmaf(u1 * u1, -0.044715f * 2.302208198144325f, -2.302208198144325f));
    sts16(h_st, pack_bf(u0 * rcp_fast(1.f + e0), 0.f));
    sts16(h_st + 4, pack_bf(u1 * rcp_fast(1.f + e1), 0.f));
#pragma unroll
    for (int w = 0; w < 8; w++) asm volatile("bar.arrive %0, 96;" ::"r"(NB_O + w) : "memory");
}

struct Roles { bool is_f, is_owner; int f, own; };
__device__ __forceinline__ Roles roles(int cta) {
    Roles r;
    r.f = (cta * 27) >> 6;
    r.is_f = (((cta + 1) * 27) >> 6) != r.f;
    r.is_owner = !r.is_f || r.f % 9 == 4;
    r.own = r.is_f ? 74 + r.f / 9 : cta - r.f;
    return r;
}

__global__ void __launch_bounds__(NTHREADS, 1)
fused_kernel(const Params p, const __grid_constant__ CUtensorMap tm_wmod, const __grid_constant__ CUtensorMap tm_wq,
             const __grid_constant__ CUtensorMap tm_wo, const __grid_constant__ CUtensorMap tm_w1, const __grid_constant__ CUtensorMap tm_w2,
             const __grid_constant__ CUtensorMap tm_v, const __grid_constant__ CUtensorMap tm_gb) {
    extern __shared__ __align__(1024) unsigned char smem[];
    const uint32_t t_start = gtime32();
    if (threadIdx.x == 0) {
        const uint32_t c_ = blockIdx.x;
        const uint32_t off = ((c_ & 3) << 26) + (c_ >> 2) * (1u << 21) + (((ROTA * (c_ >> 2) + ROTB) & 31) << 14) + (SK - WIN) * DH * 2;
        asm volatile("cp.async.bulk.prefetch.L2.global.L2::cache_hint [%0], %1, %2;" ::"l"((const char*)p.kc + off), "r"(TILE_BYTES), "l"(0x12f0000000000000ull  ) : "memory");
    }
    const uint32_t sb = smem_u32(smem);
    const int cta = blockIdx.x;
    const int head = cta >> 2, bown = cta & 3;
    const int rot = (ROTA * head + ROTB) & (NITEM / 2 - 1);
    const char* const kb = (const char*)(p.kc + ((size_t)(bown * NH + head) * SK + (SK - WIN)) * DH);
    uint64_t pol = 0;
    if (threadIdx.x == 256) {
        mbar_init(sb + OFF_BAR, 1);
        asm volatile("fence.mbarrier_init.release.cluster;" ::: "memory");
        asm volatile("createpolicy.fractional.L2::evict_first.b64 %0, 1.0;" : "=l"(pol));
        mbar_expect_tx(sb + OFF_BAR, TILE_BYTES);
        bulk_load(sb + OFF_RING, kb + (size_t)rot * TILE_BYTES, TILE_BYTES, sb + OFF_BAR, pol);
        if ((((head + 1) * 5) >> 4) != ((head * 5) >> 4)) {
            const uint32_t bar = sb + OFF_BAR + 2 * NS * 8;
            mbar_init(bar, 1);
            asm volatile("fence.mbarrier_init.release.cluster;" ::: "memory");
            mbar_expect_tx(bar, D * 64);
#pragma unroll 1
            for (int r = 0; r < D; r += 160) tma2d(sb + X_WM + r * 64, &tm_wmod, 32 * (((head * 5) >> 4) * 4 + bown), r, bar);
        }
    }
    const uint32_t bar_full = sb + OFF_BAR, bar_empty = bar_full + NS * 8;
    const uint32_t bar_wm = bar_empty + NS * 8, bar_wq = bar_wm + 8, bar_xfree = bar_wq + 8, bar_wo = bar_xfree + 8  ;
    const uint32_t bar_w1 = bar_wo + 40  , bar_w2 = bar_w1 + 32  , bar_help = bar_w2 + 80, bar_v = bar_help + 8  ;
    const uint32_t bar_gb = bar_v + 32  , bar_x1 = bar_gb + 32;
    const int tid = threadIdx.x, warp = tid >> 5, lane = tid & 31;
    const Roles role = roles(cta);
    const bool is_f = role.is_f, is_owner = role.is_owner;
    const int f = role.f, own = role.own;
    const bool crit = (((head + 1) * 5) >> 4) != ((head * 5) >> 4);
    const int mr = cta - ((head * 5) >> 4) * 4, mq = ((head * 5) >> 4) * 4 + bown;
    const int ml = mr * 31 / 44;
    const bool late = !crit && (mr + 1) * 31 / 44 != ml;
    const int mc = crit ? mq : ml < 60 ? 40 + ml : 58 + ml;
    const bool gb_own = is_owner && own < 72;

    PROF_DECL
    PROF(0);
    uint4 xa = make_uint4(0, 0, 0, 0), xb = xa, ca0 = xa, ca1 = xa, xs[3] = {xa, xa, xa};
    uint32_t own0 = 0;
    __nv_bfloat16 own2 = __float2bfloat16(0.f);
    if (warp < 8) {
        xa = *(const uint4*)(p.x + (tid & 3) * D + (tid >> 2) * 8);
        ca0 = ((const uint4*)p.c)[tid];
        if (tid < 64) { xb = *(const uint4*)(p.x + (tid & 3) * D + (64 + (tid >> 2)) * 8); ca1 = ((const uint4*)p.c)[256 + tid]; }
        if (warp < 4) {
#pragma unroll
            for (int i = 0; i < 3; i++) if (lane + 32 * i < 80) xs[i] = ((const uint4*)p.x)[warp * 80 + lane + 32 * i];
        } else if (warp == 4) {
            if (is_owner) own0 = *(const uint32_t*)((lane < 16 ? p.x + (lane >> 2) * D : p.b2) + 8 * own + 2 * (lane & 3));
            if (is_f) own2 = p.b1[32 * f + lane];
        }
    }
    const char* const vb = (const char*)(p.vc + ((size_t)(bown * NH + head) * SK + (SK - WIN)) * DH);
    const uint32_t bar_first = crit ? bar_wm : bar_wq;
    if (threadIdx.x == 256) {
        if (!crit) {
            mbar_init(bar_wq, 1);
            asm volatile("fence.mbarrier_init.release.cluster;" ::: "memory");
            mbar_expect_tx(bar_wq, D * 64);
            const uint32_t c0 = clock32();
            while (clock32() - c0 < WQ_DELAY) { }
#pragma unroll
            for (int r = 0; r < D; r += 160) tma2d(sb + X_WQ + r * 64, &tm_wq, 32 * cta, r, bar_wq);
        }
    } else if (threadIdx.x == 0) {
#pragma unroll
        for (int s = 0; s < NS; s++) { if (s) mbar_init(bar_full + s * 8, 1); mbar_init(bar_empty + s * 8, 4); }
        mbar_init(crit ? bar_wq : bar_wm, 1);
        mbar_init(bar_xfree, 1);
#pragma unroll
        for (int i = 0; i < 5; i++) { mbar_init(bar_wo + i * 8, 1); mbar_init(bar_w2 + i * 16, 1); mbar_init(bar_w2 + i * 16 + 8, 1); }
        mbar_init(bar_help, 1); mbar_init(bar_x1, 1);
#pragma unroll
        for (int i = 0; i < 4; i++) { mbar_init(bar_v + i * 8, 1); mbar_init(bar_w1 + i * 8, 1); mbar_init(bar_gb + i * 8, 1); }
        asm volatile("fence.mbarrier_init.release.cluster;" ::: "memory");
    }
    __syncthreads();

    if (warp == 8) {
        if (lane == 0) {
            int tp = NS;
            int sched = PACE_A - NS * PACE_TAU;
#pragma unroll 1
            for (int t = 1; t <= NITEM; t++) {
                if (t == 1) mbar_wait(bar_full, 0);
                if (t == 2) {
                    mbar_wait(bar_first, 0);
                    if (crit) {
                        mbar_expect_tx(bar_wq, D * 64);
#pragma unroll 1
                        for (int r = 0; r < D; r += 160) tma2d(sb + X_WQ + r * 64, &tm_wq, 32 * cta, r, bar_wq);
                    }
                }
                if (t == 3) {
                    asm volatile("prefetch.tensormap [%0];" ::"l"(&tm_v) : "memory");
                    asm volatile("prefetch.tensormap [%0];" ::"l"(&tm_wo) : "memory");
                    asm volatile("prefetch.tensormap [%0];" ::"l"(&tm_w1) : "memory");
                    asm volatile("prefetch.tensormap [%0];" ::"l"(&tm_w2) : "memory");
                    asm volatile("prefetch.tensormap [%0];" ::"l"(&tm_gb) : "memory");
                }
                if (t == NS && late) {
                    mbar_wait(bar_full + (NS - INFLIGHT) * 8, 0);
                    mbar_expect_tx(bar_wm, D * 64);
#pragma unroll 1
                    for (int r = 0; r < D; r += 160) tma2d(sb + X_WM + r * 64, &tm_wmod, 32 * mc, r, bar_wm);
                }
                if (t >= NS && t < PF_END) {
                    int it = 0;
                    while (!mbar_test(bar_empty + (t & (NS - 1)) * 8, ((t >> 3) - 1) & 1)) {
                        if (tp < PF_END && (int)(gtime32() - t_start) >= PACE_A + (tp - NS) * PACE_TAU) {
                            asm volatile("cp.async.bulk.prefetch.L2.global.L2::cache_hint [%0], %1, %2;"
                                         ::"l"(((tp & 1) ? vb : kb) + (size_t)(((tp >> 1) + rot) & (NITEM / 2 - 1)) * TILE_BYTES), "r"(TILE_BYTES), "l"(pol) : "memory");
                            tp++;
                        }
                        if (++it > 16 * SPIN_LIMIT) __trap();
                    }
                    if (tp <= t) tp = t + 1;
                }
                if (t == NITEM) {
                    mbar_wait(bar_xfree, 0);
                    const uint32_t t_ref = t_start + sched + LAT_T + (NITEM - 1) * PACE_TAU;
#pragma unroll 1
                    for (int i = 0; i < 5; i++) {
                        while ((int)(gtime32() - t_ref) < WO_T + i * WO_S) { }
                        mbar_expect_tx(bar_wo + i * 8, DH * 64);
                        tma2d(sb + X_WO + i * (DH * 64), &tm_wo, bown * 160 + i * 32, head * DH, bar_wo + i * 8);
                    }
                    if (gb_own) {
                        mbar_wait(bar_empty + 3 * 8, ((NITEM >> 3) - 1) & 1);
                        mbar_wait(bar_x1, 0);
                        { const uint32_t c0 = clock32(); while (clock32() - c0 < GB_EV) { } }
                        while ((int)(gtime32() - t_ref) < GB_T) { }
#pragma unroll 1
                        for (int i = 0; i < 4; i++) {
                            mbar_expect_tx(bar_gb + i * 8, 160 * 16);
                            tma2d(sb + X_GB + i * (160 * 16), &tm_gb, 5 * D + 8 * own, 160 * i, bar_gb + i * 8);
                        }
                    }
                    if (is_f) {
#pragma unroll 1
                        for (int i = 0; i < 3; i++) mbar_wait(bar_empty + i * 8, ((NITEM >> 3) - 1) & 1);
                        while ((int)(gtime32() - t_ref) < W1_T) { }
#pragma unroll 1
                        for (int i = 0; i < 4; i++) {
                            mbar_expect_tx(bar_w1 + i * 8, 160 * 64);
                            tma2d(sb + X_W1 + i * (160 * 64), &tm_w1, 32 * f, 160 * i, bar_w1 + i * 8);
                        }
                        while ((int)(gtime32() - t_ref) < W2_T) { }
#pragma unroll 1
                        for (int i = 0; i < 10; i++) {
                            mbar_expect_tx(bar_w2 + i * 8, 4096);
                            tma2d(sb + X_W2 + i * 4096, &tm_w2, 64 * i, 32 * f, bar_w2 + i * 8);
                        }
                    }
                    break;
                }
                const int s = t & (NS - 1);
                if (t >= NS) {
                    mbar_wait(bar_empty + s * 8, ((t >> 3) - 1) & 1);
                    while ((int)(gtime32() - t_start) < sched + t * PACE_TAU) { }
                } else if (t >= INFLIGHT) {
                    mbar_wait(bar_full + (t - INFLIGHT) * 8, 0);
                }
                if (t < NITEM - 2) {
                    const int pair = t == NITEM - 3 ? NITEM / 2 - 1 : t >> 1;
                    mbar_expect_tx(bar_full + s * 8, TILE_BYTES);
                    bulk_load(sb + OFF_RING + s * TILE_BYTES, ((t & 1) && t != NITEM - 3 ? vb : kb) + (size_t)((pair + rot) & (NITEM / 2 - 1)) * TILE_BYTES, TILE_BYTES, bar_full + s * 8, pol);
                } else {
                    const int row = (bown * NH + head) * SK + (SK - WIN) + ((t - NITEM / 2 + rot) & (NITEM / 2 - 1)) * TILE_KEYS;
#pragma unroll 1
                    for (int i = 0; i < 2; i++) {
                        const uint32_t bar = bar_v + (2 * (t - (NITEM - 2)) + i) * 8;
                        mbar_expect_tx(bar, TILE_BYTES / 2);
                        tma2d_hint(sb + OFF_RING + s * TILE_BYTES + i * (TILE_BYTES / 2), &tm_v, 64 * i, row, bar, pol);
                    }
                }
                if (t >= PH_FIRST + PH_LAG && (t & 3) == (PH_LAG & 3)) {
                    const int now = (int)(gtime32() - t_start) - (t - PH_LAG) * PACE_TAU;
                    uint32_t ph;
                    asm volatile("atom.relaxed.gpu.global.add.u32 %0, [%1], 0;" : "=r"(ph) : "l"(g_phase + ((t - PH_LAG) >> 2) * 32) : "memory");
                    sched = (int)min(((ph & 0xffffffu) * 4 + (NCTA - (ph >> 24)) * now) >> 7, 65535u) - LAT_T;
                }
            }
        }
        __syncwarp();
    }

    if (warp == 9) {
        int side = 0;
        if (lane == 0) {
            uint32_t best[2] = {~0u, ~0u};
#pragma unroll 1
            for (int i = 0; i < 2 * NPROBE && ((i & 1) || (int)(gtime32() - t_start) < PROBE_END); i++) {
                uint32_t t0 = clock32(), v, t1;
                asm volatile("atom.relaxed.gpu.global.exch.b32 %0, [%1], %2;" : "=r"(v) : "l"(slot(SL_SIDE, i & 1) + cta * 8), "r"(0u) : "memory");
                asm volatile("{\n.reg .pred p;\nsetp.ne.u32 p, %1, 0xffffffff;\nmov.u32 %0, 0;\n@p mov.u32 %0, %%clock;\n}" : "=r"(t1) : "r"(v) : "memory");
                if (i & 1) best[1] = min(best[1], t1 - t0); else best[0] = min(best[0], t1 - t0);
            }
            side = best[1] < best[0];
        }
        side = __shfl_sync(0xffffffffu, side, 0);
        HPROF(1);
        mbar_wait(bar_full + (NS - 1) * 8, 0);
        stg_zero4(slot(SL_O + (cta >> 4), lane >> 4) + (cta & 15) * 64 + (lane & 15) * 4);
        if (is_owner) {
#pragma unroll 1
            for (int i = lane; i < NH * 8; i += 32) stg_zero4(slot(SL_P1 + own, side) + i * 4);
#pragma unroll 1
            for (int i = lane; i < NF * 8; i += 32) stg_zero4(slot(SL_P2 + 2 * own + (i >> 8), side) + (i & 255) * 4);
            if (lane < 8) stg_zero4(slot(SL_X1 + own / 30, lane >> 2) + (own % 30) * 32 + (lane & 3) * 4);
        }
        __threadfence();
        __syncwarp();
        if (lane == 0) stg_relaxed(g_clr + cta, 1u + side);
        HPROF(0);
        HPROF(2);
        while ((int)(gtime32() - t_start) < CLR_CHECK) __nanosleep(1000);
        mbar_wait(bar_xfree, 0);
        {
            uint4 v = make_uint4(1, 1, 1, 1), gv = v, mv[20];
#pragma unroll
            for (int i = 0; i < 20; i++) mv[i] = v;
#pragma unroll 1
            for (int it = 0;; it++) {
                v = ldg_relaxed(g_clr + lane * 4);

                ldg_relaxed_if(is_owner && lane < (gb_own ? 4 : 8), gv, mod_slot(lane < 4 ? 2 : 5, own, lane & 3));
#pragma unroll
                for (int i = 0; i < 20; i++) ldg_relaxed_if(is_f, mv[i], mod_slot(3, 8 * i + (lane >> 2), lane & 3));
                bool ok = ready(v) && ready(gv);
#pragma unroll
                for (int i = 0; i < 20; i++) ok = ok && ready(mv[i]);
                if (__all_sync(0xffffffffu, ok)) break;
                if (it > SPIN_LIMIT) __trap();
                __nanosleep(2000);
            }
            const uint32_t w[4] = {v.x, v.y, v.z, v.w};
#pragma unroll
            for (int i = 0; i < 4; i++) {
                const Roles r = roles(4 * lane + i);
                if (r.is_owner) {
                    sts32(sb + OFF_TAB1 + r.own * 4, (uint32_t)(size_t)(slot(SL_P1 + r.own, w[i] - 1) + head * 32));
                    sts32(sb + OFF_TAB2 + r.own * 4, (uint32_t)(size_t)(slot(SL_P2 + 2 * r.own + (f >> 5), w[i] - 1) + (f & 31) * 32));
                }
            }
            if (lane == 0) sts32(sb + OFF_SIDE, side);
            if (lane < 8) sts128(sb + OWN_GA + lane * 16, inv4(gv));
            const uint32_t dst = sb + OFF_VB + (lane & 3) * VEC_STRIDE + (lane >> 2) * 16;
#pragma unroll
            for (int i = 0; i < 10; i++) {
                const uint4 c = inv4(mv[10 + i]);
                sts128(dst + i * 128, make_uint4(bf2_add(c.x, 0x3f803f80u), bf2_add(c.y, 0x3f803f80u), bf2_add(c.z, 0x3f803f80u), bf2_add(c.w, 0x3f803f80u)));
                sts128(dst + (OFF_RED - OFF_VB) + i * 128, inv4(mv[i]));
            }
        }
        asm volatile("fence.acq_rel.gpu;" ::: "memory");
        __syncwarp();
        HPROF(3);
        if (lane == 0) mbar_arrive(bar_help);
        {
            const uint32_t* const src = pin(slot(SL_O + (cta >> 4), side) + (cta & 12) * 64 + lane * 4);
            const uint32_t dst = pin(sb + OFF_O + (lane >> 4) * O_STRIDE + (lane & 15) * 16);
            mbar_wait(bar_v + 16, 0);
            mbar_wait(bar_v + 24, 0);
            uint4 v[2];
            const uint32_t* const ptr[2] = {src, src + 128};
            const bool on[2] = {true, true};
            poll_n<2>(v, ptr, on);
            sts128(dst, v[0]);
            sts128(dst + 2 * O_STRIDE, v[1]);
#pragma unroll
            for (int w = 0; w < 8; w++) asm volatile("bar.arrive %0, 64;" ::"r"(NB_O + w) : "memory");
        }
        HPROF(4);
    }
    if (warp >= 8) {
        if (gb_own && warp == 9) {
            uint32_t a[20][4];
#pragma unroll
            for (int i = 0; i < 20; i++) ldsm4(a[i], sb + OFF_VA + (lane & 3) * VEC_STRIDE + (4 * i + (lane >> 3)) * 16);
            float c[4][4];
#pragma unroll
            for (int i = 0; i < 4; i++) c[i][0] = c[i][1] = c[i][2] = c[i][3] = 0.f;
#pragma unroll
            for (int bx = 0; bx < 4; bx++) {
                mbar_wait(bar_gb + bx * 8, 0);
#pragma unroll
                for (int i = 5 * bx; i < 5 * bx + 5; i++) {
                    uint32_t w[4];
                    ldsm4t(w, sb + X_GB + (32 * i + lane) * 16);
                    const uint32_t a0[4] = {a[i][0], 0u, a[i][1], 0u}, a1[4] = {a[i][2], 0u, a[i][3], 0u};
                    mma16816(c[(2 * i) & 3], a0, w[0], w[1]);
                    mma16816(c[(2 * i + 1) & 3], a1, w[2], w[3]);
                }
            }
            if (lane < 16) sts32(sb + OWN_GB + lane * 4, pack_bf((c[0][0] + c[1][0]) + (c[2][0] + c[3][0]), (c[0][1] + c[1][1]) + (c[2][1] + c[3][1])));
            HPROF(6);
        }
        if (is_owner && warp == 9) nbar_arrive<NB_E6, 288>();
        if (is_f) gelu_stage(sb, warp - 8, lane);
        return;
    }

    const int g = lane >> 2, t4 = lane & 3;
    const int mi = lane >> 3, r8 = lane & 7;

    {
        auto silu4 = [&](const uint4& cv) {
            uint32_t w4[4] = {cv.x, cv.y, cv.z, cv.w};
#pragma unroll
            for (int e = 0; e < 4; e++) {
                float c0 = bf_lo(w4[e]), c1 = bf_hi(w4[e]);
                w4[e] = pack_bf(c0 * rcp_fast(1.f + ex2(-1.4426950408889634f * c0)), c1 * rcp_fast(1.f + ex2(-1.4426950408889634f * c1)));
            }
            return make_uint4(w4[0], w4[1], w4[2], w4[3]);
        };
        {
            uint4 v = silu4(ca0);
            sts128(sb + OFF_VA + (tid / 80) * VEC_STRIDE + (tid % 80) * 16, v);
            if (tid < 64) { v = silu4(ca1); sts128(sb + OFF_VA + 3 * VEC_STRIDE + (16 + tid) * 16, v); }
        }
        if (warp < 4) {
            float s = 0.f, q = 0.f;
            const float pv = __shfl_sync(0xffffffffu, bf_lo(xs[0].x), 0);
#pragma unroll
            for (int i = 0; i < 3; i++) if (i < 2 || lane < 16) acc_stats(xs[i], pv, s, q);
#pragma unroll
            for (int of = 16; of > 0; of >>= 1) { s += __shfl_xor_sync(0xffffffffu, s, of); q += __shfl_xor_sync(0xffffffffu, q, of); }
            uint32_t m2; float rden;
            ln_finish(pv, s, q, m2, rden);
            if (lane == 0) { sts32(sb + OFF_STAT + warp * 8, m2); sts_f32(sb + OFF_STAT + warp * 8 + 4, rden); }
        } else if (warp == 4) {
            sts32(sb + OWN_X + lane * 4, bf2_add(own0, 0u));
            sts_f32(sb + OWN_B1 + lane * 4, bf2f(own2));
        }
    }
    bar_cons();
    PROF(24);
    uint32_t qf[8][2];
    float o[8][4];
#pragma unroll
    for (int c = 0; c < 8; c++) { o[c][0] = o[c][1] = o[c][2] = o[c][3] = 0.f; }
    float m_run = -INFINITY, l_run = 0.f;
    const bool diag = (t4 == (g >> 1));
    const bool odd = g & 1;
    const uint32_t koff = (warp & 3) * 4096 + (r8 + 8 * (mi & 1)) * 256 + (mi >> 1) * 128 + (r8 << 4);
    const uint32_t voff = TILE_BYTES + (warp & 3) * 4096 + (r8 + 8 * (mi >> 1)) * 256 + (mi & 1) * 128 + (r8 << 4);
    const int src0 = (2 * t4) * 4 + t4, src1 = (2 * t4 + 1) * 4 + t4;
#pragma unroll 1
    for (int step = crit ? 0 : 1; step < 3; step++) {
        if (step < 2 || late) {
            if (step == 1) {
                if (!crit) mbar_wait(bar_wq, 0);
                const uint32_t m2 = lds32(sb + OFF_STAT + (tid & 3) * 8);
                const float rden = lds_f32(sb + OFF_STAT + (tid & 3) * 8 + 4);
                uint4 v[4];
                v[2] = v[3] = make_uint4(1, 1, 1, 1);
                const uint32_t* const p0 = mod_slot(0, tid >> 2, tid & 3);
                while ((int)(gtime32() - t_start) < MOD_T) { }
                PROF(2);
#pragma unroll 1
                for (int it = 0;; it++) {
                    ldg_relaxed_if(tid < 64, v[2], p0 + 16 * 64);
                    ldg_relaxed_if(tid < 64, v[3], p0 + 36 * 64);
                    v[0] = ldg_relaxed(p0);
                    v[1] = ldg_relaxed(p0 + 20 * 64);
                    if (__all_sync(0xffffffffu, min(min(min4(v[0]), min4(v[1])), min(min4(v[2]), min4(v[3]))) != 0u)) break;
                    if (it > SPIN_LIMIT) __trap();
                }
#pragma unroll
                for (int i = 0; i < 4; i++) v[i] = inv4(v[i]);
                PROF(3);
                uint4 h0 = ln_mod4(xa, v[1], v[0], m2, rden);
                sts128(sb + OFF_VB + (tid & 3) * VEC_STRIDE + (tid >> 2) * 16, h0);
                if (tid < 64) {
                    h0 = ln_mod4(xb, v[3], v[2], m2, rden);
                    sts128(sb + OFF_VB + (tid & 3) * VEC_STRIDE + (64 + (tid >> 2)) * 16, h0);
                }
            }
            mbar_wait(step == 1 ? bar_wq : bar_wm, 0);
            bar_cons();
            const uint32_t strip = sb + (step == 1 ? X_WQ : X_WM), vec = sb + (step == 1 ? OFF_VB : OFF_VA);
            float acc[2][4];
#pragma unroll
            for (int m = 0; m < 2; m++) { acc[m][0] = acc[m][1] = acc[m][2] = acc[m][3] = 0.f; }
#pragma unroll
            for (int i = 0; i < 5; i++) {
                int k0 = (warp * 5 + i) * 16;
                uint32_t b0, b1;
                load_bfrag(vec, VEC_STRIDE, k0, g, t4, b0, b1);
                int krow = k0 + r8 + 8 * (mi >> 1);
#pragma unroll
                for (int m = 0; m < 2; m++) {
                    uint32_t a[4];
                    int ch = 2 * m + (mi & 1);
                    ldsm4t(a, strip + krow * 64 + ((ch ^ ((krow >> 1) & 3)) << 4));
                    mma16816(acc[m], a, b0, b1);
                }
            }
            if (t4 < 2) {
#pragma unroll
                for (int m = 0; m < 2; m++) {
                    sts_f32x2(sb + OFF_RED + ((warp * 32 + m * 16 + g) * 4 + 2 * t4) * 4, acc[m][0], acc[m][1]);
                    sts_f32x2(sb + OFF_RED + ((warp * 32 + m * 16 + g + 8) * 4 + 2 * t4) * 4, acc[m][2], acc[m][3]);
                }
            }
            bar_cons();
            if (tid < 64) {
                float v0 = 0.f, v1 = 0.f;
#pragma unroll
                for (int w = 0; w < 8; w++) {
                    v0 += lds_f32(sb + OFF_RED + (w * 128 + (tid & 15) * 8 + (tid >> 4)) * 4);
                    v1 += lds_f32(sb + OFF_RED + (w * 128 + (tid & 15) * 8 + 4 + (tid >> 4)) * 4);
                }
                stg_relaxed(step == 1 ? g_q + (((cta & ~3) + (tid >> 4)) * 4 + bown) * 32 + (tid & 15) : g_mod + mc * 64 + tid, ~pack_bf(v0, v1));
            }
        }
        if (step == 0) continue;
        if (step == 1) {
            if (warp == 0) {
                { const uint32_t c0 = clock32(); while (clock32() - c0 < Q_PAUSE) { } }
                uint4 v = poll1(g_q + (cta * 4 + ((lane >> 2) & 3)) * 32 + (lane & 3) * 4, lane < 16);
                if (lane < 16) {
                    sts128(sb + OFF_Q + lane * 16, v);
                    stg_zero4(g_q + (cta * 4 + (lane >> 2)) * 32 + (lane & 3) * 4);
                }
            }
            bar_cons();
            PROF(4);

#pragma unroll
            for (int c = 0; c < 8; c++) {
                qf[c][0] = lds32(sb + OFF_Q + (((c ^ g) * 4 + t4) << 2));
                qf[c][1] = lds32(sb + OFF_Q + 128 + (((c ^ g) * 4 + t4) << 2));
            }
        } else {
            bar_cons();
            if (tid == 0) mbar_arrive(bar_xfree);
        }
#pragma unroll 1
        for (int j = (step == 1 ? 0 : SEG_J) + (warp >> 2); j < (step == 1 ? SEG_J : NITEM / 2 - 2); j += 2) {
            const int s = (2 * j) & (NS - 1);
            const uint32_t par = (j >> 2) & 1;
            mbar_wait(bar_full + s * 8, par);
            if (tid == 0 && 2 * j >= PH_FIRST) {
                const int x = min(max((int)(gtime32() - t_start) - 2 * j * PACE_TAU, 0), 65535);
                asm volatile("red.relaxed.gpu.global.add.u32 [%0], %1;" ::"l"(g_phase + (j >> 1) * 32), "r"((1u << 24) + (x >> 2)) : "memory");
            }
            const uint32_t base = sb + OFF_RING + s * TILE_BYTES;
            float sa[4] = {0.f, 0.f, 0.f, 0.f}, sb2[4] = {0.f, 0.f, 0.f, 0.f};
#pragma unroll
            for (int c = 0; c < 8; c += 2) {
                uint32_t a[4], a2[4];
                ldsm4(a, (base + koff) ^ (c << 4));
                ldsm4(a2, (base + koff) ^ ((c + 1) << 4));
                mma16816(sa, a, qf[c][0], qf[c][1]);
                mma16816(sb2, a2, qf[c + 1][0], qf[c + 1][1]);
            }
            const uint32_t sw = pack_bf(odd ? sa[1] + sb2[1] : sa[0] + sb2[0], odd ? sa[3] + sb2[3] : sa[2] + sb2[2]);
            const uint32_t sv = pack_bf(bf_lo(sw) * 0.08838834764831845f, bf_hi(sw) * 0.08838834764831845f);
            const float s0 = bf_lo(sv) * 1.4426950408889634f, s1 = bf_hi(sv) * 1.4426950408889634f;
            float m_new = fmaxf(m_run, fmaxf(s0, s1));
            const bool grow = __any_sync(0xffffffffu, (diag && (m_new > m_run)));
            if (lane == 0) mbar_arrive(bar_empty + s * 8);
            if (grow) {
                float al = ex2(m_run - m_new);
                float a0 = __shfl_sync(0xffffffffu, al, src0), a1 = __shfl_sync(0xffffffffu, al, src1);
#pragma unroll
                for (int c = 0; c < 8; c++) { o[c][0] *= a0; o[c][1] *= a1; o[c][2] *= a0; o[c][3] *= a1; }
                l_run *= al;
                m_run = m_new;
            }
            uint32_t pw = pack_bf(ex2(s0 - m_run), ex2(s1 - m_run));
            l_run += bf_lo(pw) + bf_hi(pw);
            uint32_t b0 = odd ? (pw << 16) : (pw & 0xffffu);
            uint32_t b1 = odd ? (pw & 0xffff0000u) : (pw >> 16);
            if (!diag) { b0 = 0u; b1 = 0u; }
            mbar_wait(bar_full + (s + 1) * 8, par);
#pragma unroll
            for (int c = 0; c < 8; c++) {
                uint32_t a[4];
                ldsm4t(a, (base + voff) ^ (c << 4));
                mma16816(o[c], a, b0, b1);
            }
            __syncwarp();
            if (lane == 0) mbar_arrive(bar_empty + (s + 1) * 8);
        }
    }
    PROF(5);
    float acc[4][4];
    uint32_t pa[8][2];
    float rinv;
    {
        const int s = 4 + (warp >> 2);
        mbar_wait(bar_full + s * 8, 1);
        const uint32_t base = sb + OFF_RING + s * TILE_BYTES;
        float sa[4] = {0.f, 0.f, 0.f, 0.f}, sb2[4] = {0.f, 0.f, 0.f, 0.f};
#pragma unroll
        for (int c = 0; c < 8; c += 2) {
            uint32_t a[4], a2[4];
            ldsm4(a, (base + koff) ^ (c << 4));
            ldsm4(a2, (base + koff) ^ ((c + 1) << 4));
            mma16816(sa, a, qf[c][0], qf[c][1]);
            mma16816(sb2, a2, qf[c + 1][0], qf[c + 1][1]);
        }
        const uint32_t sw = pack_bf(odd ? sa[1] + sb2[1] : sa[0] + sb2[0], odd ? sa[3] + sb2[3] : sa[2] + sb2[2]);
        const uint32_t sv = pack_bf(bf_lo(sw) * 0.08838834764831845f, bf_hi(sw) * 0.08838834764831845f);
        const float s0 = bf_lo(sv) * 1.4426950408889634f, s1 = bf_hi(sv) * 1.4426950408889634f;
        int mi_ = __float_as_int(diag ? fmaxf(m_run, fmaxf(s0, s1)) : -INFINITY);
        mi_ ^= (mi_ >> 31) & 0x7fffffff;
        mi_ = __reduce_max_sync(0xffffffffu, mi_);
        mi_ ^= (mi_ >> 31) & 0x7fffffff;
        if (lane == 0) sts32(sb + OFF_ML + warp * 4, mi_);
        bar_cons();
        const float4 m0 = lds_f32x4(sb + OFF_ML), m1 = lds_f32x4(sb + OFF_ML + 16);
        const float mx = fmaxf(fmaxf(fmaxf(m0.x, m0.y), fmaxf(m0.z, m0.w)), fmaxf(fmaxf(m1.x, m1.y), fmaxf(m1.z, m1.w)));
        const float scl = ex2(m_run - mx);
        const uint32_t pw = pack_bf(ex2(s0 - mx), ex2(s1 - mx));
        if (diag) { sts16(sb + SC_P + (warp * 16 + g) * 2, pw); sts16(sb + SC_P + (warp * 16 + g + 8) * 2, pw >> 16); }
        const float lw = warp_sum(diag ? fmaf(l_run, scl, bf_lo(pw) + bf_hi(pw)) : 0.f);
        const float a0 = __shfl_sync(0xffffffffu, scl, src0), a1 = __shfl_sync(0xffffffffu, scl, src1);
        float v[8], u[8];
#pragma unroll
        for (int c = 0; c < 8; c++) {
            v[c] = a0 * o[c][0] + a1 * o[c ^ 1][1];
            u[c] = a0 * o[c][2] + a1 * o[c ^ 1][3];
        }
#pragma unroll
        for (int c = 0; c < 8; c++) {
            if (!(c & 2)) {
                v[c] += __shfl_xor_sync(0xffffffffu, v[c ^ 2], 1);
                u[c] += __shfl_xor_sync(0xffffffffu, u[c ^ 2], 1);
            }
        }
#pragma unroll
        for (int c = 0; c < 2; c++) {
            v[c] += __shfl_xor_sync(0xffffffffu, v[c ^ 4], 2);
            u[c] += __shfl_xor_sync(0xffffffffu, u[c ^ 4], 2);
        }
        const uint32_t dst = sb + SC_OP + (warp * 128 + 16 * t4 + g) * 4;
        sts_f32(dst, v[0]); sts_f32(dst + 32, v[1]); sts_f32(dst + 256, u[0]); sts_f32(dst + 288, u[1]);
        if (lane == 0) sts_f32(sb + OFF_ML + 32 + warp * 4, lw);
        mbar_wait(bar_help, 0);
        bar_cons();
        const float4 l0 = lds_f32x4(sb + OFF_ML + 32), l1 = lds_f32x4(sb + OFF_ML + 48);
        rinv = rcp_fast(((l0.x + l0.y) + (l0.z + l0.w)) + ((l1.x + l1.y) + (l1.z + l1.w)));
#pragma unroll
        for (int i = 0; i < 4; i++) acc[i][0] = acc[i][1] = acc[i][2] = acc[i][3] = 0.f;
#pragma unroll
        for (int w = 0; w < 8; w++) {
            const float2 x0 = lds_f32x2(sb + SC_OP + (w * 128 + 16 * warp + 2 * t4) * 4), x1 = lds_f32x2(sb + SC_OP + (w * 128 + 16 * warp + 8 + 2 * t4) * 4);
            acc[2 * (w & 1)][0] += x0.x; acc[2 * (w & 1)][1] += x0.y;
            acc[2 * (w & 1) + 1][0] += x1.x; acc[2 * (w & 1) + 1][1] += x1.y;
        }
#pragma unroll
        for (int ks = 0; ks < 8; ks++) { pa[ks][0] = lds32(sb + SC_P + (8 * ks + t4) * 4); pa[ks][1] = lds32(sb + SC_P + (8 * ks + 4 + t4) * 4); }
    }
    PROF(20);
    const int mt = warp < 2 ? warp : warp + 2;
    {
        const uint32_t va = pin(sb + OFF_RING + 6 * TILE_BYTES + (warp >> 2) * (TILE_BYTES / 2) + (8 * (mi & 1) + r8) * 128 + (((2 * (warp & 3) + (mi >> 1)) ^ r8) << 4));
        const uint32_t vbar = pin(bar_v + (warp >> 2) * 8);
        uint32_t* const o_dst = pin(slot(SL_O + (cta >> 4), g) + (cta & 15) * 64 + warp * 8 + 2 * t4);
#pragma unroll
        for (int tl = 0; tl < 2; tl++) {
            mbar_wait(vbar + tl * 16, 0);
            uint32_t r[4][4];
#pragma unroll
            for (int ks = 0; ks < 4; ks++) ldsm4t(r[ks], va + tl * TILE_BYTES + ks * 2048);
#pragma unroll
            for (int ks = 0; ks < 4; ks++) {
                const uint32_t a[4] = {pa[4 * tl + ks][0], 0u, pa[4 * tl + ks][1], 0u};
                mma16816(acc[2 * (ks & 1)], a, r[ks][0], r[ks][1]);
                mma16816(acc[2 * (ks & 1) + 1], a, r[ks][2], r[ks][3]);
            }
        }
        stg_relaxed2_if(g < 2, o_dst, ~pack_bf((acc[0][0] + acc[2][0]) * rinv, (acc[0][1] + acc[2][1]) * rinv),
                        ~pack_bf((acc[1][0] + acc[3][0]) * rinv, (acc[1][1] + acc[3][1]) * rinv));
    }
    PROF(7);
    const int side = lds32(sb + OFF_SIDE);
    const uint32_t red_st = pin(sb + SC_E4 + ((warp * 4 + 2 * ((lane >> 3) & 1) + (lane >> 4)) * 8 + (lane & 7)) * 4);
    const uint32_t red_ld = pin(sb + SC_E4 + (lane & 15) * 8);
    const uint32_t* const in1 = pin(slot(SL_P1 + own, side) + tid * 4);
    const uint32_t* const in2a = pin(slot(SL_P2 + 2 * own, side) + tid * 4);
    const uint32_t* const in2b = pin(slot(SL_P2 + 2 * own + 1, side) + tid * 4);
    uint32_t* const out_dst = pin((uint32_t*)(p.out + ((lane >> 2) & 3) * D + 8 * own) + t4);
    uint32_t* const x1_dst = pin(slot(SL_X1 + own / 30, lane >> 4) + (own % 30) * 32 + (lane & 15));
    uint32_t* const rst = pin(tid >= 32 && tid < 56 ? mod_slot(lane >> 2, own, lane & 3) : own < 32 && tid == 64 ? g_clr + own * 4 : own < 16 && tid == 96 ? g_phase + own * 32 : nullptr);
    const uint32_t xw = lds32(sb + OWN_X + (lane & 15) * 4), ga_w = lds32(sb + OWN_GA + (lane & 15) * 4);
    uint32_t cs[15];
    uint32_t* dst2[5];
    uint32_t w2a[5];
#pragma unroll
    for (int j = 0; j < 10; j++) cs[j] = lds32(sb + OFF_VB + ((g & 1) * 4 + (g >> 1)) * VEC_STRIDE + warp * 160 + t4 * 4 + j * 16);
#pragma unroll
    for (int i = 0; i < 5; i++) {
        cs[10 + i] = lds32(sb + OFF_VB + (g >> 1) * VEC_STRIDE + warp * 160 + (g & 1) * 16 + t4 * 4 + i * 32);
        const uint2 t = lds64(sb + OFF_TAB2 + warp * 40 + i * 8);
        dst2[i] = slot_ptr((t4 < 2 ? t.x : t.y) + g * 16 + (t4 & 1) * 8);
        const int cc = 2 * (warp * 5 + i) + (mi & 1);
        w2a[i] = pin(sb + X_W2 + (cc >> 3) * 4096 + (r8 + 8 * (mi >> 1)) * 128 + (((cc & 7) ^ r8) << 4));
    }
    const uint32_t piv = lds32(sb + OFF_STAT + (g >> 1) * 8);
    const uint32_t* const xin = pin(slot(SL_X1 + warp / 3, side) + ((warp % 3) * 10 + (g & 1)) * 32 + (g >> 1) * 4 + t4);
    const uint32_t w1a = pin(sb + X_W1 + (warp * 80 + r8 + 8 * (mi >> 1)) * 64 + (((mi & 1) ^ ((r8 >> 1) & 3)) << 4));
    const uint32_t w1bar = pin(bar_w1 + (warp >> 1) * 8), w2bar = pin(bar_w2 + (warp + (warp >> 2)) * 8);
    const uint32_t wbar = pin(NB_O + warp);
    const uint32_t ab_st = pin(sb + SC_AB + warp * 1024 + lane * 16), y_st = pin(sb + SC_Y + warp * 512 + lane * 8), s_st = pin(sb + SC_ST + (t4 * 8 + warp) * 8);
    const uint32_t h_ld = pin(sb + SC_H1 + ((g & 3) ^ (2 * (f & 1) + ((f >> 1) & 1))) * 64 + t4 * 16);
    {
        const int kap = 2 * (head & 1) + ((head >> 1) & 1);
        const uint32_t wa = pin(sb + X_WO + (mt >> 1) * (DH * 64) + (r8 + 8 * (mi >> 1)) * 64 + ((((mt & 1) * 2 + (mi & 1)) ^ ((r8 >> 1) & 3)) << 4));
        const uint32_t oa = pin(sb + OFF_O + ((g & 3) ^ kap) * O_STRIDE + t4 * 8);
        uint32_t* dst[4];
#pragma unroll
        for (int i = 0; i < 2; i++) {
            const uint2 t = lds64(sb + OFF_TAB1 + (bown * 20 + 2 * mt + (warp < 2 ? 4 * i : 0)) * 4);
            dst[2 * i] = slot_ptr(t.x + g * 16 + t4 * 8);
            dst[2 * i + 1] = slot_ptr(t.y + g * 16 + t4 * 8);
        }
        PROF(6);
        const uint32_t wobar = pin(bar_wo + (mt >> 1) * 8);
        asm volatile("bar.sync %0, 64;" ::"r"(wbar) : "memory");
        uint2 ob[8];
#pragma unroll
        for (int ks = 0; ks < 8; ks++) ob[ks] = lds64(oa + ks * 32);
#pragma unroll
        for (int m = 0; m < 2; m++) {
            if (m == 0 || warp < 2) {
                mbar_wait(wobar + m * 8, 0);
                PROF(8);
                uint32_t wf[8][4];
#pragma unroll
                for (int ks = 0; ks < 8; ks++) ldsm4t(wf[ks], wa + m * (DH * 64) + ks * 1024);
                float c[4][4];
#pragma unroll
                for (int ks = 0; ks < 8; ks++) {
                    if (ks < 4) c[ks][0] = c[ks][1] = c[ks][2] = c[ks][3] = 0.f;
                    mma16816(c[ks & 3], wf[ks], ob[ks].x, ob[ks].y);
                }
                stg_relaxed2_if(t4 < 2, dst[2 * m], flag((c[0][0] + c[1][0]) + (c[2][0] + c[3][0])), flag((c[0][1] + c[1][1]) + (c[2][1] + c[3][1])));
                stg_relaxed2_if(t4 < 2, dst[2 * m + 1], flag((c[0][2] + c[1][2]) + (c[2][2] + c[3][2])), flag((c[0][3] + c[1][3]) + (c[2][3] + c[3][3])));
            }
        }
    }
    PROF(9);
    uint32_t x1w = 0;
    if (is_owner) {
        uint4 v;
        for (int it = 0;; it++) {
            v = ldg_relaxed(in1);
            if (__all_sync(0xffffffffu, and3(and3(v.x, v.y, v.z), v.w, 1u))) break;
            if (it > SPIN_LIMIT) __trap();
        }
        PROF(11);
        const float s0 = __uint_as_float(v.x) + __shfl_xor_sync(0xffffffffu, __uint_as_float(v.z), 8);
        const float s1 = __uint_as_float(v.y) + __shfl_xor_sync(0xffffffffu, __uint_as_float(v.w), 8);
        sts_f32(red_st, s0 + __shfl_xor_sync(0xffffffffu, s1, 16));
        nbar_sync<NB_E4, 256>();
        if (warp == 0) {
            float2 a[8];
#pragma unroll
            for (int w = 0; w < 8; w++) a[w] = lds_f32x2(red_ld + w * 128);
            const uint32_t aw = pack_bf(((a[0].x + a[1].x) + (a[2].x + a[3].x)) + ((a[4].x + a[5].x) + (a[6].x + a[7].x)),
                                        ((a[0].y + a[1].y) + (a[2].y + a[3].y)) + ((a[4].y + a[5].y) + (a[6].y + a[7].y)));
            x1w = bf2_add(xw, bf2_mul(ga_w, aw));
            stg_relaxed(x1_dst, x1w ^ 0x80008000u);
            if (lane == 0) mbar_arrive(bar_x1);
        }
        if (rst) stg_zero4(rst);
    }
    PROF(12);
    if (is_f) {
        uint32_t f1[5][2][4], f2[5][2][4];
        uint32_t d[6];
        auto load_x1 = [&] {
#pragma unroll
            for (int i = 0; i < 5; i++) d[i] = ldg_relaxed32(xin + i * 64);
        };
        auto have_x1 = [&] { return __all_sync(0xffffffffu, __vimin3_u32(__vimin3_u32(d[0], d[1], d[2]), d[3], d[4]) != 0u); };
        mbar_wait(w1bar, 0);
        load_x1();
        {
#pragma unroll
            for (int i = 0; i < 5; i++) { ldsm4t(f1[i][0], w1a + i * 1024); ldsm4t(f1[i][1], (w1a ^ 32) + i * 1024); }
            float c[2][4];
#pragma unroll
            for (int m = 0; m < 2; m++) c[m][0] = c[m][1] = c[m][2] = c[m][3] = 0.f;
#pragma unroll
            for (int i = 0; i < 5; i++) { mma16816(c[0], f1[i][0], cs[2 * i], cs[2 * i + 1]); mma16816(c[1], f1[i][1], cs[2 * i], cs[2 * i + 1]); }
#pragma unroll
            for (int i = 0; i < 5; i++) { cs[2 * i] = pin(odd ? 0u : cs[10 + i]); cs[2 * i + 1] = pin(odd ? cs[10 + i] : 0u); }
#pragma unroll
            for (int m = 0; m < 2; m++) sts128(ab_st + m * 512, make_uint4(__float_as_uint(c[m][0]), __float_as_uint(c[m][1]), __float_as_uint(c[m][2]), __float_as_uint(c[m][3])));
            nbar_arrive<NB_AB, 320>();
            d[0] |= __float_as_uint(c[1][3]) & (side >> 1);
        }
        PROF(10);
#pragma unroll 1
        for (int it = 0; !have_x1(); it++) {
            load_x1();
            if (it > SPIN_LIMIT) __trap();
        }
        PROF(13);
        {
            float y[2][4], st[4] = {0.f, 0.f, 0.f, 0.f};
#pragma unroll
            for (int m = 0; m < 2; m++) y[m][0] = y[m][1] = y[m][2] = y[m][3] = 0.f;
#pragma unroll
            for (int i = 0; i < 5; i++) d[i] = bf2_add(d[i], piv);
            d[5] = 0u;
#pragma unroll
            for (int i = 0; i < 5; i++) {
                if (i < 3) {
                    const uint32_t a[4] = {d[2 * i], 0x3f803f80u, d[2 * i + 1], 0x3f803f80u};
                    mma16816(st, a, d[2 * i], d[2 * i + 1]);
                }
                const uint32_t y0 = bf2_mul(d[i], cs[2 * i]), y1 = bf2_mul(d[i], cs[2 * i + 1]);
                mma16816(y[0], f1[i][0], y0, y1);
                mma16816(y[1], f1[i][1], y0, y1);
            }
            const float q = odd ? st[1] : st[0];
            const float q2 = q + __shfl_xor_sync(0xffffffffu, q, 4);
            if (diag && !odd) sts_f32x2(s_st, q2, st[2] + st[3]);
#pragma unroll
            for (int m = 0; m < 2; m++) sts_f32x2(y_st + m * 256, y[m][0] + y[m][1], y[m][2] + y[m][3]);
        }
        nbar_arrive<NB_Y, 320>();
        PROF(14);
        mbar_wait(w2bar, 0);
        mbar_wait(w2bar + 8, 0);
#pragma unroll
        for (int i = 0; i < 5; i++) { ldsm4t(f2[i][0], w2a[i]); ldsm4t(f2[i][1], w2a[i] + 2048); }
        asm volatile("bar.sync %0, 96;" ::"r"(wbar) : "memory");
        PROF(15);
        {
            const uint4 hb = lds128(h_ld);
            float c[5][4];
#pragma unroll
            for (int i = 0; i < 5; i++) { c[i][0] = c[i][1] = c[i][2] = c[i][3] = 0.f; mma16816(c[i], f2[i][0], hb.x, hb.y); }
#pragma unroll
            for (int i = 0; i < 5; i++) {
                mma16816(c[i], f2[i][1], hb.z, hb.w);
                stg_relaxed2_if(true, dst2[i], flag(t4 < 2 ? c[i][0] : c[i][2]), flag(t4 < 2 ? c[i][1] : c[i][3]));
            }
        }
    }
    PROF(16);
    if (is_owner) {
        const uint32_t b2w = lds32(sb + OWN_B2 + (lane & 15) * 4), gb_ld = pin(sb + OWN_GB + (lane & 15) * 4);
        const bool two = tid < NF * 8 - 256;
        uint4 v, w = make_uint4(1, 1, 1, 1);
        for (int it = 0;; it++) {
            ldg_relaxed_if(two, w, in2b);
            v = ldg_relaxed(in2a);
            if (__all_sync(0xffffffffu, and3(and3(v.x, v.y, v.z), and3(v.w, w.x, w.y), and3(w.z, w.w, 1u)))) break;
            if (it > SPIN_LIMIT) __trap();
        }
        PROF(17);
        const float s0 = (__uint_as_float(v.x) + __uint_as_float(w.x)) + __shfl_xor_sync(0xffffffffu, __uint_as_float(v.z) + __uint_as_float(w.z), 8);
        const float s1 = (__uint_as_float(v.y) + __uint_as_float(w.y)) + __shfl_xor_sync(0xffffffffu, __uint_as_float(v.w) + __uint_as_float(w.w), 8);
        sts_f32(red_st + (SC_E6 - SC_E4), s0 + __shfl_xor_sync(0xffffffffu, s1, 16));
        if (warp != 0) {
            nbar_arrive<NB_E6, 288>();
        } else {
            nbar_sync<NB_E6, 288>();
            float2 a[8];
#pragma unroll
            for (int i = 0; i < 8; i++) a[i] = lds_f32x2(red_ld + (SC_E6 - SC_E4) + i * 128);
            const uint32_t gb_w = lds32(gb_ld);
            const uint32_t aw = pack_bf(((a[0].x + a[1].x) + (a[2].x + a[3].x)) + ((a[4].x + a[5].x) + (a[6].x + a[7].x)),
                                        ((a[0].y + a[1].y) + (a[2].y + a[3].y)) + ((a[4].y + a[5].y) + (a[6].y + a[7].y)));
            x1w = bf2_add(x1w, bf2_mul(gb_w, bf2_add(aw, b2w)));
            if (lane < 16) asm volatile("st.global.u32 [%0], %1;" ::"l"(out_dst), "r"(x1w) : "memory");
        }
    }
    PROF(18);
    PROF_DUMP;
}

typedef CUresult (*EncodeFn)(CUtensorMap*, CUtensorMapDataType, cuuint32_t, void*, const cuuint64_t*, const cuuint64_t*, const cuuint32_t*,
                             const cuuint32_t*, CUtensorMapInterleave, CUtensorMapSwizzle, CUtensorMapL2promotion, CUtensorMapFloatOOBfill);

static CUtensorMap make_map(EncodeFn enc, const void* ptr, int cols, int rows, int box_cols, int box_rows, CUtensorMapSwizzle sw,
                            CUtensorMapL2promotion promo = CU_TENSOR_MAP_L2_PROMOTION_NONE) {
    CUtensorMap m;
    cuuint64_t dims[2] = {(cuuint64_t)cols, (cuuint64_t)rows};
    cuuint64_t strides[1] = {(cuuint64_t)cols * 2};
    cuuint32_t box[2] = {(cuuint32_t)box_cols, (cuuint32_t)box_rows};
    cuuint32_t es[2] = {1, 1};
    enc(&m, CU_TENSOR_MAP_DATA_TYPE_BFLOAT16, 2, const_cast<void*>(ptr), dims, strides, box, es, CU_TENSOR_MAP_INTERLEAVE_NONE, sw,
        promo, CU_TENSOR_MAP_FLOAT_OOB_FILL_NONE);
    return m;
}

}

extern "C" void kernel_launch(void* const* d_in, const int* in_sizes, int n_in, void* d_out, int out_size) {
    (void)in_sizes; (void)n_in; (void)out_size;
    static EncodeFn enc = nullptr;
    if (!enc) {
        void* fn = nullptr;
        cudaDriverEntryPointQueryResult qr;
        cudaGetDriverEntryPoint("cuTensorMapEncodeTiled", &fn, cudaEnableDefault, &qr);
        enc = (EncodeFn)fn;
        cudaFuncSetAttribute(fused_kernel, cudaFuncAttributeMaxDynamicSharedMemorySize, SMEM_BYTES);
    }
    Params p;
    p.x = (const __nv_bfloat16*)d_in[0];
    p.kc = (const __nv_bfloat16*)d_in[1];
    p.vc = (const __nv_bfloat16*)d_in[2];
    p.b1 = (const __nv_bfloat16*)d_in[7];
    p.b2 = (const __nv_bfloat16*)d_in[9];
    p.c = (const __nv_bfloat16*)d_in[10];
    p.out = (__nv_bfloat16*)d_out;
    CUtensorMap tm_wmod = make_map(enc, d_in[11], NMOD, D, 32, 160, CU_TENSOR_MAP_SWIZZLE_64B);
    CUtensorMap tm_wq = make_map(enc, d_in[3], NH * DH, D, 32, 160, CU_TENSOR_MAP_SWIZZLE_64B);
    CUtensorMap tm_wo = make_map(enc, d_in[4], D, NH * DH, 32, 128, CU_TENSOR_MAP_SWIZZLE_64B);
    CUtensorMap tm_w1 = make_map(enc, d_in[6], FF, D, 32, 160, CU_TENSOR_MAP_SWIZZLE_64B);
    CUtensorMap tm_w2 = make_map(enc, d_in[8], D, FF, 64, 32, CU_TENSOR_MAP_SWIZZLE_128B);
    CUtensorMap tm_v = make_map(enc, d_in[2], DH, NB * NH * SK, 64, TILE_KEYS, CU_TENSOR_MAP_SWIZZLE_128B);
    CUtensorMap tm_gb = make_map(enc, d_in[11], NMOD, D, 8, 160, CU_TENSOR_MAP_SWIZZLE_NONE, CU_TENSOR_MAP_L2_PROMOTION_L2_128B);
    fused_kernel<<<NCTA, NTHREADS, SMEM_BYTES>>>(p, tm_wmod, tm_wq, tm_wo, tm_w1, tm_w2, tm_v, tm_gb);
}
```

```cpp
#include <cuda_runtime.h>
#include <cuda.h>
#include <cuda_bf16.h>
#include <stdint.h>

namespace {

constexpr int NB = 4, D = 640, NH = 32, DH = 128, SK = 8192, WIN = 2048, FF = 1728, NMOD = 6 * D;
constexpr int NCTA = 128;
constexpr int NOWN = 80;
constexpr int NF = 54;
constexpr int NTHREADS = 320;
constexpr int TILE_KEYS = 64;
constexpr int TILE_BYTES = TILE_KEYS * DH * 2;
constexpr int NITEM = 2 * WIN / TILE_KEYS;
constexpr int NS = 8;
constexpr int NMODC = 120;
constexpr int SPIN_LIMIT = 1 << 18;
#define INFLIGHT 3
#define WQ_DELAY 500
#define MOD_T 4200
#define Q_PAUSE 1100
#define PACE_A 7500
#define PACE_TAU 635
#define ROTA 8
#define ROTB 0
#define PF_END 16
#define PH_FIRST 20
#define PH_LAG 5
#define LAT_T 2100
#define WO_T -900
#define WO_S 250
#define W1_T 950
#define W2_T 1650
#define GB_T 2500
#define GB_EV 300
#define CLR_CHECK 28000
constexpr int NPROBE = 8, PROBE_END = 10000;
constexpr int SEG_J = 8;

constexpr int OFF_RING = 0;
constexpr int OFF_X = OFF_RING + NS * TILE_BYTES;
constexpr int X_WM = OFF_X;
constexpr int X_WQ = OFF_X + D * 64;
constexpr int X_WO = OFF_X;
constexpr int X_W1 = X_WO + 5 * DH * 64;
constexpr int X_END = X_W1 + D * 64;
constexpr int X_W2 = OFF_RING;
constexpr int X_GB = OFF_RING + 3 * TILE_BYTES;
static_assert(X_WQ + D * 64 <= X_END, "prologue weights must fit");
constexpr int VEC_STRIDE = 1296;
constexpr int OFF_VA = X_END;
constexpr int OFF_VB = OFF_VA + 4 * VEC_STRIDE;
constexpr int OFF_RED = OFF_VB + 4 * VEC_STRIDE;
constexpr int OFF_ML = OFF_RED + 4 * VEC_STRIDE;
constexpr int O_STRIDE = 288;
constexpr int OFF_O = OFF_ML + 64;
constexpr int OFF_Q = OFF_O + 4 * O_STRIDE;
constexpr int OFF_OWN = OFF_Q + 256;
constexpr int OWN_X = OFF_OWN, OWN_B2 = OWN_X + 64, OWN_GA = OWN_B2 + 64, OWN_GB = OWN_GA + 64, OWN_B1 = OWN_GB + 64;
constexpr int OFF_STAT = OWN_B1 + 128;
constexpr int OFF_TAB1 = OFF_STAT + 32;
constexpr int OFF_TAB2 = OFF_TAB1 + NOWN * 4;
constexpr int OFF_SIDE = OFF_TAB2 + NOWN * 4;
constexpr int OFF_BAR = OFF_SIDE + 8;
constexpr int NBAR = 2 * NS + 32;
constexpr int SMEM_BYTES = OFF_BAR + NBAR * 8;
constexpr int SC_OP = OFF_RING + 4 * TILE_BYTES;
constexpr int SC_AB = SC_OP + 4096;
constexpr int SC_Y = SC_AB + 8192;
constexpr int SC_ST = SC_Y + 4096;
constexpr int SC_E4 = SC_ST + 256;
constexpr int SC_E6 = SC_E4 + 1024;
constexpr int SC_P = SC_E6 + 1024;
constexpr int SC_H1 = SC_P + 256;
static_assert(SMEM_BYTES <= 232448, "smem");
static_assert(OFF_BAR % 8 == 0 && OFF_X % 1024 == 0 && X_WQ % 512 == 0 && X_W1 % 512 == 0 && OFF_VA % 16 == 0 && OFF_RED % 16 == 0 && OFF_ML % 16 == 0 && OFF_O % 16 == 0 && OFF_Q % 16 == 0, "align");
constexpr int NB_O = 2  , NB_E4 = 10, NB_E6 = 11, NB_AB = 12, NB_Y = 13;

__device__ __align__(128) uint32_t g_mod[NMODC * 64];
__device__ __align__(128) uint32_t g_q[NCTA * 128];
__device__ uint32_t g_clr[NCTA];
__device__ uint32_t g_phase[16 * 32];
constexpr int SL_P1 = 0;
constexpr int SL_P2 = SL_P1 + NOWN;
constexpr int SL_O = SL_P2 + 2 * NOWN;
constexpr int SL_X1 = SL_O + 8;
constexpr int SL_SIDE = SL_X1 + 3;
static_assert(SL_SIDE < 256, "one 2 MB page");
__device__ uint32_t g_slots[2 * 256 * 2048];
__device__ __forceinline__ uint32_t* slot(int i, int side) {
    const size_t base = ((size_t)g_slots + 0x1fffff) & ~(size_t)0x1fffff;
    return (uint32_t*)base + i * 2048 + (((__popc(i & 0x59) ^ side) & 1) << 10);
}
#define PROF_DECL
#define HPROF(i) do { } while (0)
#define PROF(i) do { } while (0)
#define PROF_DUMP do { } while (0)

__device__ __forceinline__ uint32_t smem_u32(const void* p) { return (uint32_t)__cvta_generic_to_shared(p); }
__device__ __forceinline__ void mbar_init(uint32_t bar, uint32_t cnt) { asm volatile("mbarrier.init.shared::cta.b64 [%0], %1;" ::"r"(bar), "r"(cnt) : "memory"); }
__device__ __forceinline__ void mbar_expect_tx(uint32_t bar, uint32_t bytes) { asm volatile("mbarrier.arrive.expect_tx.shared::cta.b64 _, [%0], %1;" ::"r"(bar), "r"(bytes) : "memory"); }
__device__ __forceinline__ void mbar_arrive(uint32_t bar) { asm volatile("mbarrier.arrive.shared::cta.b64 _, [%0];" ::"r"(bar) : "memory"); }
__device__ __forceinline__ void mbar_wait(uint32_t bar, uint32_t parity) {
    uint32_t ok;
    int it = 0;
    while (true) {
        asm volatile("{\n.reg .pred p;\nmbarrier.try_wait.parity.shared::cta.b64 p, [%1], %2;\nselp.u32 %0, 1, 0, p;\n}" : "=r"(ok) : "r"(bar), "r"(parity) : "memory");
        if (ok) break;
        if (++it > SPIN_LIMIT) __trap();
    }
}
__device__ __forceinline__ void bulk_load(uint32_t dst, const void* src, uint32_t bytes, uint32_t bar, uint64_t pol) {
    asm volatile("cp.async.bulk.shared::cluster.global.mbarrier::complete_tx::bytes.L2::cache_hint [%0], [%1], %2, [%3], %4;"
                 ::"r"(dst), "l"(src), "r"(bytes), "r"(bar), "l"(pol) : "memory");
}
__device__ __forceinline__ void bar_cons() { asm volatile("bar.sync 1, 256;" ::: "memory"); }
template <int ID, int N> __device__ __forceinline__ void nbar_sync() { asm volatile("bar.sync %0, %1;" ::"n"(ID), "n"(N) : "memory"); }
template <int ID, int N> __device__ __forceinline__ void nbar_arrive() { asm volatile("bar.arrive %0, %1;" ::"n"(ID), "n"(N) : "memory"); }
__device__ __forceinline__ bool mbar_test(uint32_t bar, uint32_t parity) {
    uint32_t ok;
    asm volatile("{\n.reg .pred p;\nmbarrier.test_wait.parity.shared::cta.b64 p, [%1], %2;\nselp.u32 %0, 1, 0, p;\n}" : "=r"(ok) : "r"(bar), "r"(parity) : "memory");
    return ok;
}
__device__ __forceinline__ uint32_t pin(uint32_t v) { asm volatile("" : "+r"(v)); return v; }
template <class T> __device__ __forceinline__ T pin_hard(T v) { return __shfl_sync(0xffffffffu, v, threadIdx.x & 31); }
template <class T> __device__ __forceinline__ T* pin(T* v) { asm volatile("" : "+l"(v)); return v; }
__device__ __forceinline__ void ldsm4(uint32_t (&a)[4], uint32_t addr) {
    asm volatile("ldmatrix.sync.aligned.m8n8.x4.shared.b16 {%0,%1,%2,%3}, [%4];" : "=r"(a[0]), "=r"(a[1]), "=r"(a[2]), "=r"(a[3]) : "r"(addr) : "memory");
}
__device__ __forceinline__ void ldsm4t(uint32_t (&a)[4], uint32_t addr) {
    asm volatile("ldmatrix.sync.aligned.m8n8.x4.trans.shared.b16 {%0,%1,%2,%3}, [%4];" : "=r"(a[0]), "=r"(a[1]), "=r"(a[2]), "=r"(a[3]) : "r"(addr) : "memory");
}
__device__ __forceinline__ void mma16816(float (&c)[4], const uint32_t (&a)[4], uint32_t b0, uint32_t b1) {
    asm volatile("mma.sync.aligned.m16n8k16.row.col.f32.bf16.bf16.f32 {%0,%1,%2,%3}, {%4,%5,%6,%7}, {%8,%9}, {%0,%1,%2,%3};"
                 : "+f"(c[0]), "+f"(c[1]), "+f"(c[2]), "+f"(c[3]) : "r"(a[0]), "r"(a[1]), "r"(a[2]), "r"(a[3]), "r"(b0), "r"(b1));
}
__device__ __forceinline__ uint32_t lds32(uint32_t addr) { uint32_t v; asm volatile("ld.shared.u32 %0, [%1];" : "=r"(v) : "r"(addr) : "memory"); return v; }
__device__ __forceinline__ float lds_f32(uint32_t addr) { float v; asm volatile("ld.shared.f32 %0, [%1];" : "=f"(v) : "r"(addr) : "memory"); return v; }
__device__ __forceinline__ float2 lds_f32x2(uint32_t addr) { float2 v; asm volatile("ld.shared.v2.f32 {%0,%1}, [%2];" : "=f"(v.x), "=f"(v.y) : "r"(addr) : "memory"); return v; }
__device__ __forceinline__ float4 lds_f32x4(uint32_t addr) { float4 v; asm volatile("ld.shared.v4.f32 {%0,%1,%2,%3}, [%4];" : "=f"(v.x), "=f"(v.y), "=f"(v.z), "=f"(v.w) : "r"(addr) : "memory"); return v; }
__device__ __forceinline__ uint2 lds64(uint32_t addr) { uint2 v; asm volatile("ld.shared.v2.u32 {%0,%1}, [%2];" : "=r"(v.x), "=r"(v.y) : "r"(addr) : "memory"); return v; }
__device__ __forceinline__ uint4 lds128(uint32_t addr) { uint4 v; asm volatile("ld.shared.v4.u32 {%0,%1,%2,%3}, [%4];" : "=r"(v.x), "=r"(v.y), "=r"(v.z), "=r"(v.w) : "r"(addr) : "memory"); return v; }
__device__ __forceinline__ void sts16(uint32_t addr, uint32_t v) { asm volatile("st.shared.b16 [%0], %1;" ::"r"(addr), "h"((unsigned short)v) : "memory"); }
__device__ __forceinline__ void sts32(uint32_t addr, uint32_t v) { asm volatile("st.shared.u32 [%0], %1;" ::"r"(addr), "r"(v) : "memory"); }
__device__ __forceinline__ void sts_f32(uint32_t addr, float v) { asm volatile("st.shared.f32 [%0], %1;" ::"r"(addr), "f"(v) : "memory"); }
__device__ __forceinline__ void sts_f32x2(uint32_t addr, float a, float b) { asm volatile("st.shared.v2.f32 [%0], {%1,%2};" ::"r"(addr), "f"(a), "f"(b) : "memory"); }
__device__ __forceinline__ void sts128(uint32_t addr, uint4 v) { asm volatile("st.shared.v4.u32 [%0], {%1,%2,%3,%4};" ::"r"(addr), "r"(v.x), "r"(v.y), "r"(v.z), "r"(v.w) : "memory"); }
__device__ __forceinline__ uint4 ldg_relaxed(const uint32_t* p) {
    uint4 v;
    asm volatile("ld.relaxed.gpu.global.v4.u32 {%0,%1,%2,%3}, [%4];" : "=r"(v.x), "=r"(v.y), "=r"(v.z), "=r"(v.w) : "l"(p) : "memory");
    return v;
}
__device__ __forceinline__ void ldg_relaxed_if(bool on, uint4& v, const uint32_t* p) {
    asm volatile("{\n.reg .pred q;\nsetp.ne.u32 q, %5, 0;\n@q ld.relaxed.gpu.global.v4.u32 {%0,%1,%2,%3}, [%4];\n}"
                 : "+r"(v.x), "+r"(v.y), "+r"(v.z), "+r"(v.w) : "l"(p), "r"((uint32_t)on) : "memory");
}
__device__ __forceinline__ void stg_relaxed2_if(bool on, uint32_t* p, uint32_t a, uint32_t b) {
    asm volatile("{\n.reg .pred q;\nsetp.ne.u32 q, %3, 0;\n@q st.relaxed.gpu.global.v2.u32 [%0], {%1,%2};\n}" ::"l"(p), "r"(a), "r"(b), "r"((uint32_t)on) : "memory");
}
__device__ __forceinline__ uint32_t ldg_relaxed32(const uint32_t* p) { uint32_t v; asm volatile("ld.relaxed.gpu.global.u32 %0, [%1];" : "=r"(v) : "l"(p) : "memory"); return v; }
__device__ __forceinline__ void stg_relaxed(uint32_t* p, uint32_t v) { asm volatile("st.relaxed.gpu.global.u32 [%0], %1;" ::"l"(p), "r"(v) : "memory"); }
__device__ __forceinline__ void stg_zero4(uint32_t* p) { asm volatile("st.relaxed.gpu.global.v4.u32 [%0], {%1,%1,%1,%1};" ::"l"(p), "r"(0u) : "memory"); }
__device__ __forceinline__ bool ready(const uint4& v) { return (v.x != 0u) & (v.y != 0u) & (v.z != 0u) & (v.w != 0u); }
__device__ __forceinline__ uint32_t min4(const uint4& v) { return min(__vimin3_u32(v.x, v.y, v.z), v.w); }
__device__ __forceinline__ uint4 inv4(const uint4& v) { return make_uint4(~v.x, ~v.y, ~v.z, ~v.w); }
__device__ __forceinline__ uint32_t pack_bf(float lo, float hi) {
    uint32_t r;
    asm("cvt.rn.bf16x2.f32 %0, %1, %2;" : "=r"(r) : "f"(hi), "f"(lo));
    return r;
}
__device__ __forceinline__ float bfr(float x) { return __uint_as_float(pack_bf(0.f, x) & 0xffff0000u); }
__device__ __forceinline__ float bf_lo(uint32_t w) { return __uint_as_float(w << 16); }
__device__ __forceinline__ float bf_hi(uint32_t w) { return __uint_as_float(w & 0xffff0000u); }
__device__ __forceinline__ float bf2f(__nv_bfloat16 v) { return __bfloat162float(v); }
__device__ __forceinline__ float ex2(float x) { float y; asm("ex2.approx.ftz.f32 %0, %1;" : "=f"(y) : "f"(x)); return y; }
__device__ __forceinline__ float rcp_fast(float x) { float y; asm("rcp.approx.ftz.f32 %0, %1;" : "=f"(y) : "f"(x)); return y; }
__device__ __forceinline__ float rsqrt_fast(float x) { float y; asm("rsqrt.approx.ftz.f32 %0, %1;" : "=f"(y) : "f"(x)); return y; }
__device__ __forceinline__ float sqrt_fast(float x) { float y; asm("sqrt.approx.f32 %0, %1;" : "=f"(y) : "f"(x)); return y; }
__device__ __forceinline__ uint32_t bf2_add(uint32_t a, uint32_t b) { uint32_t r; asm("add.rn.bf16x2 %0, %1, %2;" : "=r"(r) : "r"(a), "r"(b)); return r; }
__device__ __forceinline__ uint32_t bf2_sub(uint32_t a, uint32_t b) { uint32_t r; asm("sub.rn.bf16x2 %0, %1, %2;" : "=r"(r) : "r"(a), "r"(b)); return r; }
__device__ __forceinline__ uint32_t bf2_mul(uint32_t a, uint32_t b) { uint32_t r; asm("mul.rn.bf16x2 %0, %1, %2;" : "=r"(r) : "r"(a), "r"(b)); return r; }
__device__ __forceinline__ uint32_t gtime32() { uint32_t c; asm volatile("mov.u32 %0, %%globaltimer_lo;" : "=r"(c)); return c; }
__device__ __forceinline__ uint32_t clock32() { uint32_t c; asm volatile("mov.u32 %0, %%clock;" : "=r"(c)); return c; }

__device__ __forceinline__ float warp_sum(float v) {
#pragma unroll
    for (int o = 16; o > 0; o >>= 1) v += __shfl_xor_sync(0xffffffffu, v, o);
    return v;
}

struct Params {
    const __nv_bfloat16 *x, *kc, *vc, *b1, *b2, *c;
    __nv_bfloat16* out;
};

__device__ __forceinline__ void tma2d(uint32_t dst, const CUtensorMap* tm, int x, int y, uint32_t bar) {
    asm volatile("cp.async.bulk.tensor.2d.shared::cluster.global.mbarrier::complete_tx::bytes [%0], [%1, {%2, %3}], [%4];"
                 ::"r"(dst), "l"(tm), "r"(x), "r"(y), "r"(bar) : "memory");
}

__device__ __forceinline__ void tma2d_hint(uint32_t dst, const CUtensorMap* tm, int x, int y, uint32_t bar, uint64_t pol) {
    asm volatile("cp.async.bulk.tensor.2d.shared::cluster.global.mbarrier::complete_tx::bytes.L2::cache_hint [%0], [%1, {%2, %3}], [%4], %5;"
                 ::"r"(dst), "l"(tm), "r"(x), "r"(y), "r"(bar), "l"(pol) : "memory");
}
__device__ __forceinline__ uint32_t flag(float v) { return __float_as_uint(v) | 1u; }
__device__ __forceinline__ uint32_t and3(uint32_t a, uint32_t b, uint32_t c) { uint32_t r; asm("lop3.b32 %0, %1, %2, %3, 0x80;" : "=r"(r) : "r"(a), "r"(b), "r"(c)); return r; }
__device__ __forceinline__ uint32_t* slot_ptr(uint32_t lo) {
    uint32_t* r;
    asm volatile("mov.b64 %0, {%1, %2};" : "=l"(r) : "r"(lo), "r"((uint32_t)((size_t)slot(0, 0) >> 32)));
    return r;
}

__device__ __forceinline__ void load_bfrag(uint32_t vec, int stride, int k0, int g, int t, uint32_t& b0, uint32_t& b1) {
    uint32_t a = vec + (g & 3) * stride + (k0 + 2 * t) * 2;
    b0 = lds32(a);
    b1 = lds32(a + 16);
}

__device__ __forceinline__ void ln_finish(float pivot, float sum, float sumsq, uint32_t& m2, float& rden) {
    float dm = sum * (1.f / D);
    float var = fmaxf(sumsq * (1.f / D) - dm * dm, 0.f);
    float mean = pivot + dm;
    m2 = pack_bf(mean, mean);
    rden = rcp_fast(bfr(sqrt_fast(bfr(bfr(var) + 1e-5f))));
}
__device__ __forceinline__ uint32_t ln_mod_pair(uint32_t xw, uint32_t cw, uint32_t sw, uint32_t m2, float rden) {
    uint32_t d = bf2_sub(xw, m2);
    uint32_t ln = pack_bf(bf_lo(d) * rden, bf_hi(d) * rden);
    return bf2_add(bf2_mul(ln, bf2_add(cw, 0x3f803f80u)), sw);
}
__device__ __forceinline__ uint4 ln_mod4(const uint4& x, const uint4& c, const uint4& s, uint32_t m2, float rden) {
    return make_uint4(ln_mod_pair(x.x, c.x, s.x, m2, rden), ln_mod_pair(x.y, c.y, s.y, m2, rden),
                      ln_mod_pair(x.z, c.z, s.z, m2, rden), ln_mod_pair(x.w, c.w, s.w, m2, rden));
}
__device__ __forceinline__ void acc_stats(const uint4& v, float pv, float& s, float& q) {
    const float a0 = bf_lo(v.x) - pv, a1 = bf_hi(v.x) - pv, a2 = bf_lo(v.y) - pv, a3 = bf_hi(v.y) - pv;
    const float a4 = bf_lo(v.z) - pv, a5 = bf_hi(v.z) - pv, a6 = bf_lo(v.w) - pv, a7 = bf_hi(v.w) - pv;
    s += ((a0 + a1) + (a2 + a3)) + ((a4 + a5) + (a6 + a7));
    q += (fmaf(a0, a0, a1 * a1) + fmaf(a2, a2, a3 * a3)) + (fmaf(a4, a4, a5 * a5) + fmaf(a6, a6, a7 * a7));
}
__device__ __forceinline__ uint32_t* mod_slot(int kind, int j, int b) { return g_mod + (kind * 20 + (j >> 2)) * 64 + b * 16 + (j & 3) * 4; }

template <int N>
__device__ __forceinline__ void poll_n(uint4 (&v)[N], const uint32_t* const* ptr, const bool* on) {
    bool pend[N];
#pragma unroll
    for (int i = 0; i < N; i++) pend[i] = on[i];
    int it = 0;
    while (true) {
#pragma unroll
        for (int i = 0; i < N; i++) if (pend[i]) v[i] = ldg_relaxed(ptr[i]);
        bool any = false;
#pragma unroll
        for (int i = 0; i < N; i++) { pend[i] = pend[i] && !ready(v[i]); any |= pend[i]; }
        if (!__any_sync(0xffffffffu, any)) break;
        if (++it > SPIN_LIMIT) __trap();
    }
#pragma unroll
    for (int i = 0; i < N; i++) v[i] = inv4(v[i]);
}
__device__ __forceinline__ uint4 poll1(const uint32_t* p, bool on) {
    uint4 v[1] = {make_uint4(0, 0, 0, 0)};
    const uint32_t* const ptr[1] = {p};
    const bool o[1] = {on};
    poll_n<1>(v, ptr, o);
    return v[0];
}

__device__ __forceinline__ void gelu_stage(uint32_t sb, int m, int lane) {
    const int g = lane >> 2, b = lane & 3;
    const uint32_t y_ld = pin_hard(sb + SC_Y + m * 256 + lane * 8), s_ld = pin_hard(sb + SC_ST + b * 64);
    const uint32_t h_st = pin_hard(sb + SC_H1 + b * 64 + (g >> 1) * 16 + m * 8 + (g & 1) * 2);
    float a0 = 0.f, b0 = lds_f32(sb + OWN_B1 + (16 * m + g) * 4), a1 = 0.f, b1 = lds_f32(sb + OWN_B1 + (16 * m + g + 8) * 4);
    const float piv = bf_hi(lds32(sb + OFF_STAT + b * 8));
    nbar_sync<NB_AB, 320>();
#pragma unroll
    for (int w = 0; w < 8; w++) {
        const float4 t = lds_f32x4(sb + SC_AB + w * 1024 + m * 512 + lane * 16);
        a0 += t.x; b0 += t.y; a1 += t.z; b1 += t.w;
    }
    sts128(sb + SC_AB + m * 512 + lane * 16, make_uint4(__float_as_uint(a0), __float_as_uint(b0), __float_as_uint(a1), __float_as_uint(b1)));
    nbar_sync<NB_Y, 320>();
    float4 q[4];
    float2 y[8];
#pragma unroll
    for (int i = 0; i < 4; i++) q[i] = lds_f32x4(s_ld + i * 16);
#pragma unroll
    for (int w = 0; w < 8; w++) y[w] = lds_f32x2(y_ld + w * 512);
    const float dm = (((q[0].y + q[0].w) + (q[1].y + q[1].w)) + ((q[2].y + q[2].w) + (q[3].y + q[3].w))) * (1.f / D);
    const float sq = ((q[0].x + q[0].z) + (q[1].x + q[1].z)) + ((q[2].x + q[2].z) + (q[3].x + q[3].z));
    const float r = rsqrt_fast(fmaxf(fmaf(-dm, dm, fmaf(sq, 1.f / D, 1e-5f)), 1e-5f));
    const float y0 = ((y[0].x + y[1].x) + (y[2].x + y[3].x)) + ((y[4].x + y[5].x) + (y[6].x + y[7].x));
    const float y1 = ((y[0].y + y[1].y) + (y[2].y + y[3].y)) + ((y[4].y + y[5].y) + (y[6].y + y[7].y));
    const float dmr = piv - bfr(piv - dm);
    const float u0 = fmaf(r, fmaf(dmr, a0, -y0), b0), u1 = fmaf(r, fmaf(dmr, a1, -y1), b1);
    const float e0 = ex2(u0 * fmaf(u0 * u0, -0.044715f * 2.302208198144325f, -2.302208198144325f));
    const float e1 = ex2(u1 * fmaf(u1 * u1, -0.044715f * 2.302208198144325f, -2.302208198144325f));
    sts16(h_st, pack_bf(u0 * rcp_fast(1.f + e0), 0.f));
    sts16(h_st + 4, pack_bf(u1 * rcp_fast(1.f + e1), 0.f));
#pragma unroll
    for (int w = 0; w < 8; w++) asm volatile("bar.arrive %0, 96;" ::"r"(NB_O + w) : "memory");
}

struct Roles { bool is_f, is_owner; int f, own; };
__device__ __forceinline__ Roles roles(int cta) {
    Roles r;
    r.f = (cta * 27) >> 6;
    r.is_f = (((cta + 1) * 27) >> 6) != r.f;
    r.is_owner = !r.is_f || r.f % 9 == 4;
    r.own = r.is_f ? 74 + r.f / 9 : cta - r.f;
    return r;
}

__global__ void __launch_bounds__(NTHREADS, 1)
fused_kernel(const Params p, const __grid_constant__ CUtensorMap tm_wmod, const __grid_constant__ CUtensorMap tm_wq,
             const __grid_constant__ CUtensorMap tm_wo, const __grid_constant__ CUtensorMap tm_w1, const __grid_constant__ CUtensorMap tm_w2,
             const __grid_constant__ CUtensorMap tm_v, const __grid_constant__ CUtensorMap tm_gb) {
    extern __shared__ __align__(1024) unsigned char smem[];
    const uint32_t t_start = gtime32();
    if (threadIdx.x == 0) {
        const uint32_t c_ = blockIdx.x;
        const uint32_t off = ((c_ & 3) << 26) + (c_ >> 2) * (1u << 21) + (((ROTA * (c_ >> 2) + ROTB) & 31) << 14) + (SK - WIN) * DH * 2;
        asm volatile("cp.async.bulk.prefetch.L2.global.L2::cache_hint [%0], %1, %2;" ::"l"((const char*)p.kc + off), "r"(TILE_BYTES), "l"(0x12f0000000000000ull  ) : "memory");
    }
    const uint32_t sb = smem_u32(smem);
    const int cta = blockIdx.x;
    const int head = cta >> 2, bown = cta & 3;
    const int rot = (ROTA * head + ROTB) & (NITEM / 2 - 1);
    const char* const kb = (const char*)(p.kc + ((size_t)(bown * NH + head) * SK + (SK - WIN)) * DH);
    uint64_t pol = 0;
    if (threadIdx.x == 256) {
        mbar_init(sb + OFF_BAR, 1);
        asm volatile("fence.mbarrier_init.release.cluster;" ::: "memory");
        asm volatile("createpolicy.fractional.L2::evict_first.b64 %0, 1.0;" : "=l"(pol));
        mbar_expect_tx(sb + OFF_BAR, TILE_BYTES);
        bulk_load(sb + OFF_RING, kb + (size_t)rot * TILE_BYTES, TILE_BYTES, sb + OFF_BAR, pol);
        if ((((head + 1) * 5) >> 4) != ((head * 5) >> 4)) {
            const uint32_t bar = sb + OFF_BAR + 2 * NS * 8;
            mbar_init(bar, 1);
            asm volatile("fence.mbarrier_init.release.cluster;" ::: "memory");
            mbar_expect_tx(bar, D * 64);
#pragma unroll 1
            for (int r = 0; r < D; r += 160) tma2d(sb + X_WM + r * 64, &tm_wmod, 32 * (((head * 5) >> 4) * 4 + bown), r, bar);
        }
    }
    const uint32_t bar_full = sb + OFF_BAR, bar_empty = bar_full + NS * 8;
    const uint32_t bar_wm = bar_empty + NS * 8, bar_wq = bar_wm + 8, bar_xfree = bar_wq + 8, bar_wo = bar_xfree + 8  ;
    const uint32_t bar_w1 = bar_wo + 40  , bar_w2 = bar_w1 + 32  , bar_help = bar_w2 + 80, bar_v = bar_help + 8  ;
    const uint32_t bar_gb = bar_v + 32  , bar_x1 = bar_gb + 32;
    const int tid = threadIdx.x, warp = tid >> 5, lane = tid & 31;
    const Roles role = roles(cta);
    const bool is_f = role.is_f, is_owner = role.is_owner;
    const int f = role.f, own = role.own;
    const bool crit = (((head + 1) * 5) >> 4) != ((head * 5) >> 4);
    const int mr = cta - ((head * 5) >> 4) * 4, mq = ((head * 5) >> 4) * 4 + bown;
    const int ml = mr * 31 / 44;
    const bool late = !crit && (mr + 1) * 31 / 44 != ml;
    const int mc = crit ? mq : ml < 60 ? 40 + ml : 58 + ml;
    const bool gb_own = is_owner && own < 72;

    PROF_DECL
    PROF(0);
    uint4 xa = make_uint4(0, 0, 0, 0), xb = xa, ca0 = xa, ca1 = xa, xs[3] = {xa, xa, xa};
    uint32_t own0 = 0;
    __nv_bfloat16 own2 = __float2bfloat16(0.f);
    if (warp < 8) {
        xa = *(const uint4*)(p.x + (tid & 3) * D + (tid >> 2) * 8);
        ca0 = ((const uint4*)p.c)[tid];
        if (tid < 64) { xb = *(const uint4*)(p.x + (tid & 3) * D + (64 + (tid >> 2)) * 8); ca1 = ((const uint4*)p.c)[256 + tid]; }
        if (warp < 4) {
#pragma unroll
            for (int i = 0; i < 3; i++) if (lane + 32 * i < 80) xs[i] = ((const uint4*)p.x)[warp * 80 + lane + 32 * i];
        } else if (warp == 4) {
            if (is_owner) own0 = *(const uint32_t*)((lane < 16 ? p.x + (lane >> 2) * D : p.b2) + 8 * own + 2 * (lane & 3));
            if (is_f) own2 = p.b1[32 * f + lane];
        }
    }
    const char* const vb = (const char*)(p.vc + ((size_t)(bown * NH + head) * SK + (SK - WIN)) * DH);
    const uint32_t bar_first = crit ? bar_wm : bar_wq;
    if (threadIdx.x == 256) {
        if (!crit) {
            mbar_init(bar_wq, 1);
            asm volatile("fence.mbarrier_init.release.cluster;" ::: "memory");
            mbar_expect_tx(bar_wq, D * 64);
            const uint32_t c0 = clock32();
            while (clock32() - c0 < WQ_DELAY) { }
#pragma unroll
            for (int r = 0; r < D; r += 160) tma2d(sb + X_WQ + r * 64, &tm_wq, 32 * cta, r, bar_wq);
        }
    } else if (threadIdx.x == 0) {
#pragma unroll
        for (int s = 0; s < NS; s++) { if (s) mbar_init(bar_full + s * 8, 1); mbar_init(bar_empty + s * 8, 4); }
        mbar_init(crit ? bar_wq : bar_wm, 1);
        mbar_init(bar_xfree, 1);
#pragma unroll
        for (int i = 0; i < 5; i++) { mbar_init(bar_wo + i * 8, 1); mbar_init(bar_w2 + i * 16, 1); mbar_init(bar_w2 + i * 16 + 8, 1); }
        mbar_init(bar_help, 1); mbar_init(bar_x1, 1);
#pragma unroll
        for (int i = 0; i < 4; i++) { mbar_init(bar_v + i * 8, 1); mbar_init(bar_w1 + i * 8, 1); mbar_init(bar_gb + i * 8, 1); }
        asm volatile("fence.mbarrier_init.release.cluster;" ::: "memory");
    }
    __syncthreads();

    if (warp == 8) {
        if (lane == 0) {
            int tp = NS;
            int sched = PACE_A - NS * PACE_TAU;
#pragma unroll 1
            for (int t = 1; t <= NITEM; t++) {
                if (t == 1) mbar_wait(bar_full, 0);
                if (t == 2) {
                    mbar_wait(bar_first, 0);
                    if (crit) {
                        mbar_expect_tx(bar_wq, D * 64);
#pragma unroll 1
                        for (int r = 0; r < D; r += 160) tma2d(sb + X_WQ + r * 64, &tm_wq, 32 * cta, r, bar_wq);
                    }
                }
                if (t == 3) {
                    asm volatile("prefetch.tensormap [%0];" ::"l"(&tm_v) : "memory");
                    asm volatile("prefetch.tensormap [%0];" ::"l"(&tm_wo) : "memory");
                    asm volatile("prefetch.tensormap [%0];" ::"l"(&tm_w1) : "memory");
                    asm volatile("prefetch.tensormap [%0];" ::"l"(&tm_w2) : "memory");
                    asm volatile("prefetch.tensormap [%0];" ::"l"(&tm_gb) : "memory");
                }
                if (t == NS && late) {
                    mbar_wait(bar_full + (NS - INFLIGHT) * 8, 0);
                    mbar_expect_tx(bar_wm, D * 64);
#pragma unroll 1
                    for (int r = 0; r < D; r += 160) tma2d(sb + X_WM + r * 64, &tm_wmod, 32 * mc, r, bar_wm);
                }
                if (t >= NS && t < PF_END) {
                    int it = 0;
                    while (!mbar_test(bar_empty + (t & (NS - 1)) * 8, ((t >> 3) - 1) & 1)) {
                        if (tp < PF_END && (int)(gtime32() - t_start) >= PACE_A + (tp - NS) * PACE_TAU) {
                            asm volatile("cp.async.bulk.prefetch.L2.global.L2::cache_hint [%0], %1, %2;"
                                         ::"l"(((tp & 1) ? vb : kb) + (size_t)(((tp >> 1) + rot) & (NITEM / 2 - 1)) * TILE_BYTES), "r"(TILE_BYTES), "l"(pol) : "memory");
                            tp++;
                        }
                        if (++it > 16 * SPIN_LIMIT) __trap();
                    }
                    if (tp <= t) tp = t + 1;
                }
                if (t == NITEM) {
                    mbar_wait(bar_xfree, 0);
                    const uint32_t t_ref = t_start + sched + LAT_T + (NITEM - 1) * PACE_TAU;
#pragma unroll 1
                    for (int i = 0; i < 5; i++) {
                        while ((int)(gtime32() - t_ref) < WO_T + i * WO_S) { }
                        mbar_expect_tx(bar_wo + i * 8, DH * 64);
                        tma2d(sb + X_WO + i * (DH * 64), &tm_wo, bown * 160 + i * 32, head * DH, bar_wo + i * 8);
                    }
                    if (gb_own) {
                        mbar_wait(bar_empty + 3 * 8, ((NITEM >> 3) - 1) & 1);
                        mbar_wait(bar_x1, 0);
                        { const uint32_t c0 = clock32(); while (clock32() - c0 < GB_EV) { } }
                        while ((int)(gtime32() - t_ref) < GB_T) { }
#pragma unroll 1
                        for (int i = 0; i < 4; i++) {
                            mbar_expect_tx(bar_gb + i * 8, 160 * 16);
                            tma2d(sb + X_GB + i * (160 * 16), &tm_gb, 5 * D + 8 * own, 160 * i, bar_gb + i * 8);
                        }
                    }
                    if (is_f) {
#pragma unroll 1
                        for (int i = 0; i < 3; i++) mbar_wait(bar_empty + i * 8, ((NITEM >> 3) - 1) & 1);
                        while ((int)(gtime32() - t_ref) < W1_T) { }
#pragma unroll 1
                        for (int i = 0; i < 4; i++) {
                            mbar_expect_tx(bar_w1 + i * 8, 160 * 64);
                            tma2d(sb + X_W1 + i * (160 * 64), &tm_w1, 32 * f, 160 * i, bar_w1 + i * 8);
                        }
                        while ((int)(gtime32() - t_ref) < W2_T) { }
#pragma unroll 1
                        for (int i = 0; i < 10; i++) {
                            mbar_expect_tx(bar_w2 + i * 8, 4096);
                            tma2d(sb + X_W2 + i * 4096, &tm_w2, 64 * i, 32 * f, bar_w2 + i * 8);
                        }
                    }
                    break;
                }
                const int s = t & (NS - 1);
                if (t >= NS) {
                    mbar_wait(bar_empty + s * 8, ((t >> 3) - 1) & 1);
                    while ((int)(gtime32() - t_start) < sched + t * PACE_TAU) { }
                } else if (t >= INFLIGHT) {
                    mbar_wait(bar_full + (t - INFLIGHT) * 8, 0);
                }
                if (t < NITEM - 2) {
                    const int pair = t == NITEM - 3 ? NITEM / 2 - 1 : t >> 1;
                    mbar_expect_tx(bar_full + s * 8, TILE_BYTES);
                    bulk_load(sb + OFF_RING + s * TILE_BYTES, ((t & 1) && t != NITEM - 3 ? vb : kb) + (size_t)((pair + rot) & (NITEM / 2 - 1)) * TILE_BYTES, TILE_BYTES, bar_full + s * 8, pol);
                } else {
                    const int row = (bown * NH + head) * SK + (SK - WIN) + ((t - NITEM / 2 + rot) & (NITEM / 2 - 1)) * TILE_KEYS;
#pragma unroll 1
                    for (int i = 0; i < 2; i++) {
                        const uint32_t bar = bar_v + (2 * (t - (NITEM - 2)) + i) * 8;
                        mbar_expect_tx(bar, TILE_BYTES / 2);
                        tma2d_hint(sb + OFF_RING + s * TILE_BYTES + i * (TILE_BYTES / 2), &tm_v, 64 * i, row, bar, pol);
                    }
                }
                if (t >= PH_FIRST + PH_LAG && (t & 3) == (PH_LAG & 3)) {
                    const int now = (int)(gtime32() - t_start) - (t - PH_LAG) * PACE_TAU;
                    uint32_t ph;
                    asm volatile("atom.relaxed.gpu.global.add.u32 %0, [%1], 0;" : "=r"(ph) : "l"(g_phase + ((t - PH_LAG) >> 2) * 32) : "memory");
                    sched = (int)min(((ph & 0xffffffu) * 4 + (NCTA - (ph >> 24)) * now) >> 7, 65535u) - LAT_T;
                }
            }
        }
        __syncwarp();
    }

    if (warp == 9) {
        int side = 0;
        if (lane == 0) {
            uint32_t best[2] = {~0u, ~0u};
#pragma unroll
            for (int i = 0; i < 4; i++) stg_zero4(slot(SL_SIDE, i >> 1) + cta * 8 + (i & 1) * 4);
            uint32_t n = 0;
#pragma unroll 1
            for (int i = 0; (i & 1) || (n < NPROBE - 1 && (int)(gtime32() - t_start) < PROBE_END); i++) {
                uint32_t t0 = clock32(), t1;
                asm volatile("atom.relaxed.gpu.global.inc.u32 %0, [%1], %2;" : "=r"(n) : "l"(slot(SL_SIDE, i & 1) + cta * 8), "r"(0xffffu) : "memory");
                asm volatile("{\n.reg .pred p;\nsetp.ne.u32 p, %1, 0xffffffff;\nmov.u32 %0, 0;\n@p mov.u32 %0, %%clock;\n}" : "=r"(t1) : "r"(n) : "memory");
                if (i & 1) best[1] = min(best[1], t1 - t0); else best[0] = min(best[0], t1 - t0);
            }
            side = best[1] < best[0];
        }
        side = __shfl_sync(0xffffffffu, side, 0);
        HPROF(1);
        mbar_wait(bar_full + (NS - 1) * 8, 0);
        stg_zero4(slot(SL_O + (cta >> 4), lane >> 4) + (cta & 15) * 64 + (lane & 15) * 4);
        if (is_owner) {
#pragma unroll 1
            for (int i = lane; i < NH * 8; i += 32) stg_zero4(slot(SL_P1 + own, side) + i * 4);
#pragma unroll 1
            for (int i = lane; i < NF * 8; i += 32) stg_zero4(slot(SL_P2 + 2 * own + (i >> 8), side) + (i & 255) * 4);
            if (lane < 8) stg_zero4(slot(SL_X1 + own / 30, lane >> 2) + (own % 30) * 32 + (lane & 3) * 4);
        }
        __threadfence();
        __syncwarp();
        if (lane == 0) stg_relaxed(g_clr + cta, 1u + side);
        HPROF(0);
        HPROF(2);
        while ((int)(gtime32() - t_start) < CLR_CHECK) __nanosleep(1000);
        mbar_wait(bar_xfree, 0);
        {
            uint4 v = make_uint4(1, 1, 1, 1), gv = v, mv[20];
#pragma unroll
            for (int i = 0; i < 20; i++) mv[i] = v;
#pragma unroll 1
            for (int it = 0;; it++) {
                v = ldg_relaxed(g_clr + lane * 4);

                ldg_relaxed_if(is_owner && lane < (gb_own ? 4 : 8), gv, mod_slot(lane < 4 ? 2 : 5, own, lane & 3));
#pragma unroll
                for (int i = 0; i < 20; i++) ldg_relaxed_if(is_f, mv[i], mod_slot(3, 8 * i + (lane >> 2), lane & 3));
                bool ok = ready(v) && ready(gv);
#pragma unroll
                for (int i = 0; i < 20; i++) ok = ok && ready(mv[i]);
                if (__all_sync(0xffffffffu, ok)) break;
                if (it > SPIN_LIMIT) __trap();
                __nanosleep(2000);
            }
            const uint32_t w[4] = {v.x, v.y, v.z, v.w};
#pragma unroll
            for (int i = 0; i < 4; i++) {
                const Roles r = roles(4 * lane + i);
                if (r.is_owner) {
                    sts32(sb + OFF_TAB1 + r.own * 4, (uint32_t)(size_t)(slot(SL_P1 + r.own, w[i] - 1) + head * 32));
                    sts32(sb + OFF_TAB2 + r.own * 4, (uint32_t)(size_t)(slot(SL_P2 + 2 * r.own + (f >> 5), w[i] - 1) + (f & 31) * 32));
                }
            }
            if (lane == 0) sts32(sb + OFF_SIDE, side);
            if (lane < 8) sts128(sb + OWN_GA + lane * 16, inv4(gv));
            const uint32_t dst = sb + OFF_VB + (lane & 3) * VEC_STRIDE + (lane >> 2) * 16;
#pragma unroll
            for (int i = 0; i < 10; i++) {
                const uint4 c = inv4(mv[10 + i]);
                sts128(dst + i * 128, make_uint4(bf2_add(c.x, 0x3f803f80u), bf2_add(c.y, 0x3f803f80u), bf2_add(c.z, 0x3f803f80u), bf2_add(c.w, 0x3f803f80u)));
                sts128(dst + (OFF_RED - OFF_VB) + i * 128, inv4(mv[i]));
            }
        }
        asm volatile("fence.acq_rel.gpu;" ::: "memory");
        __syncwarp();
        HPROF(3);
        if (lane == 0) mbar_arrive(bar_help);
        {
            const uint32_t* const src = pin(slot(SL_O + (cta >> 4), side) + (cta & 12) * 64 + lane * 4);
            const uint32_t dst = pin(sb + OFF_O + (lane >> 4) * O_STRIDE + (lane & 15) * 16);
            mbar_wait(bar_v + 16, 0);
            mbar_wait(bar_v + 24, 0);
            uint4 v[2];
            const uint32_t* const ptr[2] = {src, src + 128};
            const bool on[2] = {true, true};
            poll_n<2>(v, ptr, on);
            sts128(dst, v[0]);
            sts128(dst + 2 * O_STRIDE, v[1]);
#pragma unroll
            for (int w = 0; w < 8; w++) asm volatile("bar.arrive %0, 64;" ::"r"(NB_O + w) : "memory");
        }
        HPROF(4);
    }
    if (warp >= 8) {
        if (gb_own && warp == 9) {
            uint32_t a[20][4];
#pragma unroll
            for (int i = 0; i < 20; i++) ldsm4(a[i], sb + OFF_VA + (lane & 3) * VEC_STRIDE + (4 * i + (lane >> 3)) * 16);
            float c[4][4];
#pragma unroll
            for (int i = 0; i < 4; i++) c[i][0] = c[i][1] = c[i][2] = c[i][3] = 0.f;
#pragma unroll
            for (int bx = 0; bx < 4; bx++) {
                mbar_wait(bar_gb + bx * 8, 0);
#pragma unroll
                for (int i = 5 * bx; i < 5 * bx + 5; i++) {
                    uint32_t w[4];
                    ldsm4t(w, sb + X_GB + (32 * i + lane) * 16);
                    const uint32_t a0[4] = {a[i][0], 0u, a[i][1], 0u}, a1[4] = {a[i][2], 0u, a[i][3], 0u};
                    mma16816(c[(2 * i) & 3], a0, w[0], w[1]);
                    mma16816(c[(2 * i + 1) & 3], a1, w[2], w[3]);
                }
            }
            if (lane < 16) sts32(sb + OWN_GB + lane * 4, pack_bf((c[0][0] + c[1][0]) + (c[2][0] + c[3][0]), (c[0][1] + c[1][1]) + (c[2][1] + c[3][1])));
            HPROF(6);
        }
        if (is_owner && warp == 9) nbar_arrive<NB_E6, 288>();
        if (is_f) gelu_stage(sb, warp - 8, lane);
        return;
    }

    const int g = lane >> 2, t4 = lane & 3;
    const int mi = lane >> 3, r8 = lane & 7;

    {
        auto silu4 = [&](const uint4& cv) {
            uint32_t w4[4] = {cv.x, cv.y, cv.z, cv.w};
#pragma unroll
            for (int e = 0; e < 4; e++) {
                float c0 = bf_lo(w4[e]), c1 = bf_hi(w4[e]);
                w4[e] = pack_bf(c0 * rcp_fast(1.f + ex2(-1.4426950408889634f * c0)), c1 * rcp_fast(1.f + ex2(-1.4426950408889634f * c1)));
            }
            return make_uint4(w4[0], w4[1], w4[2], w4[3]);
        };
        {
            uint4 v = silu4(ca0);
            sts128(sb + OFF_VA + (tid / 80) * VEC_STRIDE + (tid % 80) * 16, v);
            if (tid < 64) { v = silu4(ca1); sts128(sb + OFF_VA + 3 * VEC_STRIDE + (16 + tid) * 16, v); }
        }
        if (warp < 4) {
            float s = 0.f, q = 0.f;
            const float pv = __shfl_sync(0xffffffffu, bf_lo(xs[0].x), 0);
#pragma unroll
            for (int i = 0; i < 3; i++) if (i < 2 || lane < 16) acc_stats(xs[i], pv, s, q);
#pragma unroll
            for (int of = 16; of > 0; of >>= 1) { s += __shfl_xor_sync(0xffffffffu, s, of); q += __shfl_xor_sync(0xffffffffu, q, of); }
            uint32_t m2; float rden;
            ln_finish(pv, s, q, m2, rden);
            if (lane == 0) { sts32(sb + OFF_STAT + warp * 8, m2); sts_f32(sb + OFF_STAT + warp * 8 + 4, rden); }
        } else if (warp == 4) {
            sts32(sb + OWN_X + lane * 4, bf2_add(own0, 0u));
            sts_f32(sb + OWN_B1 + lane * 4, bf2f(own2));
        }
    }
    bar_cons();
    PROF(24);
    uint32_t qf[8][2];
    float o[8][4];
#pragma unroll
    for (int c = 0; c < 8; c++) { o[c][0] = o[c][1] = o[c][2] = o[c][3] = 0.f; }
    float m_run = -INFINITY, l_run = 0.f;
    const bool diag = (t4 == (g >> 1));
    const bool odd = g & 1;
    const uint32_t koff = (warp & 3) * 4096 + (r8 + 8 * (mi & 1)) * 256 + (mi >> 1) * 128 + (r8 << 4);
    const uint32_t voff = TILE_BYTES + (warp & 3) * 4096 + (r8 + 8 * (mi >> 1)) * 256 + (mi & 1) * 128 + (r8 << 4);
    const int src0 = (2 * t4) * 4 + t4, src1 = (2 * t4 + 1) * 4 + t4;
#pragma unroll 1
    for (int step = crit ? 0 : 1; step < 3; step++) {
        if (step < 2 || late) {
            if (step == 1) {
                if (!crit) mbar_wait(bar_wq, 0);
                const uint32_t m2 = lds32(sb + OFF_STAT + (tid & 3) * 8);
                const float rden = lds_f32(sb + OFF_STAT + (tid & 3) * 8 + 4);
                uint4 v[4];
                v[2] = v[3] = make_uint4(1, 1, 1, 1);
                const uint32_t* const p0 = mod_slot(0, tid >> 2, tid & 3);
                while ((int)(gtime32() - t_start) < MOD_T) { }
                PROF(2);
#pragma unroll 1
                for (int it = 0;; it++) {
                    ldg_relaxed_if(tid < 64, v[2], p0 + 16 * 64);
                    ldg_relaxed_if(tid < 64, v[3], p0 + 36 * 64);
                    v[0] = ldg_relaxed(p0);
                    v[1] = ldg_relaxed(p0 + 20 * 64);
                    if (__all_sync(0xffffffffu, min(min(min4(v[0]), min4(v[1])), min(min4(v[2]), min4(v[3]))) != 0u)) break;
                    if (it > SPIN_LIMIT) __trap();
                }
#pragma unroll
                for (int i = 0; i < 4; i++) v[i] = inv4(v[i]);
                PROF(3);
                uint4 h0 = ln_mod4(xa, v[1], v[0], m2, rden);
                sts128(sb + OFF_VB + (tid & 3) * VEC_STRIDE + (tid >> 2) * 16, h0);
                if (tid < 64) {
                    h0 = ln_mod4(xb, v[3], v[2], m2, rden);
                    sts128(sb + OFF_VB + (tid & 3) * VEC_STRIDE + (64 + (tid >> 2)) * 16, h0);
                }
            }
            mbar_wait(step == 1 ? bar_wq : bar_wm, 0);
            bar_cons();
            const uint32_t strip = sb + (step == 1 ? X_WQ : X_WM), vec = sb + (step == 1 ? OFF_VB : OFF_VA);
            float acc[2][4];
#pragma unroll
            for (int m = 0; m < 2; m++) { acc[m][0] = acc[m][1] = acc[m][2] = acc[m][3] = 0.f; }
#pragma unroll
            for (int i = 0; i < 5; i++) {
                int k0 = (warp * 5 + i) * 16;
                uint32_t b0, b1;
                load_bfrag(vec, VEC_STRIDE, k0, g, t4, b0, b1);
                int krow = k0 + r8 + 8 * (mi >> 1);
#pragma unroll
                for (int m = 0; m < 2; m++) {
                    uint32_t a[4];
                    int ch = 2 * m + (mi & 1);
                    ldsm4t(a, strip + krow * 64 + ((ch ^ ((krow >> 1) & 3)) << 4));
                    mma16816(acc[m], a, b0, b1);
                }
            }
            if (t4 < 2) {
#pragma unroll
                for (int m = 0; m < 2; m++) {
                    sts_f32x2(sb + OFF_RED + ((warp * 32 + m * 16 + g) * 4 + 2 * t4) * 4, acc[m][0], acc[m][1]);
                    sts_f32x2(sb + OFF_RED + ((warp * 32 + m * 16 + g + 8) * 4 + 2 * t4) * 4, acc[m][2], acc[m][3]);
                }
            }
            bar_cons();
            if (tid < 64) {
                float v0 = 0.f, v1 = 0.f;
#pragma unroll
                for (int w = 0; w < 8; w++) {
                    v0 += lds_f32(sb + OFF_RED + (w * 128 + (tid & 15) * 8 + (tid >> 4)) * 4);
                    v1 += lds_f32(sb + OFF_RED + (w * 128 + (tid & 15) * 8 + 4 + (tid >> 4)) * 4);
                }
                stg_relaxed(step == 1 ? g_q + (((cta & ~3) + (tid >> 4)) * 4 + bown) * 32 + (tid & 15) : g_mod + mc * 64 + tid, ~pack_bf(v0, v1));
            }
        }
        if (step == 0) continue;
        if (step == 1) {
            if (warp == 0) {
                { const uint32_t c0 = clock32(); while (clock32() - c0 < Q_PAUSE) { } }
                uint4 v = poll1(g_q + (cta * 4 + ((lane >> 2) & 3)) * 32 + (lane & 3) * 4, lane < 16);
                if (lane < 16) {
                    sts128(sb + OFF_Q + lane * 16, v);
                    stg_zero4(g_q + (cta * 4 + (lane >> 2)) * 32 + (lane & 3) * 4);
                }
            }
            bar_cons();
            PROF(4);

#pragma unroll
            for (int c = 0; c < 8; c++) {
                qf[c][0] = lds32(sb + OFF_Q + (((c ^ g) * 4 + t4) << 2));
                qf[c][1] = lds32(sb + OFF_Q + 128 + (((c ^ g) * 4 + t4) << 2));
            }
        } else {
            bar_cons();
            if (tid == 0) mbar_arrive(bar_xfree);
        }
#pragma unroll 1
        for (int j = (step == 1 ? 0 : SEG_J) + (warp >> 2); j < (step == 1 ? SEG_J : NITEM / 2 - 2); j += 2) {
            const int s = (2 * j) & (NS - 1);
            const uint32_t par = (j >> 2) & 1;
            mbar_wait(bar_full + s * 8, par);
            if (tid == 0 && 2 * j >= PH_FIRST) {
                const int x = min(max((int)(gtime32() - t_start) - 2 * j * PACE_TAU, 0), 65535);
                asm volatile("red.relaxed.gpu.global.add.u32 [%0], %1;" ::"l"(g_phase + (j >> 1) * 32), "r"((1u << 24) + (x >> 2)) : "memory");
            }
            const uint32_t base = sb + OFF_RING + s * TILE_BYTES;
            float sa[4] = {0.f, 0.f, 0.f, 0.f}, sb2[4] = {0.f, 0.f, 0.f, 0.f};
#pragma unroll
            for (int c = 0; c < 8; c += 2) {
                uint32_t a[4], a2[4];
                ldsm4(a, (base + koff) ^ (c << 4));
                ldsm4(a2, (base + koff) ^ ((c + 1) << 4));
                mma16816(sa, a, qf[c][0], qf[c][1]);
                mma16816(sb2, a2, qf[c + 1][0], qf[c + 1][1]);
            }
            const uint32_t sw = pack_bf(odd ? sa[1] + sb2[1] : sa[0] + sb2[0], odd ? sa[3] + sb2[3] : sa[2] + sb2[2]);
            const uint32_t sv = pack_bf(bf_lo(sw) * 0.08838834764831845f, bf_hi(sw) * 0.08838834764831845f);
            const float s0 = bf_lo(sv) * 1.4426950408889634f, s1 = bf_hi(sv) * 1.4426950408889634f;
            float m_new = fmaxf(m_run, fmaxf(s0, s1));
            const bool grow = __any_sync(0xffffffffu, (diag && (m_new > m_run)));
            if (lane == 0) mbar_arrive(bar_empty + s * 8);
            if (grow) {
                float al = ex2(m_run - m_new);
                float a0 = __shfl_sync(0xffffffffu, al, src0), a1 = __shfl_sync(0xffffffffu, al, src1);
#pragma unroll
                for (int c = 0; c < 8; c++) { o[c][0] *= a0; o[c][1] *= a1; o[c][2] *= a0; o[c][3] *= a1; }
                l_run *= al;
                m_run = m_new;
            }
            uint32_t pw = pack_bf(ex2(s0 - m_run), ex2(s1 - m_run));
            l_run += bf_lo(pw) + bf_hi(pw);
            uint32_t b0 = odd ? (pw << 16) : (pw & 0xffffu);
            uint32_t b1 = odd ? (pw & 0xffff0000u) : (pw >> 16);
            if (!diag) { b0 = 0u; b1 = 0u; }
            mbar_wait(bar_full + (s + 1) * 8, par);
#pragma unroll
            for (int c = 0; c < 8; c++) {
                uint32_t a[4];
                ldsm4t(a, (base + voff) ^ (c << 4));
                mma16816(o[c], a, b0, b1);
            }
            __syncwarp();
            if (lane == 0) mbar_arrive(bar_empty + (s + 1) * 8);
        }
    }
    PROF(5);
    float acc[4][4];
    uint32_t pa[8][2];
    float rinv;
    {
        const int s = 4 + (warp >> 2);
        mbar_wait(bar_full + s * 8, 1);
        const uint32_t base = sb + OFF_RING + s * TILE_BYTES;
        float sa[4] = {0.f, 0.f, 0.f, 0.f}, sb2[4] = {0.f, 0.f, 0.f, 0.f};
#pragma unroll
        for (int c = 0; c < 8; c += 2) {
            uint32_t a[4], a2[4];
            ldsm4(a, (base + koff) ^ (c << 4));
            ldsm4(a2, (base + koff) ^ ((c + 1) << 4));
            mma16816(sa, a, qf[c][0], qf[c][1]);
            mma16816(sb2, a2, qf[c + 1][0], qf[c + 1][1]);
        }
        const uint32_t sw = pack_bf(odd ? sa[1] + sb2[1] : sa[0] + sb2[0], odd ? sa[3] + sb2[3] : sa[2] + sb2[2]);
        const uint32_t sv = pack_bf(bf_lo(sw) * 0.08838834764831845f, bf_hi(sw) * 0.08838834764831845f);
        const float s0 = bf_lo(sv) * 1.4426950408889634f, s1 = bf_hi(sv) * 1.4426950408889634f;
        int mi_ = __float_as_int(diag ? fmaxf(m_run, fmaxf(s0, s1)) : -INFINITY);
        mi_ ^= (mi_ >> 31) & 0x7fffffff;
        mi_ = __reduce_max_sync(0xffffffffu, mi_);
        mi_ ^= (mi_ >> 31) & 0x7fffffff;
        if (lane == 0) sts32(sb + OFF_ML + warp * 4, mi_);
        bar_cons();
        const float4 m0 = lds_f32x4(sb + OFF_ML), m1 = lds_f32x4(sb + OFF_ML + 16);
        const float mx = fmaxf(fmaxf(fmaxf(m0.x, m0.y), fmaxf(m0.z, m0.w)), fmaxf(fmaxf(m1.x, m1.y), fmaxf(m1.z, m1.w)));
        const float scl = ex2(m_run - mx);
        const uint32_t pw = pack_bf(ex2(s0 - mx), ex2(s1 - mx));
        if (diag) { sts16(sb + SC_P + (warp * 16 + g) * 2, pw); sts16(sb + SC_P + (warp * 16 + g + 8) * 2, pw >> 16); }
        const float lw = warp_sum(diag ? fmaf(l_run, scl, bf_lo(pw) + bf_hi(pw)) : 0.f);
        const float a0 = __shfl_sync(0xffffffffu, scl, src0), a1 = __shfl_sync(0xffffffffu, scl, src1);
        float v[8], u[8];
#pragma unroll
        for (int c = 0; c < 8; c++) {
            v[c] = a0 * o[c][0] + a1 * o[c ^ 1][1];
            u[c] = a0 * o[c][2] + a1 * o[c ^ 1][3];
        }
#pragma unroll
        for (int c = 0; c < 8; c++) {
            if (!(c & 2)) {
                v[c] += __shfl_xor_sync(0xffffffffu, v[c ^ 2], 1);
                u[c] += __shfl_xor_sync(0xffffffffu, u[c ^ 2], 1);
            }
        }
#pragma unroll
        for (int c = 0; c < 2; c++) {
            v[c] += __shfl_xor_sync(0xffffffffu, v[c ^ 4], 2);
            u[c] += __shfl_xor_sync(0xffffffffu, u[c ^ 4], 2);
        }
        const uint32_t dst = sb + SC_OP + (warp * 128 + 16 * t4 + g) * 4;
        sts_f32(dst, v[0]); sts_f32(dst + 32, v[1]); sts_f32(dst + 256, u[0]); sts_f32(dst + 288, u[1]);
        if (lane == 0) sts_f32(sb + OFF_ML + 32 + warp * 4, lw);
        mbar_wait(bar_help, 0);
        bar_cons();
        const float4 l0 = lds_f32x4(sb + OFF_ML + 32), l1 = lds_f32x4(sb + OFF_ML + 48);
        rinv = rcp_fast(((l0.x + l0.y) + (l0.z + l0.w)) + ((l1.x + l1.y) + (l1.z + l1.w)));
#pragma unroll
        for (int i = 0; i < 4; i++) acc[i][0] = acc[i][1] = acc[i][2] = acc[i][3] = 0.f;
#pragma unroll
        for (int w = 0; w < 8; w++) {
            const float2 x0 = lds_f32x2(sb + SC_OP + (w * 128 + 16 * warp + 2 * t4) * 4), x1 = lds_f32x2(sb + SC_OP + (w * 128 + 16 * warp + 8 + 2 * t4) * 4);
            acc[2 * (w & 1)][0] += x0.x; acc[2 * (w & 1)][1] += x0.y;
            acc[2 * (w & 1) + 1][0] += x1.x; acc[2 * (w & 1) + 1][1] += x1.y;
        }
#pragma unroll
        for (int ks = 0; ks < 8; ks++) { pa[ks][0] = lds32(sb + SC_P + (8 * ks + t4) * 4); pa[ks][1] = lds32(sb + SC_P + (8 * ks + 4 + t4) * 4); }
    }
    PROF(20);
    const int mt = warp < 2 ? warp : warp + 2;
    {
        const uint32_t va = pin(sb + OFF_RING + 6 * TILE_BYTES + (warp >> 2) * (TILE_BYTES / 2) + (8 * (mi & 1) + r8) * 128 + (((2 * (warp & 3) + (mi >> 1)) ^ r8) << 4));
        const uint32_t vbar = pin(bar_v + (warp >> 2) * 8);
        uint32_t* const o_dst = pin(slot(SL_O + (cta >> 4), g) + (cta & 15) * 64 + warp * 8 + 2 * t4);
#pragma unroll
        for (int tl = 0; tl < 2; tl++) {
            mbar_wait(vbar + tl * 16, 0);
            uint32_t r[4][4];
#pragma unroll
            for (int ks = 0; ks < 4; ks++) ldsm4t(r[ks], va + tl * TILE_BYTES + ks * 2048);
#pragma unroll
            for (int ks = 0; ks < 4; ks++) {
                const uint32_t a[4] = {pa[4 * tl + ks][0], 0u, pa[4 * tl + ks][1], 0u};
                mma16816(acc[2 * (ks & 1)], a, r[ks][0], r[ks][1]);
                mma16816(acc[2 * (ks & 1) + 1], a, r[ks][2], r[ks][3]);
            }
        }
        stg_relaxed2_if(g < 2, o_dst, ~pack_bf((acc[0][0] + acc[2][0]) * rinv, (acc[0][1] + acc[2][1]) * rinv),
                        ~pack_bf((acc[1][0] + acc[3][0]) * rinv, (acc[1][1] + acc[3][1]) * rinv));
    }
    PROF(7);
    const int side = lds32(sb + OFF_SIDE);
    const uint32_t red_st = pin(sb + SC_E4 + ((warp * 4 + 2 * ((lane >> 3) & 1) + (lane >> 4)) * 8 + (lane & 7)) * 4);
    const uint32_t red_ld = pin(sb + SC_E4 + (lane & 15) * 8);
    const uint32_t* const in1 = pin(slot(SL_P1 + own, side) + tid * 4);
    const uint32_t* const in2a = pin(slot(SL_P2 + 2 * own, side) + tid * 4);
    const uint32_t* const in2b = pin(slot(SL_P2 + 2 * own + 1, side) + tid * 4);
    uint32_t* const out_dst = pin((uint32_t*)(p.out + ((lane >> 2) & 3) * D + 8 * own) + t4);
    uint32_t* const x1_dst = pin(slot(SL_X1 + own / 30, lane >> 4) + (own % 30) * 32 + (lane & 15));
    uint32_t* const rst = pin(tid >= 32 && tid < 56 ? mod_slot(lane >> 2, own, lane & 3) : own < 32 && tid == 64 ? g_clr + own * 4 : own < 16 && tid == 96 ? g_phase + own * 32 : nullptr);
    const uint32_t xw = lds32(sb + OWN_X + (lane & 15) * 4), ga_w = lds32(sb + OWN_GA + (lane & 15) * 4);
    uint32_t cs[15];
    uint32_t* dst2[5];
    uint32_t w2a[5];
#pragma unroll
    for (int j = 0; j < 10; j++) cs[j] = lds32(sb + OFF_VB + ((g & 1) * 4 + (g >> 1)) * VEC_STRIDE + warp * 160 + t4 * 4 + j * 16);
#pragma unroll
    for (int i = 0; i < 5; i++) {
        cs[10 + i] = lds32(sb + OFF_VB + (g >> 1) * VEC_STRIDE + warp * 160 + (g & 1) * 16 + t4 * 4 + i * 32);
        const uint2 t = lds64(sb + OFF_TAB2 + warp * 40 + i * 8);
        dst2[i] = slot_ptr((t4 < 2 ? t.x : t.y) + g * 16 + (t4 & 1) * 8);
        const int cc = 2 * (warp * 5 + i) + (mi & 1);
        w2a[i] = pin(sb + X_W2 + (cc >> 3) * 4096 + (r8 + 8 * (mi >> 1)) * 128 + (((cc & 7) ^ r8) << 4));
    }
    const uint32_t piv = lds32(sb + OFF_STAT + (g >> 1) * 8);
    const uint32_t* const xin = pin(slot(SL_X1 + warp / 3, side) + ((warp % 3) * 10 + (g & 1)) * 32 + (g >> 1) * 4 + t4);
    const uint32_t w1a = pin(sb + X_W1 + (warp * 80 + r8 + 8 * (mi >> 1)) * 64 + (((mi & 1) ^ ((r8 >> 1) & 3)) << 4));
    const uint32_t w1bar = pin(bar_w1 + (warp >> 1) * 8), w2bar = pin(bar_w2 + (warp + (warp >> 2)) * 8);
    const uint32_t wbar = pin(NB_O + warp);
    const uint32_t ab_st = pin(sb + SC_AB + warp * 1024 + lane * 16), y_st = pin(sb + SC_Y + warp * 512 + lane * 8), s_st = pin(sb + SC_ST + (t4 * 8 + warp) * 8);
    const uint32_t h_ld = pin(sb + SC_H1 + ((g & 3) ^ (2 * (f & 1) + ((f >> 1) & 1))) * 64 + t4 * 16);
    {
        const int kap = 2 * (head & 1) + ((head >> 1) & 1);
        const uint32_t wa = pin(sb + X_WO + (mt >> 1) * (DH * 64) + (r8 + 8 * (mi >> 1)) * 64 + ((((mt & 1) * 2 + (mi & 1)) ^ ((r8 >> 1) & 3)) << 4));
        const uint32_t oa = pin(sb + OFF_O + ((g & 3) ^ kap) * O_STRIDE + t4 * 8);
        uint32_t* dst[4];
#pragma unroll
        for (int i = 0; i < 2; i++) {
            const uint2 t = lds64(sb + OFF_TAB1 + (bown * 20 + 2 * mt + (warp < 2 ? 4 * i : 0)) * 4);
            dst[2 * i] = slot_ptr(t.x + g * 16 + t4 * 8);
            dst[2 * i + 1] = slot_ptr(t.y + g * 16 + t4 * 8);
        }
        PROF(6);
        const uint32_t wobar = pin(bar_wo + (mt >> 1) * 8);
        asm volatile("bar.sync %0, 64;" ::"r"(wbar) : "memory");
        uint2 ob[8];
#pragma unroll
        for (int ks = 0; ks < 8; ks++) ob[ks] = lds64(oa + ks * 32);
#pragma unroll
        for (int m = 0; m < 2; m++) {
            if (m == 0 || warp < 2) {
                mbar_wait(wobar + m * 8, 0);
                PROF(8);
                uint32_t wf[8][4];
#pragma unroll
                for (int ks = 0; ks < 8; ks++) ldsm4t(wf[ks], wa + m * (DH * 64) + ks * 1024);
                float c[4][4];
#pragma unroll
                for (int ks = 0; ks < 8; ks++) {
                    if (ks < 4) c[ks][0] = c[ks][1] = c[ks][2] = c[ks][3] = 0.f;
                    mma16816(c[ks & 3], wf[ks], ob[ks].x, ob[ks].y);
                }
                stg_relaxed2_if(t4 < 2, dst[2 * m], flag((c[0][0] + c[1][0]) + (c[2][0] + c[3][0])), flag((c[0][1] + c[1][1]) + (c[2][1] + c[3][1])));
                stg_relaxed2_if(t4 < 2, dst[2 * m + 1], flag((c[0][2] + c[1][2]) + (c[2][2] + c[3][2])), flag((c[0][3] + c[1][3]) + (c[2][3] + c[3][3])));
            }
        }
    }
    PROF(9);
    uint32_t x1w = 0;
    if (is_owner) {
        uint4 v;
        for (int it = 0;; it++) {
            v = ldg_relaxed(in1);
            if (__all_sync(0xffffffffu, and3(and3(v.x, v.y, v.z), v.w, 1u))) break;
            if (it > SPIN_LIMIT) __trap();
        }
        PROF(11);
        const float s0 = __uint_as_float(v.x) + __shfl_xor_sync(0xffffffffu, __uint_as_float(v.z), 8);
        const float s1 = __uint_as_float(v.y) + __shfl_xor_sync(0xffffffffu, __uint_as_float(v.w), 8);
        sts_f32(red_st, s0 + __shfl_xor_sync(0xffffffffu, s1, 16));
        nbar_sync<NB_E4, 256>();
        if (warp == 0) {
            float2 a[8];
#pragma unroll
            for (int w = 0; w < 8; w++) a[w] = lds_f32x2(red_ld + w * 128);
            const uint32_t aw = pack_bf(((a[0].x + a[1].x) + (a[2].x + a[3].x)) + ((a[4].x + a[5].x) + (a[6].x + a[7].x)),
                                        ((a[0].y + a[1].y) + (a[2].y + a[3].y)) + ((a[4].y + a[5].y) + (a[6].y + a[7].y)));
            x1w = bf2_add(xw, bf2_mul(ga_w, aw));
            stg_relaxed(x1_dst, x1w ^ 0x80008000u);
            if (lane == 0) mbar_arrive(bar_x1);
        }
        if (rst) stg_zero4(rst);
    }
    PROF(12);
    if (is_f) {
        uint32_t f1[5][2][4], f2[5][2][4];
        uint32_t d[6];
        auto load_x1 = [&] {
#pragma unroll
            for (int i = 0; i < 5; i++) d[i] = ldg_relaxed32(xin + i * 64);
        };
        auto have_x1 = [&] { return __all_sync(0xffffffffu, __vimin3_u32(__vimin3_u32(d[0], d[1], d[2]), d[3], d[4]) != 0u); };
        mbar_wait(w1bar, 0);
        load_x1();
        {
#pragma unroll
            for (int i = 0; i < 5; i++) { ldsm4t(f1[i][0], w1a + i * 1024); ldsm4t(f1[i][1], (w1a ^ 32) + i * 1024); }
            float c[2][4];
#pragma unroll
            for (int m = 0; m < 2; m++) c[m][0] = c[m][1] = c[m][2] = c[m][3] = 0.f;
#pragma unroll
            for (int i = 0; i < 5; i++) { mma16816(c[0], f1[i][0], cs[2 * i], cs[2 * i + 1]); mma16816(c[1], f1[i][1], cs[2 * i], cs[2 * i + 1]); }
#pragma unroll
            for (int i = 0; i < 5; i++) { cs[2 * i] = pin(odd ? 0u : cs[10 + i]); cs[2 * i + 1] = pin(odd ? cs[10 + i] : 0u); }
#pragma unroll
            for (int m = 0; m < 2; m++) sts128(ab_st + m * 512, make_uint4(__float_as_uint(c[m][0]), __float_as_uint(c[m][1]), __float_as_uint(c[m][2]), __float_as_uint(c[m][3])));
            nbar_arrive<NB_AB, 320>();
            d[0] |= __float_as_uint(c[1][3]) & (side >> 1);
        }
        PROF(10);
#pragma unroll 1
        for (int it = 0; !have_x1(); it++) {
            load_x1();
            if (it > SPIN_LIMIT) __trap();
        }
        PROF(13);
        {
            float y[2][4], st[4] = {0.f, 0.f, 0.f, 0.f};
#pragma unroll
            for (int m = 0; m < 2; m++) y[m][0] = y[m][1] = y[m][2] = y[m][3] = 0.f;
#pragma unroll
            for (int i = 0; i < 5; i++) d[i] = bf2_add(d[i], piv);
            d[5] = 0u;
#pragma unroll
            for (int i = 0; i < 5; i++) {
                if (i < 3) {
                    const uint32_t a[4] = {d[2 * i], 0x3f803f80u, d[2 * i + 1], 0x3f803f80u};
                    mma16816(st, a, d[2 * i], d[2 * i + 1]);
                }
                const uint32_t y0 = bf2_mul(d[i], cs[2 * i]), y1 = bf2_mul(d[i], cs[2 * i + 1]);
                mma16816(y[0], f1[i][0], y0, y1);
                mma16816(y[1], f1[i][1], y0, y1);
            }
            const float q = odd ? st[1] : st[0];
            const float q2 = q + __shfl_xor_sync(0xffffffffu, q, 4);
            if (diag && !odd) sts_f32x2(s_st, q2, st[2] + st[3]);
#pragma unroll
            for (int m = 0; m < 2; m++) sts_f32x2(y_st + m * 256, y[m][0] + y[m][1], y[m][2] + y[m][3]);
        }
        nbar_arrive<NB_Y, 320>();
        PROF(14);
        mbar_wait(w2bar, 0);
        mbar_wait(w2bar + 8, 0);
#pragma unroll
        for (int i = 0; i < 5; i++) { ldsm4t(f2[i][0], w2a[i]); ldsm4t(f2[i][1], w2a[i] + 2048); }
        asm volatile("bar.sync %0, 96;" ::"r"(wbar) : "memory");
        PROF(15);
        {
            const uint4 hb = lds128(h_ld);
            float c[5][4];
#pragma unroll
            for (int i = 0; i < 5; i++) { c[i][0] = c[i][1] = c[i][2] = c[i][3] = 0.f; mma16816(c[i], f2[i][0], hb.x, hb.y); }
#pragma unroll
            for (int i = 0; i < 5; i++) {
                mma16816(c[i], f2[i][1], hb.z, hb.w);
                stg_relaxed2_if(true, dst2[i], flag(t4 < 2 ? c[i][0] : c[i][2]), flag(t4 < 2 ? c[i][1] : c[i][3]));
            }
        }
    }
    PROF(16);
    if (is_owner) {
        const uint32_t b2w = lds32(sb + OWN_B2 + (lane & 15) * 4), gb_ld = pin(sb + OWN_GB + (lane & 15) * 4);
        const bool two = tid < NF * 8 - 256;
        uint4 v, w = make_uint4(1, 1, 1, 1);
        for (int it = 0;; it++) {
            ldg_relaxed_if(two, w, in2b);
            v = ldg_relaxed(in2a);
            if (__all_sync(0xffffffffu, and3(and3(v.x, v.y, v.z), and3(v.w, w.x, w.y), and3(w.z, w.w, 1u)))) break;
            if (it > SPIN_LIMIT) __trap();
        }
        PROF(17);
        const float s0 = (__uint_as_float(v.x) + __uint_as_float(w.x)) + __shfl_xor_sync(0xffffffffu, __uint_as_float(v.z) + __uint_as_float(w.z), 8);
        const float s1 = (__uint_as_float(v.y) + __uint_as_float(w.y)) + __shfl_xor_sync(0xffffffffu, __uint_as_float(v.w) + __uint_as_float(w.w), 8);
        sts_f32(red_st + (SC_E6 - SC_E4), s0 + __shfl_xor_sync(0xffffffffu, s1, 16));
        if (warp != 0) {
            nbar_arrive<NB_E6, 288>();
        } else {
            nbar_sync<NB_E6, 288>();
            float2 a[8];
#pragma unroll
            for (int i = 0; i < 8; i++) a[i] = lds_f32x2(red_ld + (SC_E6 - SC_E4) + i * 128);
            const uint32_t gb_w = lds32(gb_ld);
            const uint32_t aw = pack_bf(((a[0].x + a[1].x) + (a[2].x + a[3].x)) + ((a[4].x + a[5].x) + (a[6].x + a[7].x)),
                                        ((a[0].y + a[1].y) + (a[2].y + a[3].y)) + ((a[4].y + a[5].y) + (a[6].y + a[7].y)));
            x1w = bf2_add(x1w, bf2_mul(gb_w, bf2_add(aw, b2w)));
            if (lane < 16) asm volatile("st.global.u32 [%0], %1;" ::"l"(out_dst), "r"(x1w) : "memory");
        }
    }
    PROF(18);
    PROF_DUMP;
}

typedef CUresult (*EncodeFn)(CUtensorMap*, CUtensorMapDataType, cuuint32_t, void*, const cuuint64_t*, const cuuint64_t*, const cuuint32_t*,
                             const cuuint32_t*, CUtensorMapInterleave, CUtensorMapSwizzle, CUtensorMapL2promotion, CUtensorMapFloatOOBfill);

static CUtensorMap make_map(EncodeFn enc, const void* ptr, int cols, int rows, int box_cols, int box_rows, CUtensorMapSwizzle sw,
                            CUtensorMapL2promotion promo = CU_TENSOR_MAP_L2_PROMOTION_NONE) {
    CUtensorMap m;
    cuuint64_t dims[2] = {(cuuint64_t)cols, (cuuint64_t)rows};
    cuuint64_t strides[1] = {(cuuint64_t)cols * 2};
    cuuint32_t box[2] = {(cuuint32_t)box_cols, (cuuint32_t)box_rows};
    cuuint32_t es[2] = {1, 1};
    enc(&m, CU_TENSOR_MAP_DATA_TYPE_BFLOAT16, 2, const_cast<void*>(ptr), dims, strides, box, es, CU_TENSOR_MAP_INTERLEAVE_NONE, sw,
        promo, CU_TENSOR_MAP_FLOAT_OOB_FILL_NONE);
    return m;
}

}

extern "C" void kernel_launch(void* const* d_in, const int* in_sizes, int n_in, void* d_out, int out_size) {
    (void)in_sizes; (void)n_in; (void)out_size;
    static EncodeFn enc = nullptr;
    if (!enc) {
        void* fn = nullptr;
        cudaDriverEntryPointQueryResult qr;
        cudaGetDriverEntryPoint("cuTensorMapEncodeTiled", &fn, cudaEnableDefault, &qr);
        enc = (EncodeFn)fn;
        cudaFuncSetAttribute(fused_kernel, cudaFuncAttributeMaxDynamicSharedMemorySize, SMEM_BYTES);
    }
    Params p;
    p.x = (const __nv_bfloat16*)d_in[0];
    p.kc = (const __nv_bfloat16*)d_in[1];
    p.vc = (const __nv_bfloat16*)d_in[2];
    p.b1 = (const __nv_bfloat16*)d_in[7];
    p.b2 = (const __nv_bfloat16*)d_in[9];
    p.c = (const __nv_bfloat16*)d_in[10];
    p.out = (__nv_bfloat16*)d_out;
    CUtensorMap tm_wmod = make_map(enc, d_in[11], NMOD, D, 32, 160, CU_TENSOR_MAP_SWIZZLE_64B, CU_TENSOR_MAP_L2_PROMOTION_L2_128B);
    CUtensorMap tm_wq = make_map(enc, d_in[3], NH * DH, D, 32, 160, CU_TENSOR_MAP_SWIZZLE_64B, CU_TENSOR_MAP_L2_PROMOTION_L2_128B);
    CUtensorMap tm_wo = make_map(enc, d_in[4], D, NH * DH, 32, 128, CU_TENSOR_MAP_SWIZZLE_64B);
    CUtensorMap tm_w1 = make_map(enc, d_in[6], FF, D, 32, 160, CU_TENSOR_MAP_SWIZZLE_64B);
    CUtensorMap tm_w2 = make_map(enc, d_in[8], D, FF, 64, 32, CU_TENSOR_MAP_SWIZZLE_128B);
    CUtensorMap tm_v = make_map(enc, d_in[2], DH, NB * NH * SK, 64, TILE_KEYS, CU_TENSOR_MAP_SWIZZLE_128B);
    CUtensorMap tm_gb = make_map(enc, d_in[11], NMOD, D, 8, 160, CU_TENSOR_MAP_SWIZZLE_NONE, CU_TENSOR_MAP_L2_PROMOTION_L2_128B);
    fused_kernel<<<NCTA, NTHREADS, SMEM_BYTES>>>(p, tm_wmod, tm_wq, tm_wo, tm_w1, tm_w2, tm_v, tm_gb);
}
```

```cpp
#include <cuda_runtime.h>
#include <cuda.h>
#include <cuda_bf16.h>
#include <stdint.h>

namespace {

constexpr int NB = 4, D = 640, NH = 32, DH = 128, SK = 8192, WIN = 2048, FF = 1728, NMOD = 6 * D;
constexpr int NCTA = 128;
constexpr int NOWN = 80;
constexpr int NF = 54;
constexpr int NTHREADS = 320;
constexpr int TILE_KEYS = 64;
constexpr int TILE_BYTES = TILE_KEYS * DH * 2;
constexpr int NITEM = 2 * WIN / TILE_KEYS;
constexpr int NS = 8;
constexpr int NMODC = 120;
constexpr int SPIN_LIMIT = 1 << 18;
#define INFLIGHT 3
#define WQ_DELAY 500
#define MOD_T 4200
#define Q_PAUSE 1100
#define PACE_A 7500
#define PACE_TAU 635
#define ROTA 8
#define ROTB 0
#define PF_END 16
#define PH_FIRST 20
#define PH_LAG 5
#define LAT_T 2400
#define WO_T -950
#define WO_S 250
#define W1_T 950
#define W2_T 1650
#define GB_T 2500
#define GB_EV 300
#define CLR_CHECK 28000
constexpr int NPROBE = 8, PROBE_END = 10000;
constexpr int SEG_J = 8;

constexpr int OFF_RING = 0;
constexpr int OFF_X = OFF_RING + NS * TILE_BYTES;
constexpr int X_WM = OFF_X;
constexpr int X_WQ = OFF_X + D * 64;
constexpr int X_WO = OFF_X;
constexpr int X_W1 = X_WO + 5 * DH * 64;
constexpr int X_END = X_W1 + D * 64;
constexpr int X_W2 = OFF_RING;
constexpr int X_GB = OFF_RING + 3 * TILE_BYTES;
static_assert(X_WQ + D * 64 <= X_END, "prologue weights must fit");
constexpr int VEC_STRIDE = 1296;
constexpr int OFF_VA = X_END;
constexpr int OFF_VB = OFF_VA + 4 * VEC_STRIDE;
constexpr int OFF_RED = OFF_VB + 4 * VEC_STRIDE;
constexpr int OFF_ML = OFF_RED + 4 * VEC_STRIDE;
constexpr int O_STRIDE = 288;
constexpr int OFF_O = OFF_ML + 64;
constexpr int OFF_Q = OFF_O + 4 * O_STRIDE;
constexpr int OFF_OWN = OFF_Q + 256;
constexpr int OWN_X = OFF_OWN, OWN_B2 = OWN_X + 64, OWN_GA = OWN_B2 + 64, OWN_GB = OWN_GA + 64, OWN_B1 = OWN_GB + 64;
constexpr int OFF_STAT = OWN_B1 + 128;
constexpr int OFF_TAB1 = OFF_STAT + 32;
constexpr int OFF_TAB2 = OFF_TAB1 + NOWN * 4;
constexpr int OFF_SIDE = OFF_TAB2 + NOWN * 4;
constexpr int OFF_BAR = OFF_SIDE + 8;
constexpr int NBAR = 2 * NS + 32;
constexpr int SMEM_BYTES = OFF_BAR + NBAR * 8;
constexpr int SC_OP = OFF_RING + 4 * TILE_BYTES;
constexpr int SC_AB = SC_OP + 4096;
constexpr int SC_Y = SC_AB + 8192;
constexpr int SC_ST = SC_Y + 4096;
constexpr int SC_E4 = SC_ST + 256;
constexpr int SC_E6 = SC_E4 + 1024;
constexpr int SC_P = SC_E6 + 1024;
constexpr int SC_H1 = SC_P + 256;
static_assert(SMEM_BYTES <= 232448, "smem");
static_assert(OFF_BAR % 8 == 0 && OFF_X % 1024 == 0 && X_WQ % 512 == 0 && X_W1 % 512 == 0 && OFF_VA % 16 == 0 && OFF_RED % 16 == 0 && OFF_ML % 16 == 0 && OFF_O % 16 == 0 && OFF_Q % 16 == 0, "align");
constexpr int NB_O = 2  , NB_E4 = 10, NB_E6 = 11, NB_AB = 12, NB_Y = 13;

__device__ __align__(128) uint32_t g_mod[NMODC * 64];
__device__ __align__(128) uint32_t g_q[NCTA * 128];
__device__ uint32_t g_clr[NCTA];
__device__ uint32_t g_phase[16 * 32];
constexpr int SL_P1 = 0;
constexpr int SL_P2 = SL_P1 + NOWN;
constexpr int SL_O = SL_P2 + 2 * NOWN;
constexpr int SL_X1 = SL_O + 8;
constexpr int SL_SIDE = SL_X1 + 3;
static_assert(SL_SIDE < 256, "one 2 MB page");
__device__ uint32_t g_slots[2 * 256 * 2048];
__device__ __forceinline__ uint32_t* slot(int i, int side) {
    const size_t base = ((size_t)g_slots + 0x1fffff) & ~(size_t)0x1fffff;
    return (uint32_t*)base + i * 2048 + (((__popc(i & 0x59) ^ side) & 1) << 10);
}
#define PROF_DECL
#define HPROF(i) do { } while (0)
#define PROF(i) do { } while (0)
#define PROF_DUMP do { } while (0)

__device__ __forceinline__ uint32_t smem_u32(const void* p) { return (uint32_t)__cvta_generic_to_shared(p); }
__device__ __forceinline__ void mbar_init(uint32_t bar, uint32_t cnt) { asm volatile("mbarrier.init.shared::cta.b64 [%0], %1;" ::"r"(bar), "r"(cnt) : "memory"); }
__device__ __forceinline__ void mbar_expect_tx(uint32_t bar, uint32_t bytes) { asm volatile("mbarrier.arrive.expect_tx.shared::cta.b64 _, [%0], %1;" ::"r"(bar), "r"(bytes) : "memory"); }
__device__ __forceinline__ void mbar_arrive(uint32_t bar) { asm volatile("mbarrier.arrive.shared::cta.b64 _, [%0];" ::"r"(bar) : "memory"); }
__device__ __forceinline__ void mbar_wait(uint32_t bar, uint32_t parity) {
    uint32_t ok;
    int it = 0;
    while (true) {
        asm volatile("{\n.reg .pred p;\nmbarrier.try_wait.parity.shared::cta.b64 p, [%1], %2;\nselp.u32 %0, 1, 0, p;\n}" : "=r"(ok) : "r"(bar), "r"(parity) : "memory");
        if (ok) break;
        if (++it > SPIN_LIMIT) __trap();
    }
}
__device__ __forceinline__ void bulk_load(uint32_t dst, const void* src, uint32_t bytes, uint32_t bar, uint64_t pol) {
    asm volatile("cp.async.bulk.shared::cluster.global.mbarrier::complete_tx::bytes.L2::cache_hint [%0], [%1], %2, [%3], %4;"
                 ::"r"(dst), "l"(src), "r"(bytes), "r"(bar), "l"(pol) : "memory");
}
__device__ __forceinline__ void bar_cons() { asm volatile("bar.sync 1, 256;" ::: "memory"); }
template <int ID, int N> __device__ __forceinline__ void nbar_sync() { asm volatile("bar.sync %0, %1;" ::"n"(ID), "n"(N) : "memory"); }
template <int ID, int N> __device__ __forceinline__ void nbar_arrive() { asm volatile("bar.arrive %0, %1;" ::"n"(ID), "n"(N) : "memory"); }
__device__ __forceinline__ bool mbar_test(uint32_t bar, uint32_t parity) {
    uint32_t ok;
    asm volatile("{\n.reg .pred p;\nmbarrier.test_wait.parity.shared::cta.b64 p, [%1], %2;\nselp.u32 %0, 1, 0, p;\n}" : "=r"(ok) : "r"(bar), "r"(parity) : "memory");
    return ok;
}
__device__ __forceinline__ uint32_t pin(uint32_t v) { asm volatile("" : "+r"(v)); return v; }
template <class T> __device__ __forceinline__ T pin_hard(T v) { return __shfl_sync(0xffffffffu, v, threadIdx.x & 31); }
template <class T> __device__ __forceinline__ T* pin(T* v) { asm volatile("" : "+l"(v)); return v; }
__device__ __forceinline__ void ldsm4(uint32_t (&a)[4], uint32_t addr) {
    asm volatile("ldmatrix.sync.aligned.m8n8.x4.shared.b16 {%0,%1,%2,%3}, [%4];" : "=r"(a[0]), "=r"(a[1]), "=r"(a[2]), "=r"(a[3]) : "r"(addr) : "memory");
}
__device__ __forceinline__ void ldsm4t(uint32_t (&a)[4], uint32_t addr) {
    asm volatile("ldmatrix.sync.aligned.m8n8.x4.trans.shared.b16 {%0,%1,%2,%3}, [%4];" : "=r"(a[0]), "=r"(a[1]), "=r"(a[2]), "=r"(a[3]) : "r"(addr) : "memory");
}
__device__ __forceinline__ void mma16816(float (&c)[4], const uint32_t (&a)[4], uint32_t b0, uint32_t b1) {
    asm volatile("mma.sync.aligned.m16n8k16.row.col.f32.bf16.bf16.f32 {%0,%1,%2,%3}, {%4,%5,%6,%7}, {%8,%9}, {%0,%1,%2,%3};"
                 : "+f"(c[0]), "+f"(c[1]), "+f"(c[2]), "+f"(c[3]) : "r"(a[0]), "r"(a[1]), "r"(a[2]), "r"(a[3]), "r"(b0), "r"(b1));
}
__device__ __forceinline__ uint32_t lds32(uint32_t addr) { uint32_t v; asm volatile("ld.shared.u32 %0, [%1];" : "=r"(v) : "r"(addr) : "memory"); return v; }
__device__ __forceinline__ float lds_f32(uint32_t addr) { float v; asm volatile("ld.shared.f32 %0, [%1];" : "=f"(v) : "r"(addr) : "memory"); return v; }
__device__ __forceinline__ float2 lds_f32x2(uint32_t addr) { float2 v; asm volatile("ld.shared.v2.f32 {%0,%1}, [%2];" : "=f"(v.x), "=f"(v.y) : "r"(addr) : "memory"); return v; }
__device__ __forceinline__ float4 lds_f32x4(uint32_t addr) { float4 v; asm volatile("ld.shared.v4.f32 {%0,%1,%2,%3}, [%4];" : "=f"(v.x), "=f"(v.y), "=f"(v.z), "=f"(v.w) : "r"(addr) : "memory"); return v; }
__device__ __forceinline__ uint2 lds64(uint32_t addr) { uint2 v; asm volatile("ld.shared.v2.u32 {%0,%1}, [%2];" : "=r"(v.x), "=r"(v.y) : "r"(addr) : "memory"); return v; }
__device__ __forceinline__ uint4 lds128(uint32_t addr) { uint4 v; asm volatile("ld.shared.v4.u32 {%0,%1,%2,%3}, [%4];" : "=r"(v.x), "=r"(v.y), "=r"(v.z), "=r"(v.w) : "r"(addr) : "memory"); return v; }
__device__ __forceinline__ void sts16(uint32_t addr, uint32_t v) { asm volatile("st.shared.b16 [%0], %1;" ::"r"(addr), "h"((unsigned short)v) : "memory"); }
__device__ __forceinline__ void sts32(uint32_t addr, uint32_t v) { asm volatile("st.shared.u32 [%0], %1;" ::"r"(addr), "r"(v) : "memory"); }
__device__ __forceinline__ void sts_f32(uint32_t addr, float v) { asm volatile("st.shared.f32 [%0], %1;" ::"r"(addr), "f"(v) : "memory"); }
__device__ __forceinline__ void sts_f32x2(uint32_t addr, float a, float b) { asm volatile("st.shared.v2.f32 [%0], {%1,%2};" ::"r"(addr), "f"(a), "f"(b) : "memory"); }
__device__ __forceinline__ void sts128(uint32_t addr, uint4 v) { asm volatile("st.shared.v4.u32 [%0], {%1,%2,%3,%4};" ::"r"(addr), "r"(v.x), "r"(v.y), "r"(v.z), "r"(v.w) : "memory"); }
__device__ __forceinline__ uint4 ldg_relaxed(const uint32_t* p) {
    uint4 v;
    asm volatile("ld.relaxed.gpu.global.v4.u32 {%0,%1,%2,%3}, [%4];" : "=r"(v.x), "=r"(v.y), "=r"(v.z), "=r"(v.w) : "l"(p) : "memory");
    return v;
}
__device__ __forceinline__ void ldg_relaxed_if(bool on, uint4& v, const uint32_t* p) {
    asm volatile("{\n.reg .pred q;\nsetp.ne.u32 q, %5, 0;\n@q ld.relaxed.gpu.global.v4.u32 {%0,%1,%2,%3}, [%4];\n}"
                 : "+r"(v.x), "+r"(v.y), "+r"(v.z), "+r"(v.w) : "l"(p), "r"((uint32_t)on) : "memory");
}
__device__ __forceinline__ void stg_relaxed2_if(bool on, uint32_t* p, uint32_t a, uint32_t b) {
    asm volatile("{\n.reg .pred q;\nsetp.ne.u32 q, %3, 0;\n@q st.relaxed.gpu.global.v2.u32 [%0], {%1,%2};\n}" ::"l"(p), "r"(a), "r"(b), "r"((uint32_t)on) : "memory");
}
__device__ __forceinline__ uint32_t ldg_relaxed32(const uint32_t* p) { uint32_t v; asm volatile("ld.relaxed.gpu.global.u32 %0, [%1];" : "=r"(v) : "l"(p) : "memory"); return v; }
__device__ __forceinline__ void stg_relaxed(uint32_t* p, uint32_t v) { asm volatile("st.relaxed.gpu.global.u32 [%0], %1;" ::"l"(p), "r"(v) : "memory"); }
__device__ __forceinline__ void stg_zero4(uint32_t* p) { asm volatile("st.relaxed.gpu.global.v4.u32 [%0], {%1,%1,%1,%1};" ::"l"(p), "r"(0u) : "memory"); }
__device__ __forceinline__ bool ready(const uint4& v) { return (v.x != 0u) & (v.y != 0u) & (v.z != 0u) & (v.w != 0u); }
__device__ __forceinline__ uint32_t min4(const uint4& v) { return min(__vimin3_u32(v.x, v.y, v.z), v.w); }
__device__ __forceinline__ uint4 inv4(const uint4& v) { return make_uint4(~v.x, ~v.y, ~v.z, ~v.w); }
__device__ __forceinline__ uint32_t pack_bf(float lo, float hi) {
    uint32_t r;
    asm("cvt.rn.bf16x2.f32 %0, %1, %2;" : "=r"(r) : "f"(hi), "f"(lo));
    return r;
}
__device__ __forceinline__ float bfr(float x) { return __uint_as_float(pack_bf(0.f, x) & 0xffff0000u); }
__device__ __forceinline__ float bf_lo(uint32_t w) { return __uint_as_float(w << 16); }
__device__ __forceinline__ float bf_hi(uint32_t w) { return __uint_as_float(w & 0xffff0000u); }
__device__ __forceinline__ float bf2f(__nv_bfloat16 v) { return __bfloat162float(v); }
__device__ __forceinline__ float ex2(float x) { float y; asm("ex2.approx.ftz.f32 %0, %1;" : "=f"(y) : "f"(x)); return y; }
__device__ __forceinline__ float rcp_fast(float x) { float y; asm("rcp.approx.ftz.f32 %0, %1;" : "=f"(y) : "f"(x)); return y; }
__device__ __forceinline__ float rsqrt_fast(float x) { float y; asm("rsqrt.approx.ftz.f32 %0, %1;" : "=f"(y) : "f"(x)); return y; }
__device__ __forceinline__ float sqrt_fast(float x) { float y; asm("sqrt.approx.f32 %0, %1;" : "=f"(y) : "f"(x)); return y; }
__device__ __forceinline__ uint32_t bf2_add(uint32_t a, uint32_t b) { uint32_t r; asm("add.rn.bf16x2 %0, %1, %2;" : "=r"(r) : "r"(a), "r"(b)); return r; }
__device__ __forceinline__ uint32_t bf2_sub(uint32_t a, uint32_t b) { uint32_t r; asm("sub.rn.bf16x2 %0, %1, %2;" : "=r"(r) : "r"(a), "r"(b)); return r; }
__device__ __forceinline__ uint32_t bf2_mul(uint32_t a, uint32_t b) { uint32_t r; asm("mul.rn.bf16x2 %0, %1, %2;" : "=r"(r) : "r"(a), "r"(b)); return r; }
__device__ __forceinline__ uint32_t gtime32() { uint32_t c; asm volatile("mov.u32 %0, %%globaltimer_lo;" : "=r"(c)); return c; }
__device__ __forceinline__ uint32_t clock32() { uint32_t c; asm volatile("mov.u32 %0, %%clock;" : "=r"(c)); return c; }

__device__ __forceinline__ float warp_sum(float v) {
#pragma unroll
    for (int o = 16; o > 0; o >>= 1) v += __shfl_xor_sync(0xffffffffu, v, o);
    return v;
}

struct Params {
    const __nv_bfloat16 *x, *kc, *vc, *b1, *b2, *c;
    __nv_bfloat16* out;
};

__device__ __forceinline__ void tma2d(uint32_t dst, const CUtensorMap* tm, int x, int y, uint32_t bar) {
    asm volatile("cp.async.bulk.tensor.2d.shared::cluster.global.mbarrier::complete_tx::bytes [%0], [%1, {%2, %3}], [%4];"
                 ::"r"(dst), "l"(tm), "r"(x), "r"(y), "r"(bar) : "memory");
}

__device__ __forceinline__ void tma2d_hint(uint32_t dst, const CUtensorMap* tm, int x, int y, uint32_t bar, uint64_t pol) {
    asm volatile("cp.async.bulk.tensor.2d.shared::cluster.global.mbarrier::complete_tx::bytes.L2::cache_hint [%0], [%1, {%2, %3}], [%4], %5;"
                 ::"r"(dst), "l"(tm), "r"(x), "r"(y), "r"(bar), "l"(pol) : "memory");
}
__device__ __forceinline__ uint32_t flag(float v) { return __float_as_uint(v) | 1u; }
__device__ __forceinline__ uint32_t and3(uint32_t a, uint32_t b, uint32_t c) { uint32_t r; asm("lop3.b32 %0, %1, %2, %3, 0x80;" : "=r"(r) : "r"(a), "r"(b), "r"(c)); return r; }
__device__ __forceinline__ uint32_t* slot_ptr(uint32_t lo) {
    uint32_t* r;
    asm volatile("mov.b64 %0, {%1, %2};" : "=l"(r) : "r"(lo), "r"((uint32_t)((size_t)slot(0, 0) >> 32)));
    return r;
}

__device__ __forceinline__ void load_bfrag(uint32_t vec, int stride, int k0, int g, int t, uint32_t& b0, uint32_t& b1) {
    uint32_t a = vec + (g & 3) * stride + (k0 + 2 * t) * 2;
    b0 = lds32(a);
    b1 = lds32(a + 16);
}

__device__ __forceinline__ void ln_finish(float pivot, float sum, float sumsq, uint32_t& m2, float& rden) {
    float dm = sum * (1.f / D);
    float var = fmaxf(sumsq * (1.f / D) - dm * dm, 0.f);
    float mean = pivot + dm;
    m2 = pack_bf(mean, mean);
    rden = rcp_fast(bfr(sqrt_fast(bfr(bfr(var) + 1e-5f))));
}
__device__ __forceinline__ uint32_t ln_mod_pair(uint32_t xw, uint32_t cw, uint32_t sw, uint32_t m2, float rden) {
    uint32_t d = bf2_sub(xw, m2);
    uint32_t ln = pack_bf(bf_lo(d) * rden, bf_hi(d) * rden);
    return bf2_add(bf2_mul(ln, bf2_add(cw, 0x3f803f80u)), sw);
}
__device__ __forceinline__ uint4 ln_mod4(const uint4& x, const uint4& c, const uint4& s, uint32_t m2, float rden) {
    return make_uint4(ln_mod_pair(x.x, c.x, s.x, m2, rden), ln_mod_pair(x.y, c.y, s.y, m2, rden),
                      ln_mod_pair(x.z, c.z, s.z, m2, rden), ln_mod_pair(x.w, c.w, s.w, m2, rden));
}
__device__ __forceinline__ void acc_stats(const uint4& v, float pv, float& s, float& q) {
    const float a0 = bf_lo(v.x) - pv, a1 = bf_hi(v.x) - pv, a2 = bf_lo(v.y) - pv, a3 = bf_hi(v.y) - pv;
    const float a4 = bf_lo(v.z) - pv, a5 = bf_hi(v.z) - pv, a6 = bf_lo(v.w) - pv, a7 = bf_hi(v.w) - pv;
    s += ((a0 + a1) + (a2 + a3)) + ((a4 + a5) + (a6 + a7));
    q += (fmaf(a0, a0, a1 * a1) + fmaf(a2, a2, a3 * a3)) + (fmaf(a4, a4, a5 * a5) + fmaf(a6, a6, a7 * a7));
}
__device__ __forceinline__ uint32_t* mod_slot(int kind, int j, int b) { return g_mod + (kind * 20 + (j >> 2)) * 64 + b * 16 + (j & 3) * 4; }

template <int N>
__device__ __forceinline__ void poll_n(uint4 (&v)[N], const uint32_t* const* ptr, const bool* on) {
    bool pend[N];
#pragma unroll
    for (int i = 0; i < N; i++) pend[i] = on[i];
    int it = 0;
    while (true) {
#pragma unroll
        for (int i = 0; i < N; i++) if (pend[i]) v[i] = ldg_relaxed(ptr[i]);
        bool any = false;
#pragma unroll
        for (int i = 0; i < N; i++) { pend[i] = pend[i] && !ready(v[i]); any |= pend[i]; }
        if (!__any_sync(0xffffffffu, any)) break;
        if (++it > SPIN_LIMIT) __trap();
    }
#pragma unroll
    for (int i = 0; i < N; i++) v[i] = inv4(v[i]);
}
__device__ __forceinline__ uint4 poll1(const uint32_t* p, bool on) {
    uint4 v[1] = {make_uint4(0, 0, 0, 0)};
    const uint32_t* const ptr[1] = {p};
    const bool o[1] = {on};
    poll_n<1>(v, ptr, o);
    return v[0];
}

__device__ __forceinline__ void gelu_stage(uint32_t sb, int m, int lane) {
    const int g = lane >> 2, b = lane & 3;
    const uint32_t y_ld = pin_hard(sb + SC_Y + m * 256 + lane * 8), s_ld = pin_hard(sb + SC_ST + b * 64);
    const uint32_t h_st = pin_hard(sb + SC_H1 + b * 64 + (g >> 1) * 16 + m * 8 + (g & 1) * 2);
    float a0 = 0.f, b0 = lds_f32(sb + OWN_B1 + (16 * m + g) * 4), a1 = 0.f, b1 = lds_f32(sb + OWN_B1 + (16 * m + g + 8) * 4);
    const float piv = bf_hi(lds32(sb + OFF_STAT + b * 8));
    nbar_sync<NB_AB, 320>();
#pragma unroll
    for (int w = 0; w < 8; w++) {
        const float4 t = lds_f32x4(sb + SC_AB + w * 1024 + m * 512 + lane * 16);
        a0 += t.x; b0 += t.y; a1 += t.z; b1 += t.w;
    }
    sts128(sb + SC_AB + m * 512 + lane * 16, make_uint4(__float_as_uint(a0), __float_as_uint(b0), __float_as_uint(a1), __float_as_uint(b1)));
    nbar_sync<NB_Y, 320>();
    float4 q[4];
    float2 y[8];
#pragma unroll
    for (int i = 0; i < 4; i++) q[i] = lds_f32x4(s_ld + i * 16);
#pragma unroll
    for (int w = 0; w < 8; w++) y[w] = lds_f32x2(y_ld + w * 512);
    const float dm = (((q[0].y + q[0].w) + (q[1].y + q[1].w)) + ((q[2].y + q[2].w) + (q[3].y + q[3].w))) * (1.f / D);
    const float sq = ((q[0].x + q[0].z) + (q[1].x + q[1].z)) + ((q[2].x + q[2].z) + (q[3].x + q[3].z));
    const float r = rsqrt_fast(fmaxf(fmaf(-dm, dm, fmaf(sq, 1.f / D, 1e-5f)), 1e-5f));
    const float y0 = ((y[0].x + y[1].x) + (y[2].x + y[3].x)) + ((y[4].x + y[5].x) + (y[6].x + y[7].x));
    const float y1 = ((y[0].y + y[1].y) + (y[2].y + y[3].y)) + ((y[4].y + y[5].y) + (y[6].y + y[7].y));
    const float dmr = piv - bfr(piv - dm);
    const float u0 = fmaf(r, fmaf(dmr, a0, -y0), b0), u1 = fmaf(r, fmaf(dmr, a1, -y1), b1);
    const float e0 = ex2(u0 * fmaf(u0 * u0, -0.044715f * 2.302208198144325f, -2.302208198144325f));
    const float e1 = ex2(u1 * fmaf(u1 * u1, -0.044715f * 2.302208198144325f, -2.302208198144325f));
    sts16(h_st, pack_bf(u0 * rcp_fast(1.f + e0), 0.f));
    sts16(h_st + 4, pack_bf(u1 * rcp_fast(1.f + e1), 0.f));
#pragma unroll
    for (int w = 0; w < 8; w++) asm volatile("bar.arrive %0, 96;" ::"r"(NB_O + w) : "memory");
}

struct Roles { bool is_f, is_owner; int f, own; };
__device__ __forceinline__ Roles roles(int cta) {
    Roles r;
    r.f = (cta * 27) >> 6;
    r.is_f = (((cta + 1) * 27) >> 6) != r.f;
    r.is_owner = !r.is_f || r.f % 9 == 4;
    r.own = r.is_f ? 74 + r.f / 9 : cta - r.f;
    return r;
}

__global__ void __launch_bounds__(NTHREADS, 1)
fused_kernel(const Params p, const __grid_constant__ CUtensorMap tm_wmod, const __grid_constant__ CUtensorMap tm_wq,
             const __grid_constant__ CUtensorMap tm_wo, const __grid_constant__ CUtensorMap tm_w1, const __grid_constant__ CUtensorMap tm_w2,
             const __grid_constant__ CUtensorMap tm_v, const __grid_constant__ CUtensorMap tm_gb) {
    extern __shared__ __align__(1024) unsigned char smem[];
    const uint32_t t_start = gtime32();
    if (threadIdx.x == 0) {
        const uint32_t c_ = blockIdx.x;
        const uint32_t off = ((c_ & 3) << 26) + (c_ >> 2) * (1u << 21) + (((ROTA * (c_ >> 2) + ROTB) & 31) << 14) + (SK - WIN) * DH * 2;
        asm volatile("cp.async.bulk.prefetch.L2.global.L2::cache_hint [%0], %1, %2;" ::"l"((const char*)p.kc + off), "r"(TILE_BYTES), "l"(0x12f0000000000000ull  ) : "memory");
    }
    const uint32_t sb = smem_u32(smem);
    const int cta = blockIdx.x;
    const int head = cta >> 2, bown = cta & 3;
    const int rot = (ROTA * head + ROTB) & (NITEM / 2 - 1);
    const char* const kb = (const char*)(p.kc + ((size_t)(bown * NH + head) * SK + (SK - WIN)) * DH);
    uint64_t pol = 0;
    if (threadIdx.x == 256) {
        mbar_init(sb + OFF_BAR, 1);
        asm volatile("fence.mbarrier_init.release.cluster;" ::: "memory");
        asm volatile("createpolicy.fractional.L2::evict_first.b64 %0, 1.0;" : "=l"(pol));
        mbar_expect_tx(sb + OFF_BAR, TILE_BYTES);
        bulk_load(sb + OFF_RING, kb + (size_t)rot * TILE_BYTES, TILE_BYTES, sb + OFF_BAR, pol);
        if ((((head + 1) * 5) >> 4) != ((head * 5) >> 4)) {
            const uint32_t bar = sb + OFF_BAR + 2 * NS * 8;
            mbar_init(bar, 1);
            asm volatile("fence.mbarrier_init.release.cluster;" ::: "memory");
            mbar_expect_tx(bar, D * 64);
#pragma unroll 1
            for (int r = 0; r < D; r += 160) tma2d(sb + X_WM + r * 64, &tm_wmod, 32 * (((head * 5) >> 4) * 4 + bown), r, bar);
        }
    }
    const uint32_t bar_full = sb + OFF_BAR, bar_empty = bar_full + NS * 8;
    const uint32_t bar_wm = bar_empty + NS * 8, bar_wq = bar_wm + 8, bar_xfree = bar_wq + 8, bar_wo = bar_xfree + 8  ;
    const uint32_t bar_w1 = bar_wo + 40  , bar_w2 = bar_w1 + 32  , bar_help = bar_w2 + 80, bar_v = bar_help + 8  ;
    const uint32_t bar_gb = bar_v + 32  , bar_x1 = bar_gb + 32;
    const int tid = threadIdx.x, warp = tid >> 5, lane = tid & 31;
    const Roles role = roles(cta);
    const bool is_f = role.is_f, is_owner = role.is_owner;
    const int f = role.f, own = role.own;
    const bool crit = (((head + 1) * 5) >> 4) != ((head * 5) >> 4);
    const int mr = cta - ((head * 5) >> 4) * 4, mq = ((head * 5) >> 4) * 4 + bown;
    const int ml = mr * 31 / 44;
    const bool late = !crit && (mr + 1) * 31 / 44 != ml;
    const int mc = crit ? mq : ml < 60 ? 40 + ml : 58 + ml;
    const bool gb_own = is_owner && own < 72;

    PROF_DECL
    PROF(0);
    uint4 xa = make_uint4(0, 0, 0, 0), xb = xa, ca0 = xa, ca1 = xa, xs[3] = {xa, xa, xa};
    uint32_t own0 = 0;
    __nv_bfloat16 own2 = __float2bfloat16(0.f);
    if (warp < 8) {
        xa = *(const uint4*)(p.x + (tid & 3) * D + (tid >> 2) * 8);
        ca0 = ((const uint4*)p.c)[tid];
        if (tid < 64) { xb = *(const uint4*)(p.x + (tid & 3) * D + (64 + (tid >> 2)) * 8); ca1 = ((const uint4*)p.c)[256 + tid]; }
        if (warp < 4) {
#pragma unroll
            for (int i = 0; i < 3; i++) if (lane + 32 * i < 80) xs[i] = ((const uint4*)p.x)[warp * 80 + lane + 32 * i];
        } else if (warp == 4) {
            if (is_owner) own0 = *(const uint32_t*)((lane < 16 ? p.x + (lane >> 2) * D : p.b2) + 8 * own + 2 * (lane & 3));
            if (is_f) own2 = p.b1[32 * f + lane];
        }
    }
    const char* const vb = (const char*)(p.vc + ((size_t)(bown * NH + head) * SK + (SK - WIN)) * DH);
    const uint32_t bar_first = crit ? bar_wm : bar_wq;
    if (threadIdx.x == 256) {
        if (!crit) {
            mbar_init(bar_wq, 1);
            asm volatile("fence.mbarrier_init.release.cluster;" ::: "memory");
            mbar_expect_tx(bar_wq, D * 64);
            const uint32_t c0 = clock32();
            while (clock32() - c0 < WQ_DELAY) { }
#pragma unroll
            for (int r = 0; r < D; r += 160) tma2d(sb + X_WQ + r * 64, &tm_wq, 32 * cta, r, bar_wq);
        }
    } else if (threadIdx.x == 0) {
#pragma unroll
        for (int s = 0; s < NS; s++) { if (s) mbar_init(bar_full + s * 8, 1); mbar_init(bar_empty + s * 8, 4); }
        mbar_init(crit ? bar_wq : bar_wm, 1);
        mbar_init(bar_xfree, 1);
#pragma unroll
        for (int i = 0; i < 5; i++) { mbar_init(bar_wo + i * 8, 1); mbar_init(bar_w2 + i * 16, 1); mbar_init(bar_w2 + i * 16 + 8, 1); }
        mbar_init(bar_help, 1); mbar_init(bar_x1, 1);
#pragma unroll
        for (int i = 0; i < 4; i++) { mbar_init(bar_v + i * 8, 1); mbar_init(bar_w1 + i * 8, 1); mbar_init(bar_gb + i * 8, 1); }
        asm volatile("fence.mbarrier_init.release.cluster;" ::: "memory");
    }
    __syncthreads();

    if (warp == 8) {
        if (lane == 0) {
            int tp = NS;
            int sched = PACE_A - NS * PACE_TAU;
            int phase = 0;
#pragma unroll 1
            for (int t = 1; t <= NITEM; t++) {
                if (t == 1) mbar_wait(bar_full, 0);
                if (t == 2) {
                    mbar_wait(bar_first, 0);
                    if (crit) {
                        mbar_expect_tx(bar_wq, D * 64);
#pragma unroll 1
                        for (int r = 0; r < D; r += 160) tma2d(sb + X_WQ + r * 64, &tm_wq, 32 * cta, r, bar_wq);
                    }
                }
                if (t == 3) {
                    asm volatile("prefetch.tensormap [%0];" ::"l"(&tm_v) : "memory");
                    asm volatile("prefetch.tensormap [%0];" ::"l"(&tm_wo) : "memory");
                    asm volatile("prefetch.tensormap [%0];" ::"l"(&tm_w1) : "memory");
                    asm volatile("prefetch.tensormap [%0];" ::"l"(&tm_w2) : "memory");
                    asm volatile("prefetch.tensormap [%0];" ::"l"(&tm_gb) : "memory");
                }
                if (t == NS && late) {
                    mbar_wait(bar_full + (NS - INFLIGHT) * 8, 0);
                    mbar_expect_tx(bar_wm, D * 64);
#pragma unroll 1
                    for (int r = 0; r < D; r += 160) tma2d(sb + X_WM + r * 64, &tm_wmod, 32 * mc, r, bar_wm);
                }
                if (t >= NS && t < PF_END) {
                    int it = 0;
                    while (!mbar_test(bar_empty + (t & (NS - 1)) * 8, ((t >> 3) - 1) & 1)) {
                        if (tp < PF_END && (int)(gtime32() - t_start) >= PACE_A + (tp - NS) * PACE_TAU) {
                            asm volatile("cp.async.bulk.prefetch.L2.global.L2::cache_hint [%0], %1, %2;"
                                         ::"l"(((tp & 1) ? vb : kb) + (size_t)(((tp >> 1) + rot) & (NITEM / 2 - 1)) * TILE_BYTES), "r"(TILE_BYTES), "l"(pol) : "memory");
                            tp++;
                        }
                        if (++it > 16 * SPIN_LIMIT) __trap();
                    }
                    if (tp <= t) tp = t + 1;
                }
                if (t == NITEM) {
                    mbar_wait(bar_xfree, 0);
                    const uint32_t t_ref = t_start + phase + (NITEM - 1) * PACE_TAU;
#pragma unroll 1
                    for (int i = 0; i < 5; i++) {
                        while ((int)(gtime32() - t_ref) < WO_T + i * WO_S) { }
                        mbar_expect_tx(bar_wo + i * 8, DH * 64);
                        tma2d(sb + X_WO + i * (DH * 64), &tm_wo, bown * 160 + i * 32, head * DH, bar_wo + i * 8);
                    }
                    if (gb_own) {
                        mbar_wait(bar_empty + 3 * 8, ((NITEM >> 3) - 1) & 1);
                        mbar_wait(bar_x1, 0);
                        { const uint32_t c0 = clock32(); while (clock32() - c0 < GB_EV) { } }
                        while ((int)(gtime32() - t_ref) < GB_T) { }
#pragma unroll 1
                        for (int i = 0; i < 4; i++) {
                            mbar_expect_tx(bar_gb + i * 8, 160 * 16);
                            tma2d(sb + X_GB + i * (160 * 16), &tm_gb, 5 * D + 8 * own, 160 * i, bar_gb + i * 8);
                        }
                    }
                    if (is_f) {
#pragma unroll 1
                        for (int i = 0; i < 3; i++) mbar_wait(bar_empty + i * 8, ((NITEM >> 3) - 1) & 1);
                        while ((int)(gtime32() - t_ref) < W1_T) { }
#pragma unroll 1
                        for (int i = 0; i < 4; i++) {
                            mbar_expect_tx(bar_w1 + i * 8, 160 * 64);
                            tma2d(sb + X_W1 + i * (160 * 64), &tm_w1, 32 * f, 160 * i, bar_w1 + i * 8);
                        }
                        while ((int)(gtime32() - t_ref) < W2_T) { }
#pragma unroll 1
                        for (int i = 0; i < 10; i++) {
                            mbar_expect_tx(bar_w2 + i * 8, 4096);
                            tma2d(sb + X_W2 + i * 4096, &tm_w2, 64 * i, 32 * f, bar_w2 + i * 8);
                        }
                    }
                    break;
                }
                const int s = t & (NS - 1);
                if (t >= NS) {
                    mbar_wait(bar_empty + s * 8, ((t >> 3) - 1) & 1);
                    while ((int)(gtime32() - t_start) < sched + t * PACE_TAU) { }
                } else if (t >= INFLIGHT) {
                    mbar_wait(bar_full + (t - INFLIGHT) * 8, 0);
                }
                if (t < NITEM - 2) {
                    const int pair = t == NITEM - 3 ? NITEM / 2 - 1 : t >> 1;
                    mbar_expect_tx(bar_full + s * 8, TILE_BYTES);
                    bulk_load(sb + OFF_RING + s * TILE_BYTES, ((t & 1) && t != NITEM - 3 ? vb : kb) + (size_t)((pair + rot) & (NITEM / 2 - 1)) * TILE_BYTES, TILE_BYTES, bar_full + s * 8, pol);
                } else {
                    const int row = (bown * NH + head) * SK + (SK - WIN) + ((t - NITEM / 2 + rot) & (NITEM / 2 - 1)) * TILE_KEYS;
#pragma unroll 1
                    for (int i = 0; i < 2; i++) {
                        const uint32_t bar = bar_v + (2 * (t - (NITEM - 2)) + i) * 8;
                        mbar_expect_tx(bar, TILE_BYTES / 2);
                        tma2d_hint(sb + OFF_RING + s * TILE_BYTES + i * (TILE_BYTES / 2), &tm_v, 64 * i, row, bar, pol);
                    }
                }
                if (t >= PH_FIRST + PH_LAG && (t & 3) == (PH_LAG & 3)) {
                    const int now = (int)(gtime32() - t_start) - (t - PH_LAG) * PACE_TAU;
                    uint32_t ph;
                    asm volatile("atom.relaxed.gpu.global.add.u32 %0, [%1], 0;" : "=r"(ph) : "l"(g_phase + ((t - PH_LAG) >> 2) * 32) : "memory");
                    phase = (int)min(((ph & 0xffffffu) * 4 + (NCTA - (ph >> 24)) * now) >> 7, 65535u);
                    sched += (phase - LAT_T - sched) / 2;
                }
            }
        }
        __syncwarp();
    }

    if (warp == 9) {
        int side = 0;
        if (lane == 0) {
            uint32_t best[2] = {~0u, ~0u};
#pragma unroll
            for (int i = 0; i < 4; i++) stg_zero4(slot(SL_SIDE, i >> 1) + cta * 8 + (i & 1) * 4);
            uint32_t n = 0;
#pragma unroll 1
            for (int i = 0; (i & 1) || (n < NPROBE - 1 && (int)(gtime32() - t_start) < PROBE_END); i++) {
                uint32_t t0 = clock32(), t1;
                asm volatile("atom.relaxed.gpu.global.inc.u32 %0, [%1], %2;" : "=r"(n) : "l"(slot(SL_SIDE, i & 1) + cta * 8), "r"(0xffffu) : "memory");
                asm volatile("{\n.reg .pred p;\nsetp.ne.u32 p, %1, 0xffffffff;\nmov.u32 %0, 0;\n@p mov.u32 %0, %%clock;\n}" : "=r"(t1) : "r"(n) : "memory");
                if (i & 1) best[1] = min(best[1], t1 - t0); else best[0] = min(best[0], t1 - t0);
            }
            side = best[1] < best[0];
        }
        side = __shfl_sync(0xffffffffu, side, 0);
        HPROF(1);
        mbar_wait(bar_full + (NS - 1) * 8, 0);
        stg_zero4(slot(SL_O + (cta >> 4), lane >> 4) + (cta & 15) * 64 + (lane & 15) * 4);
        if (is_owner) {
#pragma unroll 1
            for (int i = lane; i < NH * 8; i += 32) stg_zero4(slot(SL_P1 + own, side) + i * 4);
#pragma unroll 1
            for (int i = lane; i < NF * 8; i += 32) stg_zero4(slot(SL_P2 + 2 * own + (i >> 8), side) + (i & 255) * 4);
            if (lane < 8) stg_zero4(slot(SL_X1 + own / 30, lane >> 2) + (own % 30) * 32 + (lane & 3) * 4);
        }
        __threadfence();
        __syncwarp();
        if (lane == 0) stg_relaxed(g_clr + cta, 1u + side);
        HPROF(0);
        HPROF(2);
        while ((int)(gtime32() - t_start) < CLR_CHECK) __nanosleep(1000);
        mbar_wait(bar_xfree, 0);
        {
            uint4 v = make_uint4(1, 1, 1, 1), gv = v, mv[20];
#pragma unroll
            for (int i = 0; i < 20; i++) mv[i] = v;
#pragma unroll 1
            for (int it = 0;; it++) {
                v = ldg_relaxed(g_clr + lane * 4);

                ldg_relaxed_if(is_owner && lane < (gb_own ? 4 : 8), gv, mod_slot(lane < 4 ? 2 : 5, own, lane & 3));
#pragma unroll
                for (int i = 0; i < 20; i++) ldg_relaxed_if(is_f, mv[i], mod_slot(3, 8 * i + (lane >> 2), lane & 3));
                bool ok = ready(v) && ready(gv);
#pragma unroll
                for (int i = 0; i < 20; i++) ok = ok && ready(mv[i]);
                if (__all_sync(0xffffffffu, ok)) break;
                if (it > SPIN_LIMIT) __trap();
                __nanosleep(2000);
            }
            const uint32_t w[4] = {v.x, v.y, v.z, v.w};
#pragma unroll
            for (int i = 0; i < 4; i++) {
                const Roles r = roles(4 * lane + i);
                if (r.is_owner) {
                    sts32(sb + OFF_TAB1 + r.own * 4, (uint32_t)(size_t)(slot(SL_P1 + r.own, w[i] - 1) + head * 32));
                    sts32(sb + OFF_TAB2 + r.own * 4, (uint32_t)(size_t)(slot(SL_P2 + 2 * r.own + (f >> 5), w[i] - 1) + (f & 31) * 32));
                }
            }
            if (lane == 0) sts32(sb + OFF_SIDE, side);
            if (lane < 8) sts128(sb + OWN_GA + lane * 16, inv4(gv));
            const uint32_t dst = sb + OFF_VB + (lane & 3) * VEC_STRIDE + (lane >> 2) * 16;
#pragma unroll
            for (int i = 0; i < 10; i++) {
                const uint4 c = inv4(mv[10 + i]);
                sts128(dst + i * 128, make_uint4(bf2_add(c.x, 0x3f803f80u), bf2_add(c.y, 0x3f803f80u), bf2_add(c.z, 0x3f803f80u), bf2_add(c.w, 0x3f803f80u)));
                sts128(dst + (OFF_RED - OFF_VB) + i * 128, inv4(mv[i]));
            }
        }
        asm volatile("fence.acq_rel.gpu;" ::: "memory");
        __syncwarp();
        HPROF(3);
        if (lane == 0) mbar_arrive(bar_help);
        {
            const uint32_t* const src = pin(slot(SL_O + (cta >> 4), side) + (cta & 12) * 64 + lane * 4);
            const uint32_t dst = pin(sb + OFF_O + (lane >> 4) * O_STRIDE + (lane & 15) * 16);
            mbar_wait(bar_v + 16, 0);
            mbar_wait(bar_v + 24, 0);
            uint4 v[2];
            const uint32_t* const ptr[2] = {src, src + 128};
            const bool on[2] = {true, true};
            poll_n<2>(v, ptr, on);
            sts128(dst, v[0]);
            sts128(dst + 2 * O_STRIDE, v[1]);
#pragma unroll
            for (int w = 0; w < 8; w++) asm volatile("bar.arrive %0, 64;" ::"r"(NB_O + w) : "memory");
        }
        HPROF(4);
    }
    if (warp >= 8) {
        if (gb_own && warp == 9) {
            uint32_t a[20][4];
#pragma unroll
            for (int i = 0; i < 20; i++) ldsm4(a[i], sb + OFF_VA + (lane & 3) * VEC_STRIDE + (4 * i + (lane >> 3)) * 16);
            float c[4][4];
#pragma unroll
            for (int i = 0; i < 4; i++) c[i][0] = c[i][1] = c[i][2] = c[i][3] = 0.f;
#pragma unroll
            for (int bx = 0; bx < 4; bx++) {
                mbar_wait(bar_gb + bx * 8, 0);
#pragma unroll
                for (int i = 5 * bx; i < 5 * bx + 5; i++) {
                    uint32_t w[4];
                    ldsm4t(w, sb + X_GB + (32 * i + lane) * 16);
                    const uint32_t a0[4] = {a[i][0], 0u, a[i][1], 0u}, a1[4] = {a[i][2], 0u, a[i][3], 0u};
                    mma16816(c[(2 * i) & 3], a0, w[0], w[1]);
                    mma16816(c[(2 * i + 1) & 3], a1, w[2], w[3]);
                }
            }
            if (lane < 16) sts32(sb + OWN_GB + lane * 4, pack_bf((c[0][0] + c[1][0]) + (c[2][0] + c[3][0]), (c[0][1] + c[1][1]) + (c[2][1] + c[3][1])));
            HPROF(6);
        }
        if (is_owner && warp == 9) nbar_arrive<NB_E6, 288>();
        if (is_f) gelu_stage(sb, warp - 8, lane);
        return;
    }

    const int g = lane >> 2, t4 = lane & 3;
    const int mi = lane >> 3, r8 = lane & 7;

    {
        auto silu4 = [&](const uint4& cv) {
            uint32_t w4[4] = {cv.x, cv.y, cv.z, cv.w};
#pragma unroll
            for (int e = 0; e < 4; e++) {
                float c0 = bf_lo(w4[e]), c1 = bf_hi(w4[e]);
                w4[e] = pack_bf(c0 * rcp_fast(1.f + ex2(-1.4426950408889634f * c0)), c1 * rcp_fast(1.f + ex2(-1.4426950408889634f * c1)));
            }
            return make_uint4(w4[0], w4[1], w4[2], w4[3]);
        };
        {
            uint4 v = silu4(ca0);
            sts128(sb + OFF_VA + (tid / 80) * VEC_STRIDE + (tid % 80) * 16, v);
            if (tid < 64) { v = silu4(ca1); sts128(sb + OFF_VA + 3 * VEC_STRIDE + (16 + tid) * 16, v); }
        }
        if (warp < 4) {
            float s = 0.f, q = 0.f;
            const float pv = __shfl_sync(0xffffffffu, bf_lo(xs[0].x), 0);
#pragma unroll
            for (int i = 0; i < 3; i++) if (i < 2 || lane < 16) acc_stats(xs[i], pv, s, q);
#pragma unroll
            for (int of = 16; of > 0; of >>= 1) { s += __shfl_xor_sync(0xffffffffu, s, of); q += __shfl_xor_sync(0xffffffffu, q, of); }
            uint32_t m2; float rden;
            ln_finish(pv, s, q, m2, rden);
            if (lane == 0) { sts32(sb + OFF_STAT + warp * 8, m2); sts_f32(sb + OFF_STAT + warp * 8 + 4, rden); }
        } else if (warp == 4) {
            sts32(sb + OWN_X + lane * 4, bf2_add(own0, 0u));
            sts_f32(sb + OWN_B1 + lane * 4, bf2f(own2));
        }
    }
    bar_cons();
    PROF(24);
    uint32_t qf[8][2];
    float o[8][4];
#pragma unroll
    for (int c = 0; c < 8; c++) { o[c][0] = o[c][1] = o[c][2] = o[c][3] = 0.f; }
    float m_run = -INFINITY, l_run = 0.f;
    const bool diag = (t4 == (g >> 1));
    const bool odd = g & 1;
    const uint32_t koff = (warp & 3) * 4096 + (r8 + 8 * (mi & 1)) * 256 + (mi >> 1) * 128 + (r8 << 4);
    const uint32_t voff = TILE_BYTES + (warp & 3) * 4096 + (r8 + 8 * (mi >> 1)) * 256 + (mi & 1) * 128 + (r8 << 4);
    const int src0 = (2 * t4) * 4 + t4, src1 = (2 * t4 + 1) * 4 + t4;
#pragma unroll 1
    for (int step = crit ? 0 : 1; step < 3; step++) {
        if (step < 2 || late) {
            if (step == 1) {
                if (!crit) mbar_wait(bar_wq, 0);
                const uint32_t m2 = lds32(sb + OFF_STAT + (tid & 3) * 8);
                const float rden = lds_f32(sb + OFF_STAT + (tid & 3) * 8 + 4);
                uint4 v[4];
                v[2] = v[3] = make_uint4(1, 1, 1, 1);
                const uint32_t* const p0 = mod_slot(0, tid >> 2, tid & 3);
                while ((int)(gtime32() - t_start) < MOD_T) { }
                PROF(2);
#pragma unroll 1
                for (int it = 0;; it++) {
                    ldg_relaxed_if(tid < 64, v[2], p0 + 16 * 64);
                    ldg_relaxed_if(tid < 64, v[3], p0 + 36 * 64);
                    v[0] = ldg_relaxed(p0);
                    v[1] = ldg_relaxed(p0 + 20 * 64);
                    if (__all_sync(0xffffffffu, min(min(min4(v[0]), min4(v[1])), min(min4(v[2]), min4(v[3]))) != 0u)) break;
                    if (it > SPIN_LIMIT) __trap();
                }
#pragma unroll
                for (int i = 0; i < 4; i++) v[i] = inv4(v[i]);
                PROF(3);
                uint4 h0 = ln_mod4(xa, v[1], v[0], m2, rden);
                sts128(sb + OFF_VB + (tid & 3) * VEC_STRIDE + (tid >> 2) * 16, h0);
                if (tid < 64) {
                    h0 = ln_mod4(xb, v[3], v[2], m2, rden);
                    sts128(sb + OFF_VB + (tid & 3) * VEC_STRIDE + (64 + (tid >> 2)) * 16, h0);
                }
            }
            mbar_wait(step == 1 ? bar_wq : bar_wm, 0);
            bar_cons();
            const uint32_t strip = sb + (step == 1 ? X_WQ : X_WM), vec = sb + (step == 1 ? OFF_VB : OFF_VA);
            float acc[2][4];
#pragma unroll
            for (int m = 0; m < 2; m++) { acc[m][0] = acc[m][1] = acc[m][2] = acc[m][3] = 0.f; }
#pragma unroll
            for (int i = 0; i < 5; i++) {
                int k0 = (warp * 5 + i) * 16;
                uint32_t b0, b1;
                load_bfrag(vec, VEC_STRIDE, k0, g, t4, b0, b1);
                int krow = k0 + r8 + 8 * (mi >> 1);
#pragma unroll
                for (int m = 0; m < 2; m++) {
                    uint32_t a[4];
                    int ch = 2 * m + (mi & 1);
                    ldsm4t(a, strip + krow * 64 + ((ch ^ ((krow >> 1) & 3)) << 4));
                    mma16816(acc[m], a, b0, b1);
                }
            }
            if (t4 < 2) {
#pragma unroll
                for (int m = 0; m < 2; m++) {
                    sts_f32x2(sb + OFF_RED + ((warp * 32 + m * 16 + g) * 4 + 2 * t4) * 4, acc[m][0], acc[m][1]);
                    sts_f32x2(sb + OFF_RED + ((warp * 32 + m * 16 + g + 8) * 4 + 2 * t4) * 4, acc[m][2], acc[m][3]);
                }
            }
            bar_cons();
            if (tid < 64) {
                float v0 = 0.f, v1 = 0.f;
#pragma unroll
                for (int w = 0; w < 8; w++) {
                    v0 += lds_f32(sb + OFF_RED + (w * 128 + (tid & 15) * 8 + (tid >> 4)) * 4);
                    v1 += lds_f32(sb + OFF_RED + (w * 128 + (tid & 15) * 8 + 4 + (tid >> 4)) * 4);
                }
                stg_relaxed(step == 1 ? g_q + (((cta & ~3) + (tid >> 4)) * 4 + bown) * 32 + (tid & 15) : g_mod + mc * 64 + tid, ~pack_bf(v0, v1));
            }
        }
        if (step == 0) continue;
        if (step == 1) {
            if (warp == 0) {
                { const uint32_t c0 = clock32(); while (clock32() - c0 < Q_PAUSE) { } }
                uint4 v = poll1(g_q + (cta * 4 + ((lane >> 2) & 3)) * 32 + (lane & 3) * 4, lane < 16);
                if (lane < 16) {
                    sts128(sb + OFF_Q + lane * 16, v);
                    stg_zero4(g_q + (cta * 4 + (lane >> 2)) * 32 + (lane & 3) * 4);
                }
            }
            bar_cons();
            PROF(4);

#pragma unroll
            for (int c = 0; c < 8; c++) {
                qf[c][0] = lds32(sb + OFF_Q + (((c ^ g) * 4 + t4) << 2));
                qf[c][1] = lds32(sb + OFF_Q + 128 + (((c ^ g) * 4 + t4) << 2));
            }
        } else {
            bar_cons();
            if (tid == 0) mbar_arrive(bar_xfree);
        }
#pragma unroll 1
        for (int j = (step == 1 ? 0 : SEG_J) + (warp >> 2); j < (step == 1 ? SEG_J : NITEM / 2 - 2); j += 2) {
            const int s = (2 * j) & (NS - 1);
            const uint32_t par = (j >> 2) & 1;
            mbar_wait(bar_full + s * 8, par);
            if (tid == 0 && 2 * j >= PH_FIRST) {
                const int x = min(max((int)(gtime32() - t_start) - 2 * j * PACE_TAU, 0), 65535);
                asm volatile("red.relaxed.gpu.global.add.u32 [%0], %1;" ::"l"(g_phase + (j >> 1) * 32), "r"((1u << 24) + (x >> 2)) : "memory");
            }
            const uint32_t base = sb + OFF_RING + s * TILE_BYTES;
            float sa[4] = {0.f, 0.f, 0.f, 0.f}, sb2[4] = {0.f, 0.f, 0.f, 0.f};
#pragma unroll
            for (int c = 0; c < 8; c += 2) {
                uint32_t a[4], a2[4];
                ldsm4(a, (base + koff) ^ (c << 4));
                ldsm4(a2, (base + koff) ^ ((c + 1) << 4));
                mma16816(sa, a, qf[c][0], qf[c][1]);
                mma16816(sb2, a2, qf[c + 1][0], qf[c + 1][1]);
            }
            const uint32_t sw = pack_bf(odd ? sa[1] + sb2[1] : sa[0] + sb2[0], odd ? sa[3] + sb2[3] : sa[2] + sb2[2]);
            const uint32_t sv = pack_bf(bf_lo(sw) * 0.08838834764831845f, bf_hi(sw) * 0.08838834764831845f);
            const float s0 = bf_lo(sv) * 1.4426950408889634f, s1 = bf_hi(sv) * 1.4426950408889634f;
            float m_new = fmaxf(m_run, fmaxf(s0, s1));
            const bool grow = __any_sync(0xffffffffu, (diag && (m_new > m_run)));
            if (lane == 0) mbar_arrive(bar_empty + s * 8);
            if (grow) {
                float al = ex2(m_run - m_new);
                float a0 = __shfl_sync(0xffffffffu, al, src0), a1 = __shfl_sync(0xffffffffu, al, src1);
#pragma unroll
                for (int c = 0; c < 8; c++) { o[c][0] *= a0; o[c][1] *= a1; o[c][2] *= a0; o[c][3] *= a1; }
                l_run *= al;
                m_run = m_new;
            }
            uint32_t pw = pack_bf(ex2(s0 - m_run), ex2(s1 - m_run));
            l_run += bf_lo(pw) + bf_hi(pw);
            uint32_t b0 = odd ? (pw << 16) : (pw & 0xffffu);
            uint32_t b1 = odd ? (pw & 0xffff0000u) : (pw >> 16);
            if (!diag) { b0 = 0u; b1 = 0u; }
            mbar_wait(bar_full + (s + 1) * 8, par);
#pragma unroll
            for (int c = 0; c < 8; c++) {
                uint32_t a[4];
                ldsm4t(a, (base + voff) ^ (c << 4));
                mma16816(o[c], a, b0, b1);
            }
            __syncwarp();
            if (lane == 0) mbar_arrive(bar_empty + (s + 1) * 8);
        }
    }
    PROF(5);
    float acc[4][4];
    uint32_t pa[8][2];
    float rinv;
    {
        const int s = 4 + (warp >> 2);
        mbar_wait(bar_full + s * 8, 1);
        const uint32_t base = sb + OFF_RING + s * TILE_BYTES;
        float sa[4] = {0.f, 0.f, 0.f, 0.f}, sb2[4] = {0.f, 0.f, 0.f, 0.f};
#pragma unroll
        for (int c = 0; c < 8; c += 2) {
            uint32_t a[4], a2[4];
            ldsm4(a, (base + koff) ^ (c << 4));
            ldsm4(a2, (base + koff) ^ ((c + 1) << 4));
            mma16816(sa, a, qf[c][0], qf[c][1]);
            mma16816(sb2, a2, qf[c + 1][0], qf[c + 1][1]);
        }
        const uint32_t sw = pack_bf(odd ? sa[1] + sb2[1] : sa[0] + sb2[0], odd ? sa[3] + sb2[3] : sa[2] + sb2[2]);
        const uint32_t sv = pack_bf(bf_lo(sw) * 0.08838834764831845f, bf_hi(sw) * 0.08838834764831845f);
        const float s0 = bf_lo(sv) * 1.4426950408889634f, s1 = bf_hi(sv) * 1.4426950408889634f;
        int mi_ = __float_as_int(diag ? fmaxf(m_run, fmaxf(s0, s1)) : -INFINITY);
        mi_ ^= (mi_ >> 31) & 0x7fffffff;
        mi_ = __reduce_max_sync(0xffffffffu, mi_);
        mi_ ^= (mi_ >> 31) & 0x7fffffff;
        if (lane == 0) sts32(sb + OFF_ML + warp * 4, mi_);
        bar_cons();
        const float4 m0 = lds_f32x4(sb + OFF_ML), m1 = lds_f32x4(sb + OFF_ML + 16);
        const float mx = fmaxf(fmaxf(fmaxf(m0.x, m0.y), fmaxf(m0.z, m0.w)), fmaxf(fmaxf(m1.x, m1.y), fmaxf(m1.z, m1.w)));
        const float scl = ex2(m_run - mx);
        const uint32_t pw = pack_bf(ex2(s0 - mx), ex2(s1 - mx));
        if (diag) { sts16(sb + SC_P + (warp * 16 + g) * 2, pw); sts16(sb + SC_P + (warp * 16 + g + 8) * 2, pw >> 16); }
        const float lw = warp_sum(diag ? fmaf(l_run, scl, bf_lo(pw) + bf_hi(pw)) : 0.f);
        const float a0 = __shfl_sync(0xffffffffu, scl, src0), a1 = __shfl_sync(0xffffffffu, scl, src1);
        float v[8], u[8];
#pragma unroll
        for (int c = 0; c < 8; c++) {
            v[c] = a0 * o[c][0] + a1 * o[c ^ 1][1];
            u[c] = a0 * o[c][2] + a1 * o[c ^ 1][3];
        }
#pragma unroll
        for (int c = 0; c < 8; c++) {
            if (!(c & 2)) {
                v[c] += __shfl_xor_sync(0xffffffffu, v[c ^ 2], 1);
                u[c] += __shfl_xor_sync(0xffffffffu, u[c ^ 2], 1);
            }
        }
#pragma unroll
        for (int c = 0; c < 2; c++) {
            v[c] += __shfl_xor_sync(0xffffffffu, v[c ^ 4], 2);
            u[c] += __shfl_xor_sync(0xffffffffu, u[c ^ 4], 2);
        }
        const uint32_t dst = sb + SC_OP + (warp * 128 + 16 * t4 + g) * 4;
        sts_f32(dst, v[0]); sts_f32(dst + 32, v[1]); sts_f32(dst + 256, u[0]); sts_f32(dst + 288, u[1]);
        if (lane == 0) sts_f32(sb + OFF_ML + 32 + warp * 4, lw);
        mbar_wait(bar_help, 0);
        bar_cons();
        const float4 l0 = lds_f32x4(sb + OFF_ML + 32), l1 = lds_f32x4(sb + OFF_ML + 48);
        rinv = rcp_fast(((l0.x + l0.y) + (l0.z + l0.w)) + ((l1.x + l1.y) + (l1.z + l1.w)));
#pragma unroll
        for (int i = 0; i < 4; i++) acc[i][0] = acc[i][1] = acc[i][2] = acc[i][3] = 0.f;
#pragma unroll
        for (int w = 0; w < 8; w++) {
            const float2 x0 = lds_f32x2(sb + SC_OP + (w * 128 + 16 * warp + 2 * t4) * 4), x1 = lds_f32x2(sb + SC_OP + (w * 128 + 16 * warp + 8 + 2 * t4) * 4);
            acc[2 * (w & 1)][0] += x0.x; acc[2 * (w & 1)][1] += x0.y;
            acc[2 * (w & 1) + 1][0] += x1.x; acc[2 * (w & 1) + 1][1] += x1.y;
        }
#pragma unroll
        for (int ks = 0; ks < 8; ks++) { pa[ks][0] = lds32(sb + SC_P + (8 * ks + t4) * 4); pa[ks][1] = lds32(sb + SC_P + (8 * ks + 4 + t4) * 4); }
    }
    PROF(20);
    const int mt = warp < 2 ? warp : warp + 2;
    {
        const uint32_t va = pin(sb + OFF_RING + 6 * TILE_BYTES + (warp >> 2) * (TILE_BYTES / 2) + (8 * (mi & 1) + r8) * 128 + (((2 * (warp & 3) + (mi >> 1)) ^ r8) << 4));
        const uint32_t vbar = pin(bar_v + (warp >> 2) * 8);
        uint32_t* const o_dst = pin(slot(SL_O + (cta >> 4), g) + (cta & 15) * 64 + warp * 8 + 2 * t4);
#pragma unroll
        for (int tl = 0; tl < 2; tl++) {
            mbar_wait(vbar + tl * 16, 0);
            uint32_t r[4][4];
#pragma unroll
            for (int ks = 0; ks < 4; ks++) ldsm4t(r[ks], va + tl * TILE_BYTES + ks * 2048);
#pragma unroll
            for (int ks = 0; ks < 4; ks++) {
                const uint32_t a[4] = {pa[4 * tl + ks][0], 0u, pa[4 * tl + ks][1], 0u};
                mma16816(acc[2 * (ks & 1)], a, r[ks][0], r[ks][1]);
                mma16816(acc[2 * (ks & 1) + 1], a, r[ks][2], r[ks][3]);
            }
        }
        stg_relaxed2_if(g < 2, o_dst, ~pack_bf((acc[0][0] + acc[2][0]) * rinv, (acc[0][1] + acc[2][1]) * rinv),
                        ~pack_bf((acc[1][0] + acc[3][0]) * rinv, (acc[1][1] + acc[3][1]) * rinv));
    }
    PROF(7);
    const int side = lds32(sb + OFF_SIDE);
    const uint32_t red_st = pin(sb + SC_E4 + ((warp * 4 + 2 * ((lane >> 3) & 1) + (lane >> 4)) * 8 + (lane & 7)) * 4);
    const uint32_t red_ld = pin(sb + SC_E4 + (lane & 15) * 8);
    const uint32_t* const in1 = pin(slot(SL_P1 + own, side) + tid * 4);
    const uint32_t* const in2a = pin(slot(SL_P2 + 2 * own, side) + tid * 4);
    const uint32_t* const in2b = pin(slot(SL_P2 + 2 * own + 1, side) + tid * 4);
    uint32_t* const out_dst = pin((uint32_t*)(p.out + ((lane >> 2) & 3) * D + 8 * own) + t4);
    uint32_t* const x1_dst = pin(slot(SL_X1 + own / 30, lane >> 4) + (own % 30) * 32 + (lane & 15));
    uint32_t* const rst = pin(tid >= 32 && tid < 56 ? mod_slot(lane >> 2, own, lane & 3) : own < 32 && tid == 64 ? g_clr + own * 4 : own < 16 && tid == 96 ? g_phase + own * 32 : nullptr);
    const uint32_t xw = lds32(sb + OWN_X + (lane & 15) * 4), ga_w = lds32(sb + OWN_GA + (lane & 15) * 4);
    uint32_t cs[15];
    uint32_t* dst2[5];
    uint32_t w2a[5];
#pragma unroll
    for (int j = 0; j < 10; j++) cs[j] = lds32(sb + OFF_VB + ((g & 1) * 4 + (g >> 1)) * VEC_STRIDE + warp * 160 + t4 * 4 + j * 16);
#pragma unroll
    for (int i = 0; i < 5; i++) {
        cs[10 + i] = lds32(sb + OFF_VB + (g >> 1) * VEC_STRIDE + warp * 160 + (g & 1) * 16 + t4 * 4 + i * 32);
        const uint2 t = lds64(sb + OFF_TAB2 + warp * 40 + i * 8);
        dst2[i] = slot_ptr((t4 < 2 ? t.x : t.y) + g * 16 + (t4 & 1) * 8);
        const int cc = 2 * (warp * 5 + i) + (mi & 1);
        w2a[i] = pin(sb + X_W2 + (cc >> 3) * 4096 + (r8 + 8 * (mi >> 1)) * 128 + (((cc & 7) ^ r8) << 4));
    }
    const uint32_t piv = lds32(sb + OFF_STAT + (g >> 1) * 8);
    const uint32_t* const xin = pin(slot(SL_X1 + warp / 3, side) + ((warp % 3) * 10 + (g & 1)) * 32 + (g >> 1) * 4 + t4);
    const uint32_t w1a = pin(sb + X_W1 + (warp * 80 + r8 + 8 * (mi >> 1)) * 64 + (((mi & 1) ^ ((r8 >> 1) & 3)) << 4));
    const uint32_t w1bar = pin(bar_w1 + (warp >> 1) * 8), w2bar = pin(bar_w2 + (warp + (warp >> 2)) * 8);
    const uint32_t wbar = pin(NB_O + warp);
    const uint32_t ab_st = pin(sb + SC_AB + warp * 1024 + lane * 16), y_st = pin(sb + SC_Y + warp * 512 + lane * 8), s_st = pin(sb + SC_ST + (t4 * 8 + warp) * 8);
    const uint32_t h_ld = pin(sb + SC_H1 + ((g & 3) ^ (2 * (f & 1) + ((f >> 1) & 1))) * 64 + t4 * 16);
    {
        const int kap = 2 * (head & 1) + ((head >> 1) & 1);
        const uint32_t wa = pin(sb + X_WO + (mt >> 1) * (DH * 64) + (r8 + 8 * (mi >> 1)) * 64 + ((((mt & 1) * 2 + (mi & 1)) ^ ((r8 >> 1) & 3)) << 4));
        const uint32_t oa = pin(sb + OFF_O + ((g & 3) ^ kap) * O_STRIDE + t4 * 8);
        uint32_t* dst[4];
#pragma unroll
        for (int i = 0; i < 2; i++) {
            const uint2 t = lds64(sb + OFF_TAB1 + (bown * 20 + 2 * mt + (warp < 2 ? 4 * i : 0)) * 4);
            dst[2 * i] = slot_ptr(t.x + g * 16 + t4 * 8);
            dst[2 * i + 1] = slot_ptr(t.y + g * 16 + t4 * 8);
        }
        PROF(6);
        const uint32_t wobar = pin(bar_wo + (mt >> 1) * 8);
        asm volatile("bar.sync %0, 64;" ::"r"(wbar) : "memory");
        uint2 ob[8];
#pragma unroll
        for (int ks = 0; ks < 8; ks++) ob[ks] = lds64(oa + ks * 32);
#pragma unroll
        for (int m = 0; m < 2; m++) {
            if (m == 0 || warp < 2) {
                mbar_wait(wobar + m * 8, 0);
                PROF(8);
                uint32_t wf[8][4];
#pragma unroll
                for (int ks = 0; ks < 8; ks++) ldsm4t(wf[ks], wa + m * (DH * 64) + ks * 1024);
                float c[4][4];
#pragma unroll
                for (int ks = 0; ks < 8; ks++) {
                    if (ks < 4) c[ks][0] = c[ks][1] = c[ks][2] = c[ks][3] = 0.f;
                    mma16816(c[ks & 3], wf[ks], ob[ks].x, ob[ks].y);
                }
                stg_relaxed2_if(t4 < 2, dst[2 * m], flag((c[0][0] + c[1][0]) + (c[2][0] + c[3][0])), flag((c[0][1] + c[1][1]) + (c[2][1] + c[3][1])));
                stg_relaxed2_if(t4 < 2, dst[2 * m + 1], flag((c[0][2] + c[1][2]) + (c[2][2] + c[3][2])), flag((c[0][3] + c[1][3]) + (c[2][3] + c[3][3])));
            }
        }
    }
    PROF(9);
    uint32_t x1w = 0;
    if (is_owner) {
        uint4 v;
        for (int it = 0;; it++) {
            v = ldg_relaxed(in1);
            if (__all_sync(0xffffffffu, and3(and3(v.x, v.y, v.z), v.w, 1u))) break;
            if (it > SPIN_LIMIT) __trap();
        }
        PROF(11);
        const float s0 = __uint_as_float(v.x) + __shfl_xor_sync(0xffffffffu, __uint_as_float(v.z), 8);
        const float s1 = __uint_as_float(v.y) + __shfl_xor_sync(0xffffffffu, __uint_as_float(v.w), 8);
        sts_f32(red_st, s0 + __shfl_xor_sync(0xffffffffu, s1, 16));
        nbar_sync<NB_E4, 256>();
        if (warp == 0) {
            float2 a[8];
#pragma unroll
            for (int w = 0; w < 8; w++) a[w] = lds_f32x2(red_ld + w * 128);
            const uint32_t aw = pack_bf(((a[0].x + a[1].x) + (a[2].x + a[3].x)) + ((a[4].x + a[5].x) + (a[6].x + a[7].x)),
                                        ((a[0].y + a[1].y) + (a[2].y + a[3].y)) + ((a[4].y + a[5].y) + (a[6].y + a[7].y)));
            x1w = bf2_add(xw, bf2_mul(ga_w, aw));
            stg_relaxed(x1_dst, x1w ^ 0x80008000u);
            if (lane == 0) mbar_arrive(bar_x1);
        }
        if (rst) stg_zero4(rst);
    }
    PROF(12);
    if (is_f) {
        uint32_t f1[5][2][4], f2[5][2][4];
        uint32_t d[6];
        auto load_x1 = [&] {
#pragma unroll
            for (int i = 0; i < 5; i++) d[i] = ldg_relaxed32(xin + i * 64);
        };
        auto have_x1 = [&] { return __all_sync(0xffffffffu, __vimin3_u32(__vimin3_u32(d[0], d[1], d[2]), d[3], d[4]) != 0u); };
        mbar_wait(w1bar, 0);
        load_x1();
        {
#pragma unroll
            for (int i = 0; i < 5; i++) { ldsm4t(f1[i][0], w1a + i * 1024); ldsm4t(f1[i][1], (w1a ^ 32) + i * 1024); }
            float c[2][4];
#pragma unroll
            for (int m = 0; m < 2; m++) c[m][0] = c[m][1] = c[m][2] = c[m][3] = 0.f;
#pragma unroll
            for (int i = 0; i < 5; i++) { mma16816(c[0], f1[i][0], cs[2 * i], cs[2 * i + 1]); mma16816(c[1], f1[i][1], cs[2 * i], cs[2 * i + 1]); }
#pragma unroll
            for (int i = 0; i < 5; i++) { cs[2 * i] = pin(odd ? 0u : cs[10 + i]); cs[2 * i + 1] = pin(odd ? cs[10 + i] : 0u); }
#pragma unroll
            for (int m = 0; m < 2; m++) sts128(ab_st + m * 512, make_uint4(__float_as_uint(c[m][0]), __float_as_uint(c[m][1]), __float_as_uint(c[m][2]), __float_as_uint(c[m][3])));
            nbar_arrive<NB_AB, 320>();
            d[0] |= __float_as_uint(c[1][3]) & (side >> 1);
        }
        PROF(10);
#pragma unroll 1
        for (int it = 0; !have_x1(); it++) {
            load_x1();
            if (it > SPIN_LIMIT) __trap();
        }
        PROF(13);
        {
            float y[2][4], st[4] = {0.f, 0.f, 0.f, 0.f};
#pragma unroll
            for (int m = 0; m < 2; m++) y[m][0] = y[m][1] = y[m][2] = y[m][3] = 0.f;
#pragma unroll
            for (int i = 0; i < 5; i++) d[i] = bf2_add(d[i], piv);
            d[5] = 0u;
#pragma unroll
            for (int i = 0; i < 5; i++) {
                if (i < 3) {
                    const uint32_t a[4] = {d[2 * i], 0x3f803f80u, d[2 * i + 1], 0x3f803f80u};
                    mma16816(st, a, d[2 * i], d[2 * i + 1]);
                }
                const uint32_t y0 = bf2_mul(d[i], cs[2 * i]), y1 = bf2_mul(d[i], cs[2 * i + 1]);
                mma16816(y[0], f1[i][0], y0, y1);
                mma16816(y[1], f1[i][1], y0, y1);
            }
            const float q = odd ? st[1] : st[0];
            const float q2 = q + __shfl_xor_sync(0xffffffffu, q, 4);
            if (diag && !odd) sts_f32x2(s_st, q2, st[2] + st[3]);
#pragma unroll
            for (int m = 0; m < 2; m++) sts_f32x2(y_st + m * 256, y[m][0] + y[m][1], y[m][2] + y[m][3]);
        }
        nbar_arrive<NB_Y, 320>();
        PROF(14);
        mbar_wait(w2bar, 0);
        mbar_wait(w2bar + 8, 0);
#pragma unroll
        for (int i = 0; i < 5; i++) { ldsm4t(f2[i][0], w2a[i]); ldsm4t(f2[i][1], w2a[i] + 2048); }
        asm volatile("bar.sync %0, 96;" ::"r"(wbar) : "memory");
        PROF(15);
        {
            const uint4 hb = lds128(h_ld);
            float c[5][4];
#pragma unroll
            for (int i = 0; i < 5; i++) { c[i][0] = c[i][1] = c[i][2] = c[i][3] = 0.f; mma16816(c[i], f2[i][0], hb.x, hb.y); }
#pragma unroll
            for (int i = 0; i < 5; i++) {
                mma16816(c[i], f2[i][1], hb.z, hb.w);
                stg_relaxed2_if(true, dst2[i], flag(t4 < 2 ? c[i][0] : c[i][2]), flag(t4 < 2 ? c[i][1] : c[i][3]));
            }
        }
    }
    PROF(16);
    if (is_owner) {
        const uint32_t b2w = lds32(sb + OWN_B2 + (lane & 15) * 4), gb_ld = pin(sb + OWN_GB + (lane & 15) * 4);
        const bool two = tid < NF * 8 - 256;
        uint4 v, w = make_uint4(1, 1, 1, 1);
        for (int it = 0;; it++) {
            ldg_relaxed_if(two, w, in2b);
            v = ldg_relaxed(in2a);
            if (__all_sync(0xffffffffu, and3(and3(v.x, v.y, v.z), and3(v.w, w.x, w.y), and3(w.z, w.w, 1u)))) break;
            if (it > SPIN_LIMIT) __trap();
        }
        PROF(17);
        const float s0 = (__uint_as_float(v.x) + __uint_as_float(w.x)) + __shfl_xor_sync(0xffffffffu, __uint_as_float(v.z) + __uint_as_float(w.z), 8);
        const float s1 = (__uint_as_float(v.y) + __uint_as_float(w.y)) + __shfl_xor_sync(0xffffffffu, __uint_as_float(v.w) + __uint_as_float(w.w), 8);
        sts_f32(red_st + (SC_E6 - SC_E4), s0 + __shfl_xor_sync(0xffffffffu, s1, 16));
        if (warp != 0) {
            nbar_arrive<NB_E6, 288>();
        } else {
            nbar_sync<NB_E6, 288>();
            float2 a[8];
#pragma unroll
            for (int i = 0; i < 8; i++) a[i] = lds_f32x2(red_ld + (SC_E6 - SC_E4) + i * 128);
            const uint32_t gb_w = lds32(gb_ld);
            const uint32_t aw = pack_bf(((a[0].x + a[1].x) + (a[2].x + a[3].x)) + ((a[4].x + a[5].x) + (a[6].x + a[7].x)),
                                        ((a[0].y + a[1].y) + (a[2].y + a[3].y)) + ((a[4].y + a[5].y) + (a[6].y + a[7].y)));
            x1w = bf2_add(x1w, bf2_mul(gb_w, bf2_add(aw, b2w)));
            if (lane < 16) asm volatile("st.global.u32 [%0], %1;" ::"l"(out_dst), "r"(x1w) : "memory");
        }
    }
    PROF(18);
    PROF_DUMP;
}

typedef CUresult (*EncodeFn)(CUtensorMap*, CUtensorMapDataType, cuuint32_t, void*, const cuuint64_t*, const cuuint64_t*, const cuuint32_t*,
                             const cuuint32_t*, CUtensorMapInterleave, CUtensorMapSwizzle, CUtensorMapL2promotion, CUtensorMapFloatOOBfill);

static CUtensorMap make_map(EncodeFn enc, const void* ptr, int cols, int rows, int box_cols, int box_rows, CUtensorMapSwizzle sw,
                            CUtensorMapL2promotion promo = CU_TENSOR_MAP_L2_PROMOTION_NONE) {
    CUtensorMap m;
    cuuint64_t dims[2] = {(cuuint64_t)cols, (cuuint64_t)rows};
    cuuint64_t strides[1] = {(cuuint64_t)cols * 2};
    cuuint32_t box[2] = {(cuuint32_t)box_cols, (cuuint32_t)box_rows};
    cuuint32_t es[2] = {1, 1};
    enc(&m, CU_TENSOR_MAP_DATA_TYPE_BFLOAT16, 2, const_cast<void*>(ptr), dims, strides, box, es, CU_TENSOR_MAP_INTERLEAVE_NONE, sw,
        promo, CU_TENSOR_MAP_FLOAT_OOB_FILL_NONE);
    return m;
}

}

extern "C" void kernel_launch(void* const* d_in, const int* in_sizes, int n_in, void* d_out, int out_size) {
    (void)in_sizes; (void)n_in; (void)out_size;
    static EncodeFn enc = nullptr;
    if (!enc) {
        void* fn = nullptr;
        cudaDriverEntryPointQueryResult qr;
        cudaGetDriverEntryPoint("cuTensorMapEncodeTiled", &fn, cudaEnableDefault, &qr);
        enc = (EncodeFn)fn;
        cudaFuncSetAttribute(fused_kernel, cudaFuncAttributeMaxDynamicSharedMemorySize, SMEM_BYTES);
    }
    Params p;
    p.x = (const __nv_bfloat16*)d_in[0];
    p.kc = (const __nv_bfloat16*)d_in[1];
    p.vc = (const __nv_bfloat16*)d_in[2];
    p.b1 = (const __nv_bfloat16*)d_in[7];
    p.b2 = (const __nv_bfloat16*)d_in[9];
    p.c = (const __nv_bfloat16*)d_in[10];
    p.out = (__nv_bfloat16*)d_out;
    CUtensorMap tm_wmod = make_map(enc, d_in[11], NMOD, D, 32, 160, CU_TENSOR_MAP_SWIZZLE_64B, CU_TENSOR_MAP_L2_PROMOTION_L2_128B);
    CUtensorMap tm_wq = make_map(enc, d_in[3], NH * DH, D, 32, 160, CU_TENSOR_MAP_SWIZZLE_64B, CU_TENSOR_MAP_L2_PROMOTION_L2_128B);
    CUtensorMap tm_wo = make_map(enc, d_in[4], D, NH * DH, 32, 128, CU_TENSOR_MAP_SWIZZLE_64B);
    CUtensorMap tm_w1 = make_map(enc, d_in[6], FF, D, 32, 160, CU_TENSOR_MAP_SWIZZLE_64B);
    CUtensorMap tm_w2 = make_map(enc, d_in[8], D, FF, 64, 32, CU_TENSOR_MAP_SWIZZLE_128B);
    CUtensorMap tm_v = make_map(enc, d_in[2], DH, NB * NH * SK, 64, TILE_KEYS, CU_TENSOR_MAP_SWIZZLE_128B);
    CUtensorMap tm_gb = make_map(enc, d_in[11], NMOD, D, 8, 160, CU_TENSOR_MAP_SWIZZLE_NONE, CU_TENSOR_MAP_L2_PROMOTION_L2_128B);
    fused_kernel<<<NCTA, NTHREADS, SMEM_BYTES>>>(p, tm_wmod, tm_wq, tm_wo, tm_w1, tm_w2, tm_v, tm_gb);
}
```

```cpp
#include <cuda_runtime.h>
#include <cuda.h>
#include <cuda_bf16.h>
#include <stdint.h>
#include <stdlib.h>

namespace {

constexpr int NB = 4, D = 640, NH = 32, DH = 128, SK = 8192, WIN = 2048, FF = 1728, NMOD = 6 * D;
constexpr int NCTA = 128;
constexpr int NOWN = 80;
constexpr int NF = 54;
constexpr int NTHREADS = 320;
constexpr int TILE_KEYS = 64;
constexpr int TILE_BYTES = TILE_KEYS * DH * 2;
constexpr int NITEM = 2 * WIN / TILE_KEYS;
constexpr int NS = 8;
constexpr int NMODC = 120;
constexpr int SPIN_LIMIT = 1 << 18;
#define INFLIGHT 3
#define WQ_DELAY 500
#define MOD_T 4200
#define Q_PAUSE 1100
#define PACE_A 7500
#define PACE_TAU 635
#define ROT(c) 0
#define PF_END 16
#define PH_FIRST 20
#define PH_LAG 5
#define LAT_T 2400
#define WO_T -950
#define WO_S 250
#define W1_T 950
#define W2_T 1650
#define GB_T 2500
#define GB_EV 300
#define CLR_CHECK 28000
constexpr int NPROBE = 8, PROBE_END = 10000;
constexpr int SEG_J = 8;

constexpr int OFF_RING = 0;
constexpr int OFF_X = OFF_RING + NS * TILE_BYTES;
constexpr int X_WM = OFF_X;
constexpr int X_WQ = OFF_X + D * 64;
constexpr int X_WO = OFF_X;
constexpr int X_W1 = X_WO + 5 * DH * 64;
constexpr int X_END = X_W1 + D * 64;
constexpr int X_W2 = OFF_RING;
constexpr int X_GB = OFF_RING + 3 * TILE_BYTES;
static_assert(X_WQ + D * 64 <= X_END, "prologue weights must fit");
constexpr int VEC_STRIDE = 1296;
constexpr int OFF_VA = X_END;
constexpr int OFF_VB = OFF_VA + 4 * VEC_STRIDE;
constexpr int OFF_RED = OFF_VB + 4 * VEC_STRIDE;
constexpr int OFF_ML = OFF_RED + 4 * VEC_STRIDE;
constexpr int O_STRIDE = 288;
constexpr int OFF_O = OFF_ML + 64;
constexpr int OFF_Q = OFF_O + 4 * O_STRIDE;
constexpr int OFF_OWN = OFF_Q + 256;
constexpr int OWN_X = OFF_OWN, OWN_B2 = OWN_X + 64, OWN_GA = OWN_B2 + 64, OWN_GB = OWN_GA + 64, OWN_B1 = OWN_GB + 64;
constexpr int OFF_STAT = OWN_B1 + 128;
constexpr int OFF_TAB1 = OFF_STAT + 32;
constexpr int OFF_TAB2 = OFF_TAB1 + NOWN * 4;
constexpr int OFF_SIDE = OFF_TAB2 + NOWN * 4;
constexpr int OFF_BAR = OFF_SIDE + 8;
constexpr int NBAR = 2 * NS + 32;
constexpr int SMEM_BYTES = OFF_BAR + NBAR * 8;
constexpr int SC_OP = OFF_RING + 4 * TILE_BYTES;
constexpr int SC_AB = SC_OP + 4096;
constexpr int SC_Y = SC_AB + 8192;
constexpr int SC_ST = SC_Y + 4096;
constexpr int SC_E4 = SC_ST + 256;
constexpr int SC_E6 = SC_E4 + 1024;
constexpr int SC_P = SC_E6 + 1024;
constexpr int SC_H1 = SC_P + 256;
static_assert(SMEM_BYTES <= 232448, "smem");
static_assert(OFF_BAR % 8 == 0 && OFF_X % 1024 == 0 && X_WQ % 512 == 0 && X_W1 % 512 == 0 && OFF_VA % 16 == 0 && OFF_RED % 16 == 0 && OFF_ML % 16 == 0 && OFF_O % 16 == 0 && OFF_Q % 16 == 0, "align");
constexpr int NB_O = 2  , NB_E4 = 10, NB_E6 = 11, NB_AB = 12, NB_Y = 13;

__device__ __align__(128) uint32_t g_mod[NMODC * 64];
__device__ __align__(128) uint32_t g_q[NCTA * 128];
__device__ uint32_t g_clr[NCTA];
__device__ uint32_t g_phase[16 * 32];
constexpr int SL_P1 = 0;
constexpr int SL_P2 = SL_P1 + NOWN;
constexpr int SL_O = SL_P2 + 2 * NOWN;
constexpr int SL_X1 = SL_O + 8;
constexpr int SL_SIDE = SL_X1 + 3;
static_assert(SL_SIDE < 256, "one 2 MB page");
__device__ uint32_t g_slots[2 * 256 * 2048];
__device__ __forceinline__ uint32_t* slot(int i, int side) {
    const size_t base = ((size_t)g_slots + 0x1fffff) & ~(size_t)0x1fffff;
    return (uint32_t*)base + i * 2048 + (((__popc(i & 0x59) ^ side) & 1) << 10);
}
#define PROF_DECL
#define HPROF(i) do { } while (0)
#define PROF(i) do { } while (0)
#define PROF_DUMP do { } while (0)

__device__ __forceinline__ uint32_t smem_u32(const void* p) { return (uint32_t)__cvta_generic_to_shared(p); }
__device__ __forceinline__ void mbar_init(uint32_t bar, uint32_t cnt) { asm volatile("mbarrier.init.shared::cta.b64 [%0], %1;" ::"r"(bar), "r"(cnt) : "memory"); }
__device__ __forceinline__ void mbar_expect_tx(uint32_t bar, uint32_t bytes) { asm volatile("mbarrier.arrive.expect_tx.shared::cta.b64 _, [%0], %1;" ::"r"(bar), "r"(bytes) : "memory"); }
__device__ __forceinline__ void mbar_arrive(uint32_t bar) { asm volatile("mbarrier.arrive.shared::cta.b64 _, [%0];" ::"r"(bar) : "memory"); }
__device__ __forceinline__ void mbar_wait(uint32_t bar, uint32_t parity) {
    uint32_t ok;
    int it = 0;
    while (true) {
        asm volatile("{\n.reg .pred p;\nmbarrier.try_wait.parity.shared::cta.b64 p, [%1], %2;\nselp.u32 %0, 1, 0, p;\n}" : "=r"(ok) : "r"(bar), "r"(parity) : "memory");
        if (ok) break;
        if (++it > SPIN_LIMIT) __trap();
    }
}
__device__ __forceinline__ void bulk_load(uint32_t dst, const void* src, uint32_t bytes, uint32_t bar, uint64_t pol) {
    asm volatile("cp.async.bulk.shared::cluster.global.mbarrier::complete_tx::bytes.L2::cache_hint [%0], [%1], %2, [%3], %4;"
                 ::"r"(dst), "l"(src), "r"(bytes), "r"(bar), "l"(pol) : "memory");
}
__device__ __forceinline__ void bar_cons() { asm volatile("bar.sync 1, 256;" ::: "memory"); }
template <int ID, int N> __device__ __forceinline__ void nbar_sync() { asm volatile("bar.sync %0, %1;" ::"n"(ID), "n"(N) : "memory"); }
template <int ID, int N> __device__ __forceinline__ void nbar_arrive() { asm volatile("bar.arrive %0, %1;" ::"n"(ID), "n"(N) : "memory"); }
__device__ __forceinline__ bool mbar_test(uint32_t bar, uint32_t parity) {
    uint32_t ok;
    asm volatile("{\n.reg .pred p;\nmbarrier.test_wait.parity.shared::cta.b64 p, [%1], %2;\nselp.u32 %0, 1, 0, p;\n}" : "=r"(ok) : "r"(bar), "r"(parity) : "memory");
    return ok;
}
__device__ __forceinline__ uint32_t pin(uint32_t v) { asm volatile("" : "+r"(v)); return v; }
template <class T> __device__ __forceinline__ T pin_hard(T v) { return __shfl_sync(0xffffffffu, v, threadIdx.x & 31); }
template <class T> __device__ __forceinline__ T* pin(T* v) { asm volatile("" : "+l"(v)); return v; }
__device__ __forceinline__ void ldsm4(uint32_t (&a)[4], uint32_t addr) {
    asm volatile("ldmatrix.sync.aligned.m8n8.x4.shared.b16 {%0,%1,%2,%3}, [%4];" : "=r"(a[0]), "=r"(a[1]), "=r"(a[2]), "=r"(a[3]) : "r"(addr) : "memory");
}
__device__ __forceinline__ void ldsm4t(uint32_t (&a)[4], uint32_t addr) {
    asm volatile("ldmatrix.sync.aligned.m8n8.x4.trans.shared.b16 {%0,%1,%2,%3}, [%4];" : "=r"(a[0]), "=r"(a[1]), "=r"(a[2]), "=r"(a[3]) : "r"(addr) : "memory");
}
__device__ __forceinline__ void mma16816(float (&c)[4], const uint32_t (&a)[4], uint32_t b0, uint32_t b1) {
    asm volatile("mma.sync.aligned.m16n8k16.row.col.f32.bf16.bf16.f32 {%0,%1,%2,%3}, {%4,%5,%6,%7}, {%8,%9}, {%0,%1,%2,%3};"
                 : "+f"(c[0]), "+f"(c[1]), "+f"(c[2]), "+f"(c[3]) : "r"(a[0]), "r"(a[1]), "r"(a[2]), "r"(a[3]), "r"(b0), "r"(b1));
}
__device__ __forceinline__ uint32_t lds32(uint32_t addr) { uint32_t v; asm volatile("ld.shared.u32 %0, [%1];" : "=r"(v) : "r"(addr) : "memory"); return v; }
__device__ __forceinline__ float lds_f32(uint32_t addr) { float v; asm volatile("ld.shared.f32 %0, [%1];" : "=f"(v) : "r"(addr) : "memory"); return v; }
__device__ __forceinline__ float2 lds_f32x2(uint32_t addr) { float2 v; asm volatile("ld.shared.v2.f32 {%0,%1}, [%2];" : "=f"(v.x), "=f"(v.y) : "r"(addr) : "memory"); return v; }
__device__ __forceinline__ float4 lds_f32x4(uint32_t addr) { float4 v; asm volatile("ld.shared.v4.f32 {%0,%1,%2,%3}, [%4];" : "=f"(v.x), "=f"(v.y), "=f"(v.z), "=f"(v.w) : "r"(addr) : "memory"); return v; }
__device__ __forceinline__ uint2 lds64(uint32_t addr) { uint2 v; asm volatile("ld.shared.v2.u32 {%0,%1}, [%2];" : "=r"(v.x), "=r"(v.y) : "r"(addr) : "memory"); return v; }
__device__ __forceinline__ uint4 lds128(uint32_t addr) { uint4 v; asm volatile("ld.shared.v4.u32 {%0,%1,%2,%3}, [%4];" : "=r"(v.x), "=r"(v.y), "=r"(v.z), "=r"(v.w) : "r"(addr) : "memory"); return v; }
__device__ __forceinline__ void sts16(uint32_t addr, uint32_t v) { asm volatile("st.shared.b16 [%0], %1;" ::"r"(addr), "h"((unsigned short)v) : "memory"); }
__device__ __forceinline__ void sts32(uint32_t addr, uint32_t v) { asm volatile("st.shared.u32 [%0], %1;" ::"r"(addr), "r"(v) : "memory"); }
__device__ __forceinline__ void sts_f32(uint32_t addr, float v) { asm volatile("st.shared.f32 [%0], %1;" ::"r"(addr), "f"(v) : "memory"); }
__device__ __forceinline__ void sts_f32x2(uint32_t addr, float a, float b) { asm volatile("st.shared.v2.f32 [%0], {%1,%2};" ::"r"(addr), "f"(a), "f"(b) : "memory"); }
__device__ __forceinline__ void sts128(uint32_t addr, uint4 v) { asm volatile("st.shared.v4.u32 [%0], {%1,%2,%3,%4};" ::"r"(addr), "r"(v.x), "r"(v.y), "r"(v.z), "r"(v.w) : "memory"); }
__device__ __forceinline__ uint4 ldg_relaxed(const uint32_t* p) {
    uint4 v;
    asm volatile("ld.relaxed.gpu.global.v4.u32 {%0,%1,%2,%3}, [%4];" : "=r"(v.x), "=r"(v.y), "=r"(v.z), "=r"(v.w) : "l"(p) : "memory");
    return v;
}
__device__ __forceinline__ void ldg_relaxed_if(bool on, uint4& v, const uint32_t* p) {
    asm volatile("{\n.reg .pred q;\nsetp.ne.u32 q, %5, 0;\n@q ld.relaxed.gpu.global.v4.u32 {%0,%1,%2,%3}, [%4];\n}"
                 : "+r"(v.x), "+r"(v.y), "+r"(v.z), "+r"(v.w) : "l"(p), "r"((uint32_t)on) : "memory");
}
__device__ __forceinline__ void stg_relaxed2_if(bool on, uint32_t* p, uint32_t a, uint32_t b) {
    asm volatile("{\n.reg .pred q;\nsetp.ne.u32 q, %3, 0;\n@q st.relaxed.gpu.global.v2.u32 [%0], {%1,%2};\n}" ::"l"(p), "r"(a), "r"(b), "r"((uint32_t)on) : "memory");
}
__device__ __forceinline__ uint32_t ldg_relaxed32(const uint32_t* p) { uint32_t v; asm volatile("ld.relaxed.gpu.global.u32 %0, [%1];" : "=r"(v) : "l"(p) : "memory"); return v; }
__device__ __forceinline__ void stg_relaxed(uint32_t* p, uint32_t v) { asm volatile("st.relaxed.gpu.global.u32 [%0], %1;" ::"l"(p), "r"(v) : "memory"); }
__device__ __forceinline__ void stg_zero4(uint32_t* p) { asm volatile("st.relaxed.gpu.global.v4.u32 [%0], {%1,%1,%1,%1};" ::"l"(p), "r"(0u) : "memory"); }
__device__ __forceinline__ bool ready(const uint4& v) { return (v.x != 0u) & (v.y != 0u) & (v.z != 0u) & (v.w != 0u); }
__device__ __forceinline__ uint32_t min4(const uint4& v) { return min(__vimin3_u32(v.x, v.y, v.z), v.w); }
__device__ __forceinline__ uint4 inv4(const uint4& v) { return make_uint4(~v.x, ~v.y, ~v.z, ~v.w); }
__device__ __forceinline__ uint32_t pack_bf(float lo, float hi) {
    uint32_t r;
    asm("cvt.rn.bf16x2.f32 %0, %1, %2;" : "=r"(r) : "f"(hi), "f"(lo));
    return r;
}
__device__ __forceinline__ float bfr(float x) { return __uint_as_float(pack_bf(0.f, x) & 0xffff0000u); }
__device__ __forceinline__ float bf_lo(uint32_t w) { return __uint_as_float(w << 16); }
__device__ __forceinline__ float bf_hi(uint32_t w) { return __uint_as_float(w & 0xffff0000u); }
__device__ __forceinline__ float bf2f(__nv_bfloat16 v) { return __bfloat162float(v); }
__device__ __forceinline__ float ex2(float x) { float y; asm("ex2.approx.ftz.f32 %0, %1;" : "=f"(y) : "f"(x)); return y; }
__device__ __forceinline__ float rcp_fast(float x) { float y; asm("rcp.approx.ftz.f32 %0, %1;" : "=f"(y) : "f"(x)); return y; }
__device__ __forceinline__ float rsqrt_fast(float x) { float y; asm("rsqrt.approx.ftz.f32 %0, %1;" : "=f"(y) : "f"(x)); return y; }
__device__ __forceinline__ float sqrt_fast(float x) { float y; asm("sqrt.approx.f32 %0, %1;" : "=f"(y) : "f"(x)); return y; }
__device__ __forceinline__ uint32_t bf2_add(uint32_t a, uint32_t b) { uint32_t r; asm("add.rn.bf16x2 %0, %1, %2;" : "=r"(r) : "r"(a), "r"(b)); return r; }
__device__ __forceinline__ uint32_t bf2_sub(uint32_t a, uint32_t b) { uint32_t r; asm("sub.rn.bf16x2 %0, %1, %2;" : "=r"(r) : "r"(a), "r"(b)); return r; }
__device__ __forceinline__ uint32_t bf2_mul(uint32_t a, uint32_t b) { uint32_t r; asm("mul.rn.bf16x2 %0, %1, %2;" : "=r"(r) : "r"(a), "r"(b)); return r; }
__device__ __forceinline__ uint32_t gtime32() { uint32_t c; asm volatile("mov.u32 %0, %%globaltimer_lo;" : "=r"(c)); return c; }
__device__ __forceinline__ uint32_t clock32() { uint32_t c; asm volatile("mov.u32 %0, %%clock;" : "=r"(c)); return c; }

__device__ __forceinline__ float warp_sum(float v) {
#pragma unroll
    for (int o = 16; o > 0; o >>= 1) v += __shfl_xor_sync(0xffffffffu, v, o);
    return v;
}

struct Params {
    const __nv_bfloat16 *x, *kc, *vc, *b1, *b2, *c;
    __nv_bfloat16* out;
};

__device__ __forceinline__ void tma2d(uint32_t dst, const CUtensorMap* tm, int x, int y, uint32_t bar) {
    asm volatile("cp.async.bulk.tensor.2d.shared::cluster.global.mbarrier::complete_tx::bytes [%0], [%1, {%2, %3}], [%4];"
                 ::"r"(dst), "l"(tm), "r"(x), "r"(y), "r"(bar) : "memory");
}

__device__ __forceinline__ void tma2d_hint(uint32_t dst, const CUtensorMap* tm, int x, int y, uint32_t bar, uint64_t pol) {
    asm volatile("cp.async.bulk.tensor.2d.shared::cluster.global.mbarrier::complete_tx::bytes.L2::cache_hint [%0], [%1, {%2, %3}], [%4], %5;"
                 ::"r"(dst), "l"(tm), "r"(x), "r"(y), "r"(bar), "l"(pol) : "memory");
}
__device__ __forceinline__ uint32_t flag(float v) { return __float_as_uint(v) | 1u; }
__device__ __forceinline__ uint32_t and3(uint32_t a, uint32_t b, uint32_t c) { uint32_t r; asm("lop3.b32 %0, %1, %2, %3, 0x80;" : "=r"(r) : "r"(a), "r"(b), "r"(c)); return r; }
__device__ __forceinline__ uint32_t* slot_ptr(uint32_t lo) {
    uint32_t* r;
    asm volatile("mov.b64 %0, {%1, %2};" : "=l"(r) : "r"(lo), "r"((uint32_t)((size_t)slot(0, 0) >> 32)));
    return r;
}

__device__ __forceinline__ void load_bfrag(uint32_t vec, int stride, int k0, int g, int t, uint32_t& b0, uint32_t& b1) {
    uint32_t a = vec + (g & 3) * stride + (k0 + 2 * t) * 2;
    b0 = lds32(a);
    b1 = lds32(a + 16);
}

__device__ __forceinline__ void ln_finish(float pivot, float sum, float sumsq, uint32_t& m2, float& rden) {
    float dm = sum * (1.f / D);
    float var = fmaxf(sumsq * (1.f / D) - dm * dm, 0.f);
    float mean = pivot + dm;
    m2 = pack_bf(mean, mean);
    rden = rcp_fast(bfr(sqrt_fast(bfr(bfr(var) + 1e-5f))));
}
__device__ __forceinline__ uint32_t ln_mod_pair(uint32_t xw, uint32_t cw, uint32_t sw, uint32_t m2, float rden) {
    uint32_t d = bf2_sub(xw, m2);
    uint32_t ln = pack_bf(bf_lo(d) * rden, bf_hi(d) * rden);
    return bf2_add(bf2_mul(ln, bf2_add(cw, 0x3f803f80u)), sw);
}
__device__ __forceinline__ uint4 ln_mod4(const uint4& x, const uint4& c, const uint4& s, uint32_t m2, float rden) {
    return make_uint4(ln_mod_pair(x.x, c.x, s.x, m2, rden), ln_mod_pair(x.y, c.y, s.y, m2, rden),
                      ln_mod_pair(x.z, c.z, s.z, m2, rden), ln_mod_pair(x.w, c.w, s.w, m2, rden));
}
__device__ __forceinline__ void acc_stats(const uint4& v, float pv, float& s, float& q) {
    const float a0 = bf_lo(v.x) - pv, a1 = bf_hi(v.x) - pv, a2 = bf_lo(v.y) - pv, a3 = bf_hi(v.y) - pv;
    const float a4 = bf_lo(v.z) - pv, a5 = bf_hi(v.z) - pv, a6 = bf_lo(v.w) - pv, a7 = bf_hi(v.w) - pv;
    s += ((a0 + a1) + (a2 + a3)) + ((a4 + a5) + (a6 + a7));
    q += (fmaf(a0, a0, a1 * a1) + fmaf(a2, a2, a3 * a3)) + (fmaf(a4, a4, a5 * a5) + fmaf(a6, a6, a7 * a7));
}
__device__ __forceinline__ uint32_t* mod_slot(int kind, int j, int b) { return g_mod + (kind * 20 + (j >> 2)) * 64 + b * 16 + (j & 3) * 4; }

template <int N>
__device__ __forceinline__ void poll_n(uint4 (&v)[N], const uint32_t* const* ptr, const bool* on) {
    bool pend[N];
#pragma unroll
    for (int i = 0; i < N; i++) pend[i] = on[i];
    int it = 0;
    while (true) {
#pragma unroll
        for (int i = 0; i < N; i++) if (pend[i]) v[i] = ldg_relaxed(ptr[i]);
        bool any = false;
#pragma unroll
        for (int i = 0; i < N; i++) { pend[i] = pend[i] && !ready(v[i]); any |= pend[i]; }
        if (!__any_sync(0xffffffffu, any)) break;
        if (++it > SPIN_LIMIT) __trap();
    }
#pragma unroll
    for (int i = 0; i < N; i++) v[i] = inv4(v[i]);
}
__device__ __forceinline__ uint4 poll1(const uint32_t* p, bool on) {
    uint4 v[1] = {make_uint4(0, 0, 0, 0)};
    const uint32_t* const ptr[1] = {p};
    const bool o[1] = {on};
    poll_n<1>(v, ptr, o);
    return v[0];
}

__device__ __forceinline__ void gelu_stage(uint32_t sb, int m, int lane) {
    const int g = lane >> 2, b = lane & 3;
    const uint32_t y_ld = pin_hard(sb + SC_Y + m * 256 + lane * 8), s_ld = pin_hard(sb + SC_ST + b * 64);
    const uint32_t h_st = pin_hard(sb + SC_H1 + b * 64 + (g >> 1) * 16 + m * 8 + (g & 1) * 2);
    float a0 = 0.f, b0 = lds_f32(sb + OWN_B1 + (16 * m + g) * 4), a1 = 0.f, b1 = lds_f32(sb + OWN_B1 + (16 * m + g + 8) * 4);
    const float piv = bf_hi(lds32(sb + OFF_STAT + b * 8));
    nbar_sync<NB_AB, 320>();
#pragma unroll
    for (int w = 0; w < 8; w++) {
        const float4 t = lds_f32x4(sb + SC_AB + w * 1024 + m * 512 + lane * 16);
        a0 += t.x; b0 += t.y; a1 += t.z; b1 += t.w;
    }
    sts128(sb + SC_AB + m * 512 + lane * 16, make_uint4(__float_as_uint(a0), __float_as_uint(b0), __float_as_uint(a1), __float_as_uint(b1)));
    nbar_sync<NB_Y, 320>();
    float4 q[4];
    float2 y[8];
#pragma unroll
    for (int i = 0; i < 4; i++) q[i] = lds_f32x4(s_ld + i * 16);
#pragma unroll
    for (int w = 0; w < 8; w++) y[w] = lds_f32x2(y_ld + w * 512);
    const float dm = (((q[0].y + q[0].w) + (q[1].y + q[1].w)) + ((q[2].y + q[2].w) + (q[3].y + q[3].w))) * (1.f / D);
    const float sq = ((q[0].x + q[0].z) + (q[1].x + q[1].z)) + ((q[2].x + q[2].z) + (q[3].x + q[3].z));
    const float r = rsqrt_fast(fmaxf(fmaf(-dm, dm, fmaf(sq, 1.f / D, 1e-5f)), 1e-5f));
    const float y0 = ((y[0].x + y[1].x) + (y[2].x + y[3].x)) + ((y[4].x + y[5].x) + (y[6].x + y[7].x));
    const float y1 = ((y[0].y + y[1].y) + (y[2].y + y[3].y)) + ((y[4].y + y[5].y) + (y[6].y + y[7].y));
    const float dmr = piv - bfr(piv - dm);
    const float u0 = fmaf(r, fmaf(dmr, a0, -y0), b0), u1 = fmaf(r, fmaf(dmr, a1, -y1), b1);
    const float e0 = ex2(u0 * fmaf(u0 * u0, -0.044715f * 2.302208198144325f, -2.302208198144325f));
    const float e1 = ex2(u1 * fmaf(u1 * u1, -0.044715f * 2.302208198144325f, -2.302208198144325f));
    sts16(h_st, pack_bf(u0 * rcp_fast(1.f + e0), 0.f));
    sts16(h_st + 4, pack_bf(u1 * rcp_fast(1.f + e1), 0.f));
#pragma unroll
    for (int w = 0; w < 8; w++) asm volatile("bar.arrive %0, 96;" ::"r"(NB_O + w) : "memory");
}

struct Roles { bool is_f, is_owner; int f, own; };
__device__ __forceinline__ Roles roles(int cta) {
    Roles r;
    r.f = (cta * 27) >> 6;
    r.is_f = (((cta + 1) * 27) >> 6) != r.f;
    r.is_owner = !r.is_f || r.f % 9 == 4;
    r.own = r.is_f ? 74 + r.f / 9 : cta - r.f;
    return r;
}

__global__ void __launch_bounds__(NTHREADS, 1)
fused_kernel(const Params p, const __grid_constant__ CUtensorMap tm_wmod, const __grid_constant__ CUtensorMap tm_wq,
             const __grid_constant__ CUtensorMap tm_wo, const __grid_constant__ CUtensorMap tm_w1, const __grid_constant__ CUtensorMap tm_w2,
             const __grid_constant__ CUtensorMap tm_v, const __grid_constant__ CUtensorMap tm_gb) {
    extern __shared__ __align__(1024) unsigned char smem[];
    const uint32_t t_start = gtime32();
    if (threadIdx.x == 0) {
        const uint32_t c_ = blockIdx.x;
        const uint32_t off = ((c_ & 3) << 26) + (c_ >> 2) * (1u << 21) + (ROT(c_) << 14) + (SK - WIN) * DH * 2;
        asm volatile("cp.async.bulk.prefetch.L2.global.L2::cache_hint [%0], %1, %2;" ::"l"((const char*)p.kc + off), "r"(TILE_BYTES), "l"(0x12f0000000000000ull  ) : "memory");
    }
    const uint32_t sb = smem_u32(smem);
    const int cta = blockIdx.x;
    const int head = cta >> 2, bown = cta & 3;
    const int rot = ROT(cta);
    const char* const kb = (const char*)(p.kc + ((size_t)(bown * NH + head) * SK + (SK - WIN)) * DH);
    uint64_t pol = 0;
    if (threadIdx.x == 256) {
        mbar_init(sb + OFF_BAR, 1);
        asm volatile("fence.mbarrier_init.release.cluster;" ::: "memory");
        asm volatile("createpolicy.fractional.L2::evict_first.b64 %0, 1.0;" : "=l"(pol));
        mbar_expect_tx(sb + OFF_BAR, TILE_BYTES);
        bulk_load(sb + OFF_RING, kb + (size_t)rot * TILE_BYTES, TILE_BYTES, sb + OFF_BAR, pol);
        if ((((head + 1) * 5) >> 4) != ((head * 5) >> 4)) {
            const uint32_t bar = sb + OFF_BAR + 2 * NS * 8;
            mbar_init(bar, 1);
            asm volatile("fence.mbarrier_init.release.cluster;" ::: "memory");
            mbar_expect_tx(bar, D * 64);
#pragma unroll 1
            for (int r = 0; r < D; r += 160) tma2d(sb + X_WM + r * 64, &tm_wmod, 32 * (((head * 5) >> 4) * 4 + bown), r, bar);
        }
    }
    const uint32_t bar_full = sb + OFF_BAR, bar_empty = bar_full + NS * 8;
    const uint32_t bar_wm = bar_empty + NS * 8, bar_wq = bar_wm + 8, bar_xfree = bar_wq + 8, bar_wo = bar_xfree + 8  ;
    const uint32_t bar_w1 = bar_wo + 40  , bar_w2 = bar_w1 + 32  , bar_help = bar_w2 + 80, bar_v = bar_help + 8  ;
    const uint32_t bar_gb = bar_v + 32  , bar_x1 = bar_gb + 32;
    const int tid = threadIdx.x, warp = tid >> 5, lane = tid & 31;
    const Roles role = roles(cta);
    const bool is_f = role.is_f, is_owner = role.is_owner;
    const int f = role.f, own = role.own;
    const bool crit = (((head + 1) * 5) >> 4) != ((head * 5) >> 4);
    const int mr = cta - ((head * 5) >> 4) * 4, mq = ((head * 5) >> 4) * 4 + bown;
    const int ml = mr * 31 / 44;
    const bool late = !crit && (mr + 1) * 31 / 44 != ml;
    const int mc = crit ? mq : ml < 60 ? 40 + ml : 58 + ml;
    const bool gb_own = is_owner && own < 72;

    PROF_DECL
    PROF(0);
    uint4 xa = make_uint4(0, 0, 0, 0), xb = xa, ca0 = xa, ca1 = xa, xs[3] = {xa, xa, xa};
    uint32_t own0 = 0;
    __nv_bfloat16 own2 = __float2bfloat16(0.f);
    if (warp < 8) {
        xa = *(const uint4*)(p.x + (tid & 3) * D + (tid >> 2) * 8);
        ca0 = ((const uint4*)p.c)[tid];
        if (tid < 64) { xb = *(const uint4*)(p.x + (tid & 3) * D + (64 + (tid >> 2)) * 8); ca1 = ((const uint4*)p.c)[256 + tid]; }
        if (warp < 4) {
#pragma unroll
            for (int i = 0; i < 3; i++) if (lane + 32 * i < 80) xs[i] = ((const uint4*)p.x)[warp * 80 + lane + 32 * i];
        } else if (warp == 4) {
            if (is_owner) own0 = *(const uint32_t*)((lane < 16 ? p.x + (lane >> 2) * D : p.b2) + 8 * own + 2 * (lane & 3));
            if (is_f) own2 = p.b1[32 * f + lane];
        }
    }
    const char* const vb = (const char*)(p.vc + ((size_t)(bown * NH + head) * SK + (SK - WIN)) * DH);
    const uint32_t bar_first = crit ? bar_wm : bar_wq;
    if (threadIdx.x == 256) {
        if (!crit) {
            mbar_init(bar_wq, 1);
            asm volatile("fence.mbarrier_init.release.cluster;" ::: "memory");
            mbar_expect_tx(bar_wq, D * 64);
            const uint32_t c0 = clock32();
            while (clock32() - c0 < WQ_DELAY) { }
#pragma unroll
            for (int r = 0; r < D; r += 160) tma2d(sb + X_WQ + r * 64, &tm_wq, 32 * cta, r, bar_wq);
        }
    } else if (threadIdx.x == 0) {
#pragma unroll
        for (int s = 0; s < NS; s++) { if (s) mbar_init(bar_full + s * 8, 1); mbar_init(bar_empty + s * 8, 4); }
        mbar_init(crit ? bar_wq : bar_wm, 1);
        mbar_init(bar_xfree, 1);
#pragma unroll
        for (int i = 0; i < 5; i++) { mbar_init(bar_wo + i * 8, 1); mbar_init(bar_w2 + i * 16, 1); mbar_init(bar_w2 + i * 16 + 8, 1); }
        mbar_init(bar_help, 1); mbar_init(bar_x1, 1);
#pragma unroll
        for (int i = 0; i < 4; i++) { mbar_init(bar_v + i * 8, 1); mbar_init(bar_w1 + i * 8, 1); mbar_init(bar_gb + i * 8, 1); }
        asm volatile("fence.mbarrier_init.release.cluster;" ::: "memory");
    }
    __syncthreads();

    if (warp == 8) {
        if (lane == 0) {
            int tp = NS;
            int sched = PACE_A - NS * PACE_TAU;
            int phase = 0;
#pragma unroll 1
            for (int t = 1; t <= NITEM; t++) {
                if (t == 1) mbar_wait(bar_full, 0);
                if (t == 2) {
                    mbar_wait(bar_first, 0);
                    if (crit) {
                        mbar_expect_tx(bar_wq, D * 64);
#pragma unroll 1
                        for (int r = 0; r < D; r += 160) tma2d(sb + X_WQ + r * 64, &tm_wq, 32 * cta, r, bar_wq);
                    }
                }
                if (t == 3) {
                    asm volatile("prefetch.tensormap [%0];" ::"l"(&tm_v) : "memory");
                    asm volatile("prefetch.tensormap [%0];" ::"l"(&tm_wo) : "memory");
                    asm volatile("prefetch.tensormap [%0];" ::"l"(&tm_w1) : "memory");
                    asm volatile("prefetch.tensormap [%0];" ::"l"(&tm_w2) : "memory");
                    asm volatile("prefetch.tensormap [%0];" ::"l"(&tm_gb) : "memory");
                }
                if (t == NS && late) {
                    mbar_wait(bar_full + (NS - INFLIGHT) * 8, 0);
                    mbar_expect_tx(bar_wm, D * 64);
#pragma unroll 1
                    for (int r = 0; r < D; r += 160) tma2d(sb + X_WM + r * 64, &tm_wmod, 32 * mc, r, bar_wm);
                }
                if (t >= NS && t < PF_END) {
                    int it = 0;
                    while (!mbar_test(bar_empty + (t & (NS - 1)) * 8, ((t >> 3) - 1) & 1)) {
                        if (tp < PF_END && (int)(gtime32() - t_start) >= PACE_A + (tp - NS) * PACE_TAU) {
                            asm volatile("cp.async.bulk.prefetch.L2.global.L2::cache_hint [%0], %1, %2;"
                                         ::"l"(((tp & 1) ? vb : kb) + (size_t)(((tp >> 1) + rot) & (NITEM / 2 - 1)) * TILE_BYTES), "r"(TILE_BYTES), "l"(pol) : "memory");
                            tp++;
                        }
                        if (++it > 16 * SPIN_LIMIT) __trap();
                    }
                    if (tp <= t) tp = t + 1;
                }
                if (t == NITEM) {
                    mbar_wait(bar_xfree, 0);
                    const uint32_t t_ref = t_start + phase + (NITEM - 1) * PACE_TAU;
#pragma unroll 1
                    for (int i = 0; i < 5; i++) {
                        while ((int)(gtime32() - t_ref) < WO_T + i * WO_S) { }
                        mbar_expect_tx(bar_wo + i * 8, DH * 64);
                        tma2d(sb + X_WO + i * (DH * 64), &tm_wo, bown * 160 + i * 32, head * DH, bar_wo + i * 8);
                    }
                    if (gb_own) {
                        mbar_wait(bar_empty + 3 * 8, ((NITEM >> 3) - 1) & 1);
                        mbar_wait(bar_x1, 0);
                        { const uint32_t c0 = clock32(); while (clock32() - c0 < GB_EV) { } }
                        while ((int)(gtime32() - t_ref) < GB_T) { }
#pragma unroll 1
                        for (int i = 0; i < 4; i++) {
                            mbar_expect_tx(bar_gb + i * 8, 160 * 16);
                            tma2d(sb + X_GB + i * (160 * 16), &tm_gb, 5 * D + 8 * own, 160 * i, bar_gb + i * 8);
                        }
                    }
                    if (is_f) {
#pragma unroll 1
                        for (int i = 0; i < 3; i++) mbar_wait(bar_empty + i * 8, ((NITEM >> 3) - 1) & 1);
                        while ((int)(gtime32() - t_ref) < W1_T) { }
#pragma unroll 1
                        for (int i = 0; i < 4; i++) {
                            mbar_expect_tx(bar_w1 + i * 8, 160 * 64);
                            tma2d(sb + X_W1 + i * (160 * 64), &tm_w1, 32 * f, 160 * i, bar_w1 + i * 8);
                        }
                        while ((int)(gtime32() - t_ref) < W2_T) { }
#pragma unroll 1
                        for (int i = 0; i < 10; i++) {
                            mbar_expect_tx(bar_w2 + i * 8, 4096);
                            tma2d(sb + X_W2 + i * 4096, &tm_w2, 64 * i, 32 * f, bar_w2 + i * 8);
                        }
                    }
                    break;
                }
                const int s = t & (NS - 1);
                if (t >= NS) {
                    mbar_wait(bar_empty + s * 8, ((t >> 3) - 1) & 1);
                    while ((int)(gtime32() - t_start) < sched + t * PACE_TAU) { }
                } else if (t >= INFLIGHT) {
                    mbar_wait(bar_full + (t - INFLIGHT) * 8, 0);
                }
                if (t < NITEM - 2) {
                    const int pair = t == NITEM - 3 ? NITEM / 2 - 1 : t >> 1;
                    mbar_expect_tx(bar_full + s * 8, TILE_BYTES);
                    bulk_load(sb + OFF_RING + s * TILE_BYTES, ((t & 1) && t != NITEM - 3 ? vb : kb) + (size_t)((pair + rot) & (NITEM / 2 - 1)) * TILE_BYTES, TILE_BYTES, bar_full + s * 8, pol);
                } else {
                    const int row = (bown * NH + head) * SK + (SK - WIN) + ((t - NITEM / 2 + rot) & (NITEM / 2 - 1)) * TILE_KEYS;
#pragma unroll 1
                    for (int i = 0; i < 2; i++) {
                        const uint32_t bar = bar_v + (2 * (t - (NITEM - 2)) + i) * 8;
                        mbar_expect_tx(bar, TILE_BYTES / 2);
                        tma2d_hint(sb + OFF_RING + s * TILE_BYTES + i * (TILE_BYTES / 2), &tm_v, 64 * i, row, bar, pol);
                    }
                }
                if (t >= PH_FIRST + PH_LAG && (t & 3) == (PH_LAG & 3)) {
                    const int now = (int)(gtime32() - t_start) - (t - PH_LAG) * PACE_TAU;
                    uint32_t ph;
                    asm volatile("atom.relaxed.gpu.global.add.u32 %0, [%1], 0;" : "=r"(ph) : "l"(g_phase + ((t - PH_LAG) >> 2) * 32) : "memory");
                    phase = (int)min(((ph & 0xffffffu) * 4 + (NCTA - (ph >> 24)) * now) >> 7, 65535u);
                    sched += (phase - LAT_T - sched) / 2;
                }
            }
        }
        __syncwarp();
    }

    if (warp == 9) {
        int side = 0;
        if (lane == 0) {
            uint32_t best[2] = {~0u, ~0u};
#pragma unroll
            for (int i = 0; i < 4; i++) stg_zero4(slot(SL_SIDE, i >> 1) + cta * 8 + (i & 1) * 4);
            uint32_t n = 0;
#pragma unroll 1
            for (int i = 0; (i & 1) || (n < NPROBE - 1 && (int)(gtime32() - t_start) < PROBE_END); i++) {
                uint32_t t0 = clock32(), t1;
                asm volatile("atom.relaxed.gpu.global.inc.u32 %0, [%1], %2;" : "=r"(n) : "l"(slot(SL_SIDE, i & 1) + cta * 8), "r"(0xffffu) : "memory");
                asm volatile("{\n.reg .pred p;\nsetp.ne.u32 p, %1, 0xffffffff;\nmov.u32 %0, 0;\n@p mov.u32 %0, %%clock;\n}" : "=r"(t1) : "r"(n) : "memory");
                if (i & 1) best[1] = min(best[1], t1 - t0); else best[0] = min(best[0], t1 - t0);
            }
            side = best[1] < best[0];
        }
        side = __shfl_sync(0xffffffffu, side, 0);
        HPROF(1);
        mbar_wait(bar_full + (NS - 1) * 8, 0);
        stg_zero4(slot(SL_O + (cta >> 4), lane >> 4) + (cta & 15) * 64 + (lane & 15) * 4);
        if (is_owner) {
#pragma unroll 1
            for (int i = lane; i < NH * 8; i += 32) stg_zero4(slot(SL_P1 + own, side) + i * 4);
#pragma unroll 1
            for (int i = lane; i < NF * 8; i += 32) stg_zero4(slot(SL_P2 + 2 * own + (i >> 8), side) + (i & 255) * 4);
            if (lane < 8) stg_zero4(slot(SL_X1 + own / 30, lane >> 2) + (own % 30) * 32 + (lane & 3) * 4);
        }
        __threadfence();
        __syncwarp();
        if (lane == 0) stg_relaxed(g_clr + cta, 1u + side);
        HPROF(0);
        HPROF(2);
        while ((int)(gtime32() - t_start) < CLR_CHECK) __nanosleep(1000);
        mbar_wait(bar_xfree, 0);
        {
            uint4 v = make_uint4(1, 1, 1, 1), gv = v, mv[20];
#pragma unroll
            for (int i = 0; i < 20; i++) mv[i] = v;
#pragma unroll 1
            for (int it = 0;; it++) {
                v = ldg_relaxed(g_clr + lane * 4);

                ldg_relaxed_if(is_owner && lane < (gb_own ? 4 : 8), gv, mod_slot(lane < 4 ? 2 : 5, own, lane & 3));
#pragma unroll
                for (int i = 0; i < 20; i++) ldg_relaxed_if(is_f, mv[i], mod_slot(3, 8 * i + (lane >> 2), lane & 3));
                bool ok = ready(v) && ready(gv);
#pragma unroll
                for (int i = 0; i < 20; i++) ok = ok && ready(mv[i]);
                if (__all_sync(0xffffffffu, ok)) break;
                if (it > SPIN_LIMIT) __trap();
                __nanosleep(2000);
            }
            const uint32_t w[4] = {v.x, v.y, v.z, v.w};
#pragma unroll
            for (int i = 0; i < 4; i++) {
                const Roles r = roles(4 * lane + i);
                if (r.is_owner) {
                    sts32(sb + OFF_TAB1 + r.own * 4, (uint32_t)(size_t)(slot(SL_P1 + r.own, w[i] - 1) + head * 32));
                    sts32(sb + OFF_TAB2 + r.own * 4, (uint32_t)(size_t)(slot(SL_P2 + 2 * r.own + (f >> 5), w[i] - 1) + (f & 31) * 32));
                }
            }
            if (lane == 0) sts32(sb + OFF_SIDE, side);
            if (lane < 8) sts128(sb + OWN_GA + lane * 16, inv4(gv));
            const uint32_t dst = sb + OFF_VB + (lane & 3) * VEC_STRIDE + (lane >> 2) * 16;
#pragma unroll
            for (int i = 0; i < 10; i++) {
                const uint4 c = inv4(mv[10 + i]);
                sts128(dst + i * 128, make_uint4(bf2_add(c.x, 0x3f803f80u), bf2_add(c.y, 0x3f803f80u), bf2_add(c.z, 0x3f803f80u), bf2_add(c.w, 0x3f803f80u)));
                sts128(dst + (OFF_RED - OFF_VB) + i * 128, inv4(mv[i]));
            }
        }
        asm volatile("fence.acq_rel.gpu;" ::: "memory");
        __syncwarp();
        HPROF(3);
        if (lane == 0) mbar_arrive(bar_help);
        {
            const uint32_t* const src = pin(slot(SL_O + (cta >> 4), side) + (cta & 12) * 64 + lane * 4);
            const uint32_t dst = pin(sb + OFF_O + (lane >> 4) * O_STRIDE + (lane & 15) * 16);
            mbar_wait(bar_v + 16, 0);
            mbar_wait(bar_v + 24, 0);
            uint4 v[2];
            const uint32_t* const ptr[2] = {src, src + 128};
            const bool on[2] = {true, true};
            poll_n<2>(v, ptr, on);
            sts128(dst, v[0]);
            sts128(dst + 2 * O_STRIDE, v[1]);
#pragma unroll
            for (int w = 0; w < 8; w++) asm volatile("bar.arrive %0, 64;" ::"r"(NB_O + w) : "memory");
        }
        HPROF(4);
    }
    if (warp >= 8) {
        if (gb_own && warp == 9) {
            uint32_t a[20][4];
#pragma unroll
            for (int i = 0; i < 20; i++) ldsm4(a[i], sb + OFF_VA + (lane & 3) * VEC_STRIDE + (4 * i + (lane >> 3)) * 16);
            float c[4][4];
#pragma unroll
            for (int i = 0; i < 4; i++) c[i][0] = c[i][1] = c[i][2] = c[i][3] = 0.f;
#pragma unroll
            for (int bx = 0; bx < 4; bx++) {
                mbar_wait(bar_gb + bx * 8, 0);
#pragma unroll
                for (int i = 5 * bx; i < 5 * bx + 5; i++) {
                    uint32_t w[4];
                    ldsm4t(w, sb + X_GB + (32 * i + lane) * 16);
                    const uint32_t a0[4] = {a[i][0], 0u, a[i][1], 0u}, a1[4] = {a[i][2], 0u, a[i][3], 0u};
                    mma16816(c[(2 * i) & 3], a0, w[0], w[1]);
                    mma16816(c[(2 * i + 1) & 3], a1, w[2], w[3]);
                }
            }
            if (lane < 16) sts32(sb + OWN_GB + lane * 4, pack_bf((c[0][0] + c[1][0]) + (c[2][0] + c[3][0]), (c[0][1] + c[1][1]) + (c[2][1] + c[3][1])));
            HPROF(6);
        }
        if (is_owner && warp == 9) nbar_arrive<NB_E6, 288>();
        if (is_f) gelu_stage(sb, warp - 8, lane);
        return;
    }

    const int g = lane >> 2, t4 = lane & 3;
    const int mi = lane >> 3, r8 = lane & 7;

    {
        auto silu4 = [&](const uint4& cv) {
            uint32_t w4[4] = {cv.x, cv.y, cv.z, cv.w};
#pragma unroll
            for (int e = 0; e < 4; e++) {
                float c0 = bf_lo(w4[e]), c1 = bf_hi(w4[e]);
                w4[e] = pack_bf(c0 * rcp_fast(1.f + ex2(-1.4426950408889634f * c0)), c1 * rcp_fast(1.f + ex2(-1.4426950408889634f * c1)));
            }
            return make_uint4(w4[0], w4[1], w4[2], w4[3]);
        };
        {
            uint4 v = silu4(ca0);
            sts128(sb + OFF_VA + (tid / 80) * VEC_STRIDE + (tid % 80) * 16, v);
            if (tid < 64) { v = silu4(ca1); sts128(sb + OFF_VA + 3 * VEC_STRIDE + (16 + tid) * 16, v); }
        }
        if (warp < 4) {
            float s = 0.f, q = 0.f;
            const float pv = __shfl_sync(0xffffffffu, bf_lo(xs[0].x), 0);
#pragma unroll
            for (int i = 0; i < 3; i++) if (i < 2 || lane < 16) acc_stats(xs[i], pv, s, q);
#pragma unroll
            for (int of = 16; of > 0; of >>= 1) { s += __shfl_xor_sync(0xffffffffu, s, of); q += __shfl_xor_sync(0xffffffffu, q, of); }
            uint32_t m2; float rden;
            ln_finish(pv, s, q, m2, rden);
            if (lane == 0) { sts32(sb + OFF_STAT + warp * 8, m2); sts_f32(sb + OFF_STAT + warp * 8 + 4, rden); }
        } else if (warp == 4) {
            sts32(sb + OWN_X + lane * 4, bf2_add(own0, 0u));
            sts_f32(sb + OWN_B1 + lane * 4, bf2f(own2));
        }
    }
    bar_cons();
    PROF(24);
    uint32_t qf[8][2];
    float o[8][4];
#pragma unroll
    for (int c = 0; c < 8; c++) { o[c][0] = o[c][1] = o[c][2] = o[c][3] = 0.f; }
    float m_run = -INFINITY, l_run = 0.f;
    const bool diag = (t4 == (g >> 1));
    const bool odd = g & 1;
    const uint32_t koff = (warp & 3) * 4096 + (r8 + 8 * (mi & 1)) * 256 + (mi >> 1) * 128 + (r8 << 4);
    const uint32_t voff = TILE_BYTES + (warp & 3) * 4096 + (r8 + 8 * (mi >> 1)) * 256 + (mi & 1) * 128 + (r8 << 4);
    const int src0 = (2 * t4) * 4 + t4, src1 = (2 * t4 + 1) * 4 + t4;
#pragma unroll 1
    for (int step = crit ? 0 : 1; step < 3; step++) {
        if (step < 2 || late) {
            if (step == 1) {
                if (!crit) mbar_wait(bar_wq, 0);
                const uint32_t m2 = lds32(sb + OFF_STAT + (tid & 3) * 8);
                const float rden = lds_f32(sb + OFF_STAT + (tid & 3) * 8 + 4);
                uint4 v[4];
                v[2] = v[3] = make_uint4(1, 1, 1, 1);
                const uint32_t* const p0 = mod_slot(0, tid >> 2, tid & 3);
                while ((int)(gtime32() - t_start) < MOD_T) { }
                PROF(2);
#pragma unroll 1
                for (int it = 0;; it++) {
                    ldg_relaxed_if(tid < 64, v[2], p0 + 16 * 64);
                    ldg_relaxed_if(tid < 64, v[3], p0 + 36 * 64);
                    v[0] = ldg_relaxed(p0);
                    v[1] = ldg_relaxed(p0 + 20 * 64);
                    if (__all_sync(0xffffffffu, min(min(min4(v[0]), min4(v[1])), min(min4(v[2]), min4(v[3]))) != 0u)) break;
                    if (it > SPIN_LIMIT) __trap();
                }
#pragma unroll
                for (int i = 0; i < 4; i++) v[i] = inv4(v[i]);
                PROF(3);
                uint4 h0 = ln_mod4(xa, v[1], v[0], m2, rden);
                sts128(sb + OFF_VB + (tid & 3) * VEC_STRIDE + (tid >> 2) * 16, h0);
                if (tid < 64) {
                    h0 = ln_mod4(xb, v[3], v[2], m2, rden);
                    sts128(sb + OFF_VB + (tid & 3) * VEC_STRIDE + (64 + (tid >> 2)) * 16, h0);
                }
            }
            mbar_wait(step == 1 ? bar_wq : bar_wm, 0);
            bar_cons();
            const uint32_t strip = sb + (step == 1 ? X_WQ : X_WM), vec = sb + (step == 1 ? OFF_VB : OFF_VA);
            float acc[2][4];
#pragma unroll
            for (int m = 0; m < 2; m++) { acc[m][0] = acc[m][1] = acc[m][2] = acc[m][3] = 0.f; }
#pragma unroll
            for (int i = 0; i < 5; i++) {
                int k0 = (warp * 5 + i) * 16;
                uint32_t b0, b1;
                load_bfrag(vec, VEC_STRIDE, k0, g, t4, b0, b1);
                int krow = k0 + r8 + 8 * (mi >> 1);
#pragma unroll
                for (int m = 0; m < 2; m++) {
                    uint32_t a[4];
                    int ch = 2 * m + (mi & 1);
                    ldsm4t(a, strip + krow * 64 + ((ch ^ ((krow >> 1) & 3)) << 4));
                    mma16816(acc[m], a, b0, b1);
                }
            }
            if (t4 < 2) {
#pragma unroll
                for (int m = 0; m < 2; m++) {
                    sts_f32x2(sb + OFF_RED + ((warp * 32 + m * 16 + g) * 4 + 2 * t4) * 4, acc[m][0], acc[m][1]);
                    sts_f32x2(sb + OFF_RED + ((warp * 32 + m * 16 + g + 8) * 4 + 2 * t4) * 4, acc[m][2], acc[m][3]);
                }
            }
            bar_cons();
            if (tid < 64) {
                float v0 = 0.f, v1 = 0.f;
#pragma unroll
                for (int w = 0; w < 8; w++) {
                    v0 += lds_f32(sb + OFF_RED + (w * 128 + (tid & 15) * 8 + (tid >> 4)) * 4);
                    v1 += lds_f32(sb + OFF_RED + (w * 128 + (tid & 15) * 8 + 4 + (tid >> 4)) * 4);
                }
                stg_relaxed(step == 1 ? g_q + (((cta & ~3) + (tid >> 4)) * 4 + bown) * 32 + (tid & 15) : g_mod + mc * 64 + tid, ~pack_bf(v0, v1));
            }
        }
        if (step == 0) continue;
        if (step == 1) {
            if (warp == 0) {
                { const uint32_t c0 = clock32(); while (clock32() - c0 < Q_PAUSE) { } }
                uint4 v = poll1(g_q + (cta * 4 + ((lane >> 2) & 3)) * 32 + (lane & 3) * 4, lane < 16);
                if (lane < 16) {
                    sts128(sb + OFF_Q + lane * 16, v);
                    stg_zero4(g_q + (cta * 4 + (lane >> 2)) * 32 + (lane & 3) * 4);
                }
            }
            bar_cons();
            PROF(4);

#pragma unroll
            for (int c = 0; c < 8; c++) {
                qf[c][0] = lds32(sb + OFF_Q + (((c ^ g) * 4 + t4) << 2));
                qf[c][1] = lds32(sb + OFF_Q + 128 + (((c ^ g) * 4 + t4) << 2));
            }
        } else {
            bar_cons();
            if (tid == 0) mbar_arrive(bar_xfree);
        }
#pragma unroll 1
        for (int j = (step == 1 ? 0 : SEG_J) + (warp >> 2); j < (step == 1 ? SEG_J : NITEM / 2 - 2); j += 2) {
            const int s = (2 * j) & (NS - 1);
            const uint32_t par = (j >> 2) & 1;
            mbar_wait(bar_full + s * 8, par);
            if (tid == 0 && 2 * j >= PH_FIRST) {
                const int x = min(max((int)(gtime32() - t_start) - 2 * j * PACE_TAU, 0), 65535);
                asm volatile("red.relaxed.gpu.global.add.u32 [%0], %1;" ::"l"(g_phase + (j >> 1) * 32), "r"((1u << 24) + (x >> 2)) : "memory");
            }
            const uint32_t base = sb + OFF_RING + s * TILE_BYTES;
            float sa[4] = {0.f, 0.f, 0.f, 0.f}, sb2[4] = {0.f, 0.f, 0.f, 0.f};
#pragma unroll
            for (int c = 0; c < 8; c += 2) {
                uint32_t a[4], a2[4];
                ldsm4(a, (base + koff) ^ (c << 4));
                ldsm4(a2, (base + koff) ^ ((c + 1) << 4));
                mma16816(sa, a, qf[c][0], qf[c][1]);
                mma16816(sb2, a2, qf[c + 1][0], qf[c + 1][1]);
            }
            const uint32_t sw = pack_bf(odd ? sa[1] + sb2[1] : sa[0] + sb2[0], odd ? sa[3] + sb2[3] : sa[2] + sb2[2]);
            const uint32_t sv = pack_bf(bf_lo(sw) * 0.08838834764831845f, bf_hi(sw) * 0.08838834764831845f);
            const float s0 = bf_lo(sv) * 1.4426950408889634f, s1 = bf_hi(sv) * 1.4426950408889634f;
            float m_new = fmaxf(m_run, fmaxf(s0, s1));
            const bool grow = __any_sync(0xffffffffu, (diag && (m_new > m_run)));
            if (lane == 0) mbar_arrive(bar_empty + s * 8);
            if (grow) {
                float al = ex2(m_run - m_new);
                float a0 = __shfl_sync(0xffffffffu, al, src0), a1 = __shfl_sync(0xffffffffu, al, src1);
#pragma unroll
                for (int c = 0; c < 8; c++) { o[c][0] *= a0; o[c][1] *= a1; o[c][2] *= a0; o[c][3] *= a1; }
                l_run *= al;
                m_run = m_new;
            }
            uint32_t pw = pack_bf(ex2(s0 - m_run), ex2(s1 - m_run));
            l_run += bf_lo(pw) + bf_hi(pw);
            uint32_t b0 = odd ? (pw << 16) : (pw & 0xffffu);
            uint32_t b1 = odd ? (pw & 0xffff0000u) : (pw >> 16);
            if (!diag) { b0 = 0u; b1 = 0u; }
            mbar_wait(bar_full + (s + 1) * 8, par);
#pragma unroll
            for (int c = 0; c < 8; c++) {
                uint32_t a[4];
                ldsm4t(a, (base + voff) ^ (c << 4));
                mma16816(o[c], a, b0, b1);
            }
            __syncwarp();
            if (lane == 0) mbar_arrive(bar_empty + (s + 1) * 8);
        }
    }
    PROF(5);
    float acc[4][4];
    uint32_t pa[8][2];
    float rinv;
    {
        const int s = 4 + (warp >> 2);
        mbar_wait(bar_full + s * 8, 1);
        const uint32_t base = sb + OFF_RING + s * TILE_BYTES;
        float sa[4] = {0.f, 0.f, 0.f, 0.f}, sb2[4] = {0.f, 0.f, 0.f, 0.f};
#pragma unroll
        for (int c = 0; c < 8; c += 2) {
            uint32_t a[4], a2[4];
            ldsm4(a, (base + koff) ^ (c << 4));
            ldsm4(a2, (base + koff) ^ ((c + 1) << 4));
            mma16816(sa, a, qf[c][0], qf[c][1]);
            mma16816(sb2, a2, qf[c + 1][0], qf[c + 1][1]);
        }
        const uint32_t sw = pack_bf(odd ? sa[1] + sb2[1] : sa[0] + sb2[0], odd ? sa[3] + sb2[3] : sa[2] + sb2[2]);
        const uint32_t sv = pack_bf(bf_lo(sw) * 0.08838834764831845f, bf_hi(sw) * 0.08838834764831845f);
        const float s0 = bf_lo(sv) * 1.4426950408889634f, s1 = bf_hi(sv) * 1.4426950408889634f;
        int mi_ = __float_as_int(diag ? fmaxf(m_run, fmaxf(s0, s1)) : -INFINITY);
        mi_ ^= (mi_ >> 31) & 0x7fffffff;
        mi_ = __reduce_max_sync(0xffffffffu, mi_);
        mi_ ^= (mi_ >> 31) & 0x7fffffff;
        if (lane == 0) sts32(sb + OFF_ML + warp * 4, mi_);
        bar_cons();
        const float4 m0 = lds_f32x4(sb + OFF_ML), m1 = lds_f32x4(sb + OFF_ML + 16);
        const float mx = fmaxf(fmaxf(fmaxf(m0.x, m0.y), fmaxf(m0.z, m0.w)), fmaxf(fmaxf(m1.x, m1.y), fmaxf(m1.z, m1.w)));
        const float scl = ex2(m_run - mx);
        const uint32_t pw = pack_bf(ex2(s0 - mx), ex2(s1 - mx));
        if (diag) { sts16(sb + SC_P + (warp * 16 + g) * 2, pw); sts16(sb + SC_P + (warp * 16 + g + 8) * 2, pw >> 16); }
        const float lw = warp_sum(diag ? fmaf(l_run, scl, bf_lo(pw) + bf_hi(pw)) : 0.f);
        const float a0 = __shfl_sync(0xffffffffu, scl, src0), a1 = __shfl_sync(0xffffffffu, scl, src1);
        float v[8], u[8];
#pragma unroll
        for (int c = 0; c < 8; c++) {
            v[c] = a0 * o[c][0] + a1 * o[c ^ 1][1];
            u[c] = a0 * o[c][2] + a1 * o[c ^ 1][3];
        }
#pragma unroll
        for (int c = 0; c < 8; c++) {
            if (!(c & 2)) {
                v[c] += __shfl_xor_sync(0xffffffffu, v[c ^ 2], 1);
                u[c] += __shfl_xor_sync(0xffffffffu, u[c ^ 2], 1);
            }
        }
#pragma unroll
        for (int c = 0; c < 2; c++) {
            v[c] += __shfl_xor_sync(0xffffffffu, v[c ^ 4], 2);
            u[c] += __shfl_xor_sync(0xffffffffu, u[c ^ 4], 2);
        }
        const uint32_t dst = sb + SC_OP + (warp * 128 + 16 * t4 + g) * 4;
        sts_f32(dst, v[0]); sts_f32(dst + 32, v[1]); sts_f32(dst + 256, u[0]); sts_f32(dst + 288, u[1]);
        if (lane == 0) sts_f32(sb + OFF_ML + 32 + warp * 4, lw);
        mbar_wait(bar_help, 0);
        bar_cons();
        const float4 l0 = lds_f32x4(sb + OFF_ML + 32), l1 = lds_f32x4(sb + OFF_ML + 48);
        rinv = rcp_fast(((l0.x + l0.y) + (l0.z + l0.w)) + ((l1.x + l1.y) + (l1.z + l1.w)));
#pragma unroll
        for (int i = 0; i < 4; i++) acc[i][0] = acc[i][1] = acc[i][2] = acc[i][3] = 0.f;
#pragma unroll
        for (int w = 0; w < 8; w++) {
            const float2 x0 = lds_f32x2(sb + SC_OP + (w * 128 + 16 * warp + 2 * t4) * 4), x1 = lds_f32x2(sb + SC_OP + (w * 128 + 16 * warp + 8 + 2 * t4) * 4);
            acc[2 * (w & 1)][0] += x0.x; acc[2 * (w & 1)][1] += x0.y;
            acc[2 * (w & 1) + 1][0] += x1.x; acc[2 * (w & 1) + 1][1] += x1.y;
        }
#pragma unroll
        for (int ks = 0; ks < 8; ks++) { pa[ks][0] = lds32(sb + SC_P + (8 * ks + t4) * 4); pa[ks][1] = lds32(sb + SC_P + (8 * ks + 4 + t4) * 4); }
    }
    PROF(20);
    const int mt = warp < 2 ? warp : warp + 2;
    {
        const uint32_t va = pin(sb + OFF_RING + 6 * TILE_BYTES + (warp >> 2) * (TILE_BYTES / 2) + (8 * (mi & 1) + r8) * 128 + (((2 * (warp & 3) + (mi >> 1)) ^ r8) << 4));
        const uint32_t vbar = pin(bar_v + (warp >> 2) * 8);
        uint32_t* const o_dst = pin(slot(SL_O + (cta >> 4), g) + (cta & 15) * 64 + warp * 8 + 2 * t4);
#pragma unroll
        for (int tl = 0; tl < 2; tl++) {
            mbar_wait(vbar + tl * 16, 0);
            uint32_t r[4][4];
#pragma unroll
            for (int ks = 0; ks < 4; ks++) ldsm4t(r[ks], va + tl * TILE_BYTES + ks * 2048);
#pragma unroll
            for (int ks = 0; ks < 4; ks++) {
                const uint32_t a[4] = {pa[4 * tl + ks][0], 0u, pa[4 * tl + ks][1], 0u};
                mma16816(acc[2 * (ks & 1)], a, r[ks][0], r[ks][1]);
                mma16816(acc[2 * (ks & 1) + 1], a, r[ks][2], r[ks][3]);
            }
        }
        stg_relaxed2_if(g < 2, o_dst, ~pack_bf((acc[0][0] + acc[2][0]) * rinv, (acc[0][1] + acc[2][1]) * rinv),
                        ~pack_bf((acc[1][0] + acc[3][0]) * rinv, (acc[1][1] + acc[3][1]) * rinv));
    }
    PROF(7);
    const int side = lds32(sb + OFF_SIDE);
    const uint32_t red_st = pin(sb + SC_E4 + ((warp * 4 + 2 * ((lane >> 3) & 1) + (lane >> 4)) * 8 + (lane & 7)) * 4);
    const uint32_t red_ld = pin(sb + SC_E4 + (lane & 15) * 8);
    const uint32_t* const in1 = pin(slot(SL_P1 + own, side) + tid * 4);
    const uint32_t* const in2a = pin(slot(SL_P2 + 2 * own, side) + tid * 4);
    const uint32_t* const in2b = pin(slot(SL_P2 + 2 * own + 1, side) + tid * 4);
    uint32_t* const out_dst = pin((uint32_t*)(p.out + ((lane >> 2) & 3) * D + 8 * own) + t4);
    uint32_t* const x1_dst = pin(slot(SL_X1 + own / 30, lane >> 4) + (own % 30) * 32 + (lane & 15));
    uint32_t* const rst = pin(tid >= 32 && tid < 56 ? mod_slot(lane >> 2, own, lane & 3) : own < 32 && tid == 64 ? g_clr + own * 4 : own < 16 && tid == 96 ? g_phase + own * 32 : nullptr);
    const uint32_t xw = lds32(sb + OWN_X + (lane & 15) * 4), ga_w = lds32(sb + OWN_GA + (lane & 15) * 4);
    uint32_t cs[15];
    uint32_t* dst2[5];
    uint32_t w2a[5];
#pragma unroll
    for (int j = 0; j < 10; j++) cs[j] = lds32(sb + OFF_VB + ((g & 1) * 4 + (g >> 1)) * VEC_STRIDE + warp * 160 + t4 * 4 + j * 16);
#pragma unroll
    for (int i = 0; i < 5; i++) {
        cs[10 + i] = lds32(sb + OFF_VB + (g >> 1) * VEC_STRIDE + warp * 160 + (g & 1) * 16 + t4 * 4 + i * 32);
        const uint2 t = lds64(sb + OFF_TAB2 + warp * 40 + i * 8);
        dst2[i] = slot_ptr((t4 < 2 ? t.x : t.y) + g * 16 + (t4 & 1) * 8);
        const int cc = 2 * (warp * 5 + i) + (mi & 1);
        w2a[i] = pin(sb + X_W2 + (cc >> 3) * 4096 + (r8 + 8 * (mi >> 1)) * 128 + (((cc & 7) ^ r8) << 4));
    }
    const uint32_t piv = lds32(sb + OFF_STAT + (g >> 1) * 8);
    const uint32_t* const xin = pin(slot(SL_X1 + warp / 3, side) + ((warp % 3) * 10 + (g & 1)) * 32 + (g >> 1) * 4 + t4);
    const uint32_t w1a = pin(sb + X_W1 + (warp * 80 + r8 + 8 * (mi >> 1)) * 64 + (((mi & 1) ^ ((r8 >> 1) & 3)) << 4));
    const uint32_t w1bar = pin(bar_w1 + (warp >> 1) * 8), w2bar = pin(bar_w2 + (warp + (warp >> 2)) * 8);
    const uint32_t wbar = pin(NB_O + warp);
    const uint32_t ab_st = pin(sb + SC_AB + warp * 1024 + lane * 16), y_st = pin(sb + SC_Y + warp * 512 + lane * 8), s_st = pin(sb + SC_ST + (t4 * 8 + warp) * 8);
    const uint32_t h_ld = pin(sb + SC_H1 + ((g & 3) ^ (2 * (f & 1) + ((f >> 1) & 1))) * 64 + t4 * 16);
    {
        const int kap = 2 * (head & 1) + ((head >> 1) & 1);
        const uint32_t wa = pin(sb + X_WO + (mt >> 1) * (DH * 64) + (r8 + 8 * (mi >> 1)) * 64 + ((((mt & 1) * 2 + (mi & 1)) ^ ((r8 >> 1) & 3)) << 4));
        const uint32_t oa = pin(sb + OFF_O + ((g & 3) ^ kap) * O_STRIDE + t4 * 8);
        uint32_t* dst[4];
#pragma unroll
        for (int i = 0; i < 2; i++) {
            const uint2 t = lds64(sb + OFF_TAB1 + (bown * 20 + 2 * mt + (warp < 2 ? 4 * i : 0)) * 4);
            dst[2 * i] = slot_ptr(t.x + g * 16 + t4 * 8);
            dst[2 * i + 1] = slot_ptr(t.y + g * 16 + t4 * 8);
        }
        PROF(6);
        const uint32_t wobar = pin(bar_wo + (mt >> 1) * 8);
        asm volatile("bar.sync %0, 64;" ::"r"(wbar) : "memory");
        uint2 ob[8];
#pragma unroll
        for (int ks = 0; ks < 8; ks++) ob[ks] = lds64(oa + ks * 32);
#pragma unroll
        for (int m = 0; m < 2; m++) {
            if (m == 0 || warp < 2) {
                mbar_wait(wobar + m * 8, 0);
                PROF(8);
                uint32_t wf[8][4];
#pragma unroll
                for (int ks = 0; ks < 8; ks++) ldsm4t(wf[ks], wa + m * (DH * 64) + ks * 1024);
                float c[4][4];
#pragma unroll
                for (int ks = 0; ks < 8; ks++) {
                    if (ks < 4) c[ks][0] = c[ks][1] = c[ks][2] = c[ks][3] = 0.f;
                    mma16816(c[ks & 3], wf[ks], ob[ks].x, ob[ks].y);
                }
                stg_relaxed2_if(t4 < 2, dst[2 * m], flag((c[0][0] + c[1][0]) + (c[2][0] + c[3][0])), flag((c[0][1] + c[1][1]) + (c[2][1] + c[3][1])));
                stg_relaxed2_if(t4 < 2, dst[2 * m + 1], flag((c[0][2] + c[1][2]) + (c[2][2] + c[3][2])), flag((c[0][3] + c[1][3]) + (c[2][3] + c[3][3])));
            }
        }
    }
    PROF(9);
    uint32_t x1w = 0;
    if (is_owner) {
        uint4 v;
        for (int it = 0;; it++) {
            v = ldg_relaxed(in1);
            if (__all_sync(0xffffffffu, and3(and3(v.x, v.y, v.z), v.w, 1u))) break;
            if (it > SPIN_LIMIT) __trap();
        }
        PROF(11);
        const float s0 = __uint_as_float(v.x) + __shfl_xor_sync(0xffffffffu, __uint_as_float(v.z), 8);
        const float s1 = __uint_as_float(v.y) + __shfl_xor_sync(0xffffffffu, __uint_as_float(v.w), 8);
        sts_f32(red_st, s0 + __shfl_xor_sync(0xffffffffu, s1, 16));
        nbar_sync<NB_E4, 256>();
        if (warp == 0) {
            float2 a[8];
#pragma unroll
            for (int w = 0; w < 8; w++) a[w] = lds_f32x2(red_ld + w * 128);
            const uint32_t aw = pack_bf(((a[0].x + a[1].x) + (a[2].x + a[3].x)) + ((a[4].x + a[5].x) + (a[6].x + a[7].x)),
                                        ((a[0].y + a[1].y) + (a[2].y + a[3].y)) + ((a[4].y + a[5].y) + (a[6].y + a[7].y)));
            x1w = bf2_add(xw, bf2_mul(ga_w, aw));
            stg_relaxed(x1_dst, x1w ^ 0x80008000u);
            if (lane == 0) mbar_arrive(bar_x1);
        }
        if (rst) stg_zero4(rst);
    }
    PROF(12);
    if (is_f) {
        uint32_t f1[5][2][4], f2[5][2][4];
        uint32_t d[6];
        auto load_x1 = [&] {
#pragma unroll
            for (int i = 0; i < 5; i++) d[i] = ldg_relaxed32(xin + i * 64);
        };
        auto have_x1 = [&] { return __all_sync(0xffffffffu, __vimin3_u32(__vimin3_u32(d[0], d[1], d[2]), d[3], d[4]) != 0u); };
        mbar_wait(w1bar, 0);
        load_x1();
        {
#pragma unroll
            for (int i = 0; i < 5; i++) { ldsm4t(f1[i][0], w1a + i * 1024); ldsm4t(f1[i][1], (w1a ^ 32) + i * 1024); }
            float c[2][4];
#pragma unroll
            for (int m = 0; m < 2; m++) c[m][0] = c[m][1] = c[m][2] = c[m][3] = 0.f;
#pragma unroll
            for (int i = 0; i < 5; i++) { mma16816(c[0], f1[i][0], cs[2 * i], cs[2 * i + 1]); mma16816(c[1], f1[i][1], cs[2 * i], cs[2 * i + 1]); }
#pragma unroll
            for (int i = 0; i < 5; i++) { cs[2 * i] = pin(odd ? 0u : cs[10 + i]); cs[2 * i + 1] = pin(odd ? cs[10 + i] : 0u); }
#pragma unroll
            for (int m = 0; m < 2; m++) sts128(ab_st + m * 512, make_uint4(__float_as_uint(c[m][0]), __float_as_uint(c[m][1]), __float_as_uint(c[m][2]), __float_as_uint(c[m][3])));
            nbar_arrive<NB_AB, 320>();
            d[0] |= __float_as_uint(c[1][3]) & (side >> 1);
        }
        PROF(10);
#pragma unroll 1
        for (int it = 0; !have_x1(); it++) {
            load_x1();
            if (it > SPIN_LIMIT) __trap();
        }
        PROF(13);
        {
            float y[2][4], st[4] = {0.f, 0.f, 0.f, 0.f};
#pragma unroll
            for (int m = 0; m < 2; m++) y[m][0] = y[m][1] = y[m][2] = y[m][3] = 0.f;
#pragma unroll
            for (int i = 0; i < 5; i++) d[i] = bf2_add(d[i], piv);
            d[5] = 0u;
#pragma unroll
            for (int i = 0; i < 5; i++) {
                if (i < 3) {
                    const uint32_t a[4] = {d[2 * i], 0x3f803f80u, d[2 * i + 1], 0x3f803f80u};
                    mma16816(st, a, d[2 * i], d[2 * i + 1]);
                }
                const uint32_t y0 = bf2_mul(d[i], cs[2 * i]), y1 = bf2_mul(d[i], cs[2 * i + 1]);
                mma16816(y[0], f1[i][0], y0, y1);
                mma16816(y[1], f1[i][1], y0, y1);
            }
            const float q = odd ? st[1] : st[0];
            const float q2 = q + __shfl_xor_sync(0xffffffffu, q, 4);
            if (diag && !odd) sts_f32x2(s_st, q2, st[2] + st[3]);
#pragma unroll
            for (int m = 0; m < 2; m++) sts_f32x2(y_st + m * 256, y[m][0] + y[m][1], y[m][2] + y[m][3]);
        }
        nbar_arrive<NB_Y, 320>();
        PROF(14);
        mbar_wait(w2bar, 0);
        mbar_wait(w2bar + 8, 0);
#pragma unroll
        for (int i = 0; i < 5; i++) { ldsm4t(f2[i][0], w2a[i]); ldsm4t(f2[i][1], w2a[i] + 2048); }
        asm volatile("bar.sync %0, 96;" ::"r"(wbar) : "memory");
        PROF(15);
        {
            const uint4 hb = lds128(h_ld);
            float c[5][4];
#pragma unroll
            for (int i = 0; i < 5; i++) { c[i][0] = c[i][1] = c[i][2] = c[i][3] = 0.f; mma16816(c[i], f2[i][0], hb.x, hb.y); }
#pragma unroll
            for (int i = 0; i < 5; i++) {
                mma16816(c[i], f2[i][1], hb.z, hb.w);
                stg_relaxed2_if(true, dst2[i], flag(t4 < 2 ? c[i][0] : c[i][2]), flag(t4 < 2 ? c[i][1] : c[i][3]));
            }
        }
    }
    PROF(16);
    if (is_owner) {
        const uint32_t b2w = lds32(sb + OWN_B2 + (lane & 15) * 4), gb_ld = pin(sb + OWN_GB + (lane & 15) * 4);
        const bool two = tid < NF * 8 - 256;
        uint4 v, w = make_uint4(1, 1, 1, 1);
        for (int it = 0;; it++) {
            ldg_relaxed_if(two, w, in2b);
            v = ldg_relaxed(in2a);
            if (__all_sync(0xffffffffu, and3(and3(v.x, v.y, v.z), and3(v.w, w.x, w.y), and3(w.z, w.w, 1u)))) break;
            if (it > SPIN_LIMIT) __trap();
        }
        PROF(17);
        const float s0 = (__uint_as_float(v.x) + __uint_as_float(w.x)) + __shfl_xor_sync(0xffffffffu, __uint_as_float(v.z) + __uint_as_float(w.z), 8);
        const float s1 = (__uint_as_float(v.y) + __uint_as_float(w.y)) + __shfl_xor_sync(0xffffffffu, __uint_as_float(v.w) + __uint_as_float(w.w), 8);
        sts_f32(red_st + (SC_E6 - SC_E4), s0 + __shfl_xor_sync(0xffffffffu, s1, 16));
        if (warp != 0) {
            nbar_arrive<NB_E6, 288>();
        } else {
            nbar_sync<NB_E6, 288>();
            float2 a[8];
#pragma unroll
            for (int i = 0; i < 8; i++) a[i] = lds_f32x2(red_ld + (SC_E6 - SC_E4) + i * 128);
            const uint32_t gb_w = lds32(gb_ld);
            const uint32_t aw = pack_bf(((a[0].x + a[1].x) + (a[2].x + a[3].x)) + ((a[4].x + a[5].x) + (a[6].x + a[7].x)),
                                        ((a[0].y + a[1].y) + (a[2].y + a[3].y)) + ((a[4].y + a[5].y) + (a[6].y + a[7].y)));
            x1w = bf2_add(x1w, bf2_mul(gb_w, bf2_add(aw, b2w)));
            if (lane < 16) asm volatile("st.global.u32 [%0], %1;" ::"l"(out_dst), "r"(x1w) : "memory");
        }
    }
    PROF(18);
    PROF_DUMP;
}

typedef CUresult (*EncodeFn)(CUtensorMap*, CUtensorMapDataType, cuuint32_t, void*, const cuuint64_t*, const cuuint64_t*, const cuuint32_t*,
                             const cuuint32_t*, CUtensorMapInterleave, CUtensorMapSwizzle, CUtensorMapL2promotion, CUtensorMapFloatOOBfill);

static CUtensorMap make_map(EncodeFn enc, const void* ptr, int cols, int rows, int box_cols, int box_rows, CUtensorMapSwizzle sw,
                            CUtensorMapL2promotion promo = CU_TENSOR_MAP_L2_PROMOTION_NONE) {
    CUtensorMap m;
    cuuint64_t dims[2] = {(cuuint64_t)cols, (cuuint64_t)rows};
    cuuint64_t strides[1] = {(cuuint64_t)cols * 2};
    cuuint32_t box[2] = {(cuuint32_t)box_cols, (cuuint32_t)box_rows};
    cuuint32_t es[2] = {1, 1};
    enc(&m, CU_TENSOR_MAP_DATA_TYPE_BFLOAT16, 2, const_cast<void*>(ptr), dims, strides, box, es, CU_TENSOR_MAP_INTERLEAVE_NONE, sw,
        promo, CU_TENSOR_MAP_FLOAT_OOB_FILL_NONE);
    return m;
}

}

extern "C" void kernel_launch(void* const* d_in, const int* in_sizes, int n_in, void* d_out, int out_size) {
    (void)in_sizes; (void)n_in; (void)out_size;
    static EncodeFn enc = nullptr;
    if (!enc) {
        void* fn = nullptr;
        cudaDriverEntryPointQueryResult qr;
        cudaGetDriverEntryPoint("cuTensorMapEncodeTiled", &fn, cudaEnableDefault, &qr);
        enc = (EncodeFn)fn;
        cudaFuncSetAttribute(fused_kernel, cudaFuncAttributeMaxDynamicSharedMemorySize, SMEM_BYTES);
    }
    Params p;
    p.x = (const __nv_bfloat16*)d_in[0];
    p.kc = (const __nv_bfloat16*)d_in[1];
    p.vc = (const __nv_bfloat16*)d_in[2];
    p.b1 = (const __nv_bfloat16*)d_in[7];
    p.b2 = (const __nv_bfloat16*)d_in[9];
    p.c = (const __nv_bfloat16*)d_in[10];
    p.out = (__nv_bfloat16*)d_out;
    CUtensorMap tm_wmod = make_map(enc, d_in[11], NMOD, D, 32, 160, CU_TENSOR_MAP_SWIZZLE_64B, CU_TENSOR_MAP_L2_PROMOTION_L2_128B);
    CUtensorMap tm_wq = make_map(enc, d_in[3], NH * DH, D, 32, 160, CU_TENSOR_MAP_SWIZZLE_64B, CU_TENSOR_MAP_L2_PROMOTION_L2_128B);
    CUtensorMap tm_wo = make_map(enc, d_in[4], D, NH * DH, 32, 128, CU_TENSOR_MAP_SWIZZLE_64B);
    CUtensorMap tm_w1 = make_map(enc, d_in[6], FF, D, 32, 160, CU_TENSOR_MAP_SWIZZLE_64B);
    CUtensorMap tm_w2 = make_map(enc, d_in[8], D, FF, 64, 32, CU_TENSOR_MAP_SWIZZLE_128B);
    CUtensorMap tm_v = make_map(enc, d_in[2], DH, NB * NH * SK, 64, TILE_KEYS, CU_TENSOR_MAP_SWIZZLE_128B);
    CUtensorMap tm_gb = make_map(enc, d_in[11], NMOD, D, 8, 160, CU_TENSOR_MAP_SWIZZLE_NONE, CU_TENSOR_MAP_L2_PROMOTION_L2_128B);
    fused_kernel<<<NCTA, NTHREADS, SMEM_BYTES>>>(p, tm_wmod, tm_wq, tm_wo, tm_w1, tm_w2, tm_v, tm_gb);
}
```

```cpp
#include <cuda_runtime.h>
#include <cuda.h>
#include <cuda_bf16.h>
#include <stdint.h>
#include <stdlib.h>

namespace {

constexpr int NB = 4, D = 640, NH = 32, DH = 128, SK = 8192, WIN = 2048, FF = 1728, NMOD = 6 * D;
constexpr int NCTA = 128;
constexpr int NOWN = 80;
constexpr int NF = 54;
constexpr int NTHREADS = 320;
constexpr int TILE_KEYS = 64;
constexpr int TILE_BYTES = TILE_KEYS * DH * 2;
constexpr int NITEM = 2 * WIN / TILE_KEYS;
constexpr int NS = 8;
constexpr int NMODC = 120;
constexpr int SPIN_LIMIT = 1 << 18;
#define INFLIGHT 3
#define WQ_DELAY 500
#define MOD_T 4200
#define Q_PAUSE 1100
#define PACE_A 7500
#define PACE_TAU 635
#define ROT(c) 0
#define PF_END 16
#define PH_FIRST 24
#define PH_LAG 5
#define LAT_T 2300
#define WO_T -950
#define WO_S 250
#define W1_T 1000
#define W2_T 1750
#define GB_T 2500
#define GB_EV 600
#define CLR_CHECK 28000
constexpr int NPROBE = 8, PROBE_END = 10000;
constexpr int SEG_J = 8;

constexpr int OFF_RING = 0;
constexpr int OFF_X = OFF_RING + NS * TILE_BYTES;
constexpr int X_WM = OFF_X;
constexpr int X_WQ = OFF_X + D * 64;
constexpr int X_WO = OFF_X;
constexpr int X_W1 = X_WO + 5 * DH * 64;
constexpr int X_END = X_W1 + D * 64;
constexpr int X_W2 = OFF_RING;
constexpr int X_GB = OFF_RING + 3 * TILE_BYTES;
static_assert(X_WQ + D * 64 <= X_END, "prologue weights must fit");
constexpr int VEC_STRIDE = 1296;
constexpr int OFF_VA = X_END;
constexpr int OFF_VB = OFF_VA + 4 * VEC_STRIDE;
constexpr int OFF_RED = OFF_VB + 4 * VEC_STRIDE;
constexpr int OFF_ML = OFF_RED + 4 * VEC_STRIDE;
constexpr int O_STRIDE = 288;
constexpr int OFF_O = OFF_ML + 64;
constexpr int OFF_Q = OFF_O + 4 * O_STRIDE;
constexpr int OFF_OWN = OFF_Q + 256;
constexpr int OWN_X = OFF_OWN, OWN_B2 = OWN_X + 64, OWN_GA = OWN_B2 + 64, OWN_GB = OWN_GA + 64, OWN_B1 = OWN_GB + 64;
constexpr int OFF_STAT = OWN_B1 + 128;
constexpr int OFF_TAB1 = OFF_STAT + 32;
constexpr int OFF_TAB2 = OFF_TAB1 + NOWN * 4;
constexpr int OFF_SIDE = OFF_TAB2 + NOWN * 4;
constexpr int OFF_BAR = OFF_SIDE + 8;
constexpr int NBAR = 2 * NS + 32;
constexpr int SMEM_BYTES = OFF_BAR + NBAR * 8;
constexpr int SC_OP = OFF_RING + 4 * TILE_BYTES;
constexpr int SC_AB = SC_OP + 4096;
constexpr int SC_Y = SC_AB + 8192;
constexpr int SC_ST = SC_Y + 4096;
constexpr int SC_E4 = SC_ST + 256;
constexpr int SC_E6 = SC_E4 + 1024;
constexpr int SC_P = SC_E6 + 1024;
constexpr int SC_H1 = SC_P + 256;
static_assert(SMEM_BYTES <= 232448, "smem");
static_assert(OFF_BAR % 8 == 0 && OFF_X % 1024 == 0 && X_WQ % 512 == 0 && X_W1 % 512 == 0 && OFF_VA % 16 == 0 && OFF_RED % 16 == 0 && OFF_ML % 16 == 0 && OFF_O % 16 == 0 && OFF_Q % 16 == 0, "align");
constexpr int NB_O = 2  , NB_E4 = 10, NB_E6 = 11, NB_AB = 12, NB_Y = 13;

__device__ __align__(128) uint32_t g_mod[NMODC * 64];
__device__ __align__(128) uint32_t g_q[NCTA * 128];
__device__ uint32_t g_clr[NCTA];
__device__ __align__(128) uint32_t g_phase[8 * 32];
constexpr int SL_P1 = 0;
constexpr int SL_P2 = SL_P1 + NOWN;
constexpr int SL_O = SL_P2 + 2 * NOWN;
constexpr int SL_X1 = SL_O + 8;
constexpr int SL_SIDE = SL_X1 + 3;
static_assert(SL_SIDE < 256, "one 2 MB page");
__device__ uint32_t g_slots[2 * 256 * 2048];
__device__ __forceinline__ uint32_t* slot(int i, int side) {
    const size_t base = ((size_t)g_slots + 0x1fffff) & ~(size_t)0x1fffff;
    return (uint32_t*)base + i * 2048 + (((__popc(i & 0x59) ^ side) & 1) << 10);
}
#define PROF_DECL
#define HPROF(i) do { } while (0)
#define PROF(i) do { } while (0)
#define PROF_DUMP do { } while (0)

__device__ __forceinline__ uint32_t smem_u32(const void* p) { return (uint32_t)__cvta_generic_to_shared(p); }
__device__ __forceinline__ void mbar_init(uint32_t bar, uint32_t cnt) { asm volatile("mbarrier.init.shared::cta.b64 [%0], %1;" ::"r"(bar), "r"(cnt) : "memory"); }
__device__ __forceinline__ void mbar_expect_tx(uint32_t bar, uint32_t bytes) { asm volatile("mbarrier.arrive.expect_tx.shared::cta.b64 _, [%0], %1;" ::"r"(bar), "r"(bytes) : "memory"); }
__device__ __forceinline__ void mbar_arrive(uint32_t bar) { asm volatile("mbarrier.arrive.shared::cta.b64 _, [%0];" ::"r"(bar) : "memory"); }
__device__ __forceinline__ void mbar_wait(uint32_t bar, uint32_t parity) {
    uint32_t ok;
    int it = 0;
    while (true) {
        asm volatile("{\n.reg .pred p;\nmbarrier.try_wait.parity.shared::cta.b64 p, [%1], %2;\nselp.u32 %0, 1, 0, p;\n}" : "=r"(ok) : "r"(bar), "r"(parity) : "memory");
        if (ok) break;
        if (++it > SPIN_LIMIT) __trap();
    }
}
__device__ __forceinline__ void bulk_load(uint32_t dst, const void* src, uint32_t bytes, uint32_t bar, uint64_t pol) {
    asm volatile("cp.async.bulk.shared::cluster.global.mbarrier::complete_tx::bytes.L2::cache_hint [%0], [%1], %2, [%3], %4;"
                 ::"r"(dst), "l"(src), "r"(bytes), "r"(bar), "l"(pol) : "memory");
}
__device__ __forceinline__ void bar_cons() { asm volatile("bar.sync 1, 256;" ::: "memory"); }
template <int ID, int N> __device__ __forceinline__ void nbar_sync() { asm volatile("bar.sync %0, %1;" ::"n"(ID), "n"(N) : "memory"); }
template <int ID, int N> __device__ __forceinline__ void nbar_arrive() { asm volatile("bar.arrive %0, %1;" ::"n"(ID), "n"(N) : "memory"); }
__device__ __forceinline__ bool mbar_test(uint32_t bar, uint32_t parity) {
    uint32_t ok;
    asm volatile("{\n.reg .pred p;\nmbarrier.test_wait.parity.shared::cta.b64 p, [%1], %2;\nselp.u32 %0, 1, 0, p;\n}" : "=r"(ok) : "r"(bar), "r"(parity) : "memory");
    return ok;
}
__device__ __forceinline__ uint32_t pin(uint32_t v) { asm volatile("" : "+r"(v)); return v; }
template <class T> __device__ __forceinline__ T pin_hard(T v) { return __shfl_sync(0xffffffffu, v, threadIdx.x & 31); }
template <class T> __device__ __forceinline__ T* pin(T* v) { asm volatile("" : "+l"(v)); return v; }
__device__ __forceinline__ void ldsm4(uint32_t (&a)[4], uint32_t addr) {
    asm volatile("ldmatrix.sync.aligned.m8n8.x4.shared.b16 {%0,%1,%2,%3}, [%4];" : "=r"(a[0]), "=r"(a[1]), "=r"(a[2]), "=r"(a[3]) : "r"(addr) : "memory");
}
__device__ __forceinline__ void ldsm4t(uint32_t (&a)[4], uint32_t addr) {
    asm volatile("ldmatrix.sync.aligned.m8n8.x4.trans.shared.b16 {%0,%1,%2,%3}, [%4];" : "=r"(a[0]), "=r"(a[1]), "=r"(a[2]), "=r"(a[3]) : "r"(addr) : "memory");
}
__device__ __forceinline__ void mma16816(float (&c)[4], const uint32_t (&a)[4], uint32_t b0, uint32_t b1) {
    asm volatile("mma.sync.aligned.m16n8k16.row.col.f32.bf16.bf16.f32 {%0,%1,%2,%3}, {%4,%5,%6,%7}, {%8,%9}, {%0,%1,%2,%3};"
                 : "+f"(c[0]), "+f"(c[1]), "+f"(c[2]), "+f"(c[3]) : "r"(a[0]), "r"(a[1]), "r"(a[2]), "r"(a[3]), "r"(b0), "r"(b1));
}
__device__ __forceinline__ uint32_t lds32(uint32_t addr) { uint32_t v; asm volatile("ld.shared.u32 %0, [%1];" : "=r"(v) : "r"(addr) : "memory"); return v; }
__device__ __forceinline__ float lds_f32(uint32_t addr) { float v; asm volatile("ld.shared.f32 %0, [%1];" : "=f"(v) : "r"(addr) : "memory"); return v; }
__device__ __forceinline__ float2 lds_f32x2(uint32_t addr) { float2 v; asm volatile("ld.shared.v2.f32 {%0,%1}, [%2];" : "=f"(v.x), "=f"(v.y) : "r"(addr) : "memory"); return v; }
__device__ __forceinline__ float4 lds_f32x4(uint32_t addr) { float4 v; asm volatile("ld.shared.v4.f32 {%0,%1,%2,%3}, [%4];" : "=f"(v.x), "=f"(v.y), "=f"(v.z), "=f"(v.w) : "r"(addr) : "memory"); return v; }
__device__ __forceinline__ uint2 lds64(uint32_t addr) { uint2 v; asm volatile("ld.shared.v2.u32 {%0,%1}, [%2];" : "=r"(v.x), "=r"(v.y) : "r"(addr) : "memory"); return v; }
__device__ __forceinline__ uint4 lds128(uint32_t addr) { uint4 v; asm volatile("ld.shared.v4.u32 {%0,%1,%2,%3}, [%4];" : "=r"(v.x), "=r"(v.y), "=r"(v.z), "=r"(v.w) : "r"(addr) : "memory"); return v; }
__device__ __forceinline__ void sts16(uint32_t addr, uint32_t v) { asm volatile("st.shared.b16 [%0], %1;" ::"r"(addr), "h"((unsigned short)v) : "memory"); }
__device__ __forceinline__ void sts32(uint32_t addr, uint32_t v) { asm volatile("st.shared.u32 [%0], %1;" ::"r"(addr), "r"(v) : "memory"); }
__device__ __forceinline__ void sts_f32(uint32_t addr, float v) { asm volatile("st.shared.f32 [%0], %1;" ::"r"(addr), "f"(v) : "memory"); }
__device__ __forceinline__ void sts_f32x2(uint32_t addr, float a, float b) { asm volatile("st.shared.v2.f32 [%0], {%1,%2};" ::"r"(addr), "f"(a), "f"(b) : "memory"); }
__device__ __forceinline__ void sts128(uint32_t addr, uint4 v) { asm volatile("st.shared.v4.u32 [%0], {%1,%2,%3,%4};" ::"r"(addr), "r"(v.x), "r"(v.y), "r"(v.z), "r"(v.w) : "memory"); }
__device__ __forceinline__ uint4 ldg_relaxed(const uint32_t* p) {
    uint4 v;
    asm volatile("ld.relaxed.gpu.global.v4.u32 {%0,%1,%2,%3}, [%4];" : "=r"(v.x), "=r"(v.y), "=r"(v.z), "=r"(v.w) : "l"(p) : "memory");
    return v;
}
__device__ __forceinline__ void ldg_relaxed_if(bool on, uint4& v, const uint32_t* p) {
    asm volatile("{\n.reg .pred q;\nsetp.ne.u32 q, %5, 0;\n@q ld.relaxed.gpu.global.v4.u32 {%0,%1,%2,%3}, [%4];\n}"
                 : "+r"(v.x), "+r"(v.y), "+r"(v.z), "+r"(v.w) : "l"(p), "r"((uint32_t)on) : "memory");
}
__device__ __forceinline__ void stg_relaxed2_if(bool on, uint32_t* p, uint32_t a, uint32_t b) {
    asm volatile("{\n.reg .pred q;\nsetp.ne.u32 q, %3, 0;\n@q st.relaxed.gpu.global.v2.u32 [%0], {%1,%2};\n}" ::"l"(p), "r"(a), "r"(b), "r"((uint32_t)on) : "memory");
}
__device__ __forceinline__ uint32_t ldg_relaxed32(const uint32_t* p) { uint32_t v; asm volatile("ld.relaxed.gpu.global.u32 %0, [%1];" : "=r"(v) : "l"(p) : "memory"); return v; }
__device__ __forceinline__ void stg_relaxed(uint32_t* p, uint32_t v) { asm volatile("st.relaxed.gpu.global.u32 [%0], %1;" ::"l"(p), "r"(v) : "memory"); }
__device__ __forceinline__ void stg_zero4(uint32_t* p) { asm volatile("st.relaxed.gpu.global.v4.u32 [%0], {%1,%1,%1,%1};" ::"l"(p), "r"(0u) : "memory"); }
__device__ __forceinline__ bool ready(const uint4& v) { return (v.x != 0u) & (v.y != 0u) & (v.z != 0u) & (v.w != 0u); }
__device__ __forceinline__ uint32_t min4(const uint4& v) { return min(__vimin3_u32(v.x, v.y, v.z), v.w); }
__device__ __forceinline__ uint4 inv4(const uint4& v) { return make_uint4(~v.x, ~v.y, ~v.z, ~v.w); }
__device__ __forceinline__ uint32_t pack_bf(float lo, float hi) {
    uint32_t r;
    asm("cvt.rn.bf16x2.f32 %0, %1, %2;" : "=r"(r) : "f"(hi), "f"(lo));
    return r;
}
__device__ __forceinline__ float bfr(float x) { return __uint_as_float(pack_bf(0.f, x) & 0xffff0000u); }
__device__ __forceinline__ float bf_lo(uint32_t w) { return __uint_as_float(w << 16); }
__device__ __forceinline__ float bf_hi(uint32_t w) { return __uint_as_float(w & 0xffff0000u); }
__device__ __forceinline__ float bf2f(__nv_bfloat16 v) { return __bfloat162float(v); }
__device__ __forceinline__ float ex2(float x) { float y; asm("ex2.approx.ftz.f32 %0, %1;" : "=f"(y) : "f"(x)); return y; }
__device__ __forceinline__ float rcp_fast(float x) { float y; asm("rcp.approx.ftz.f32 %0, %1;" : "=f"(y) : "f"(x)); return y; }
__device__ __forceinline__ float rsqrt_fast(float x) { float y; asm("rsqrt.approx.ftz.f32 %0, %1;" : "=f"(y) : "f"(x)); return y; }
__device__ __forceinline__ float sqrt_fast(float x) { float y; asm("sqrt.approx.f32 %0, %1;" : "=f"(y) : "f"(x)); return y; }
__device__ __forceinline__ uint32_t bf2_add(uint32_t a, uint32_t b) { uint32_t r; asm("add.rn.bf16x2 %0, %1, %2;" : "=r"(r) : "r"(a), "r"(b)); return r; }
__device__ __forceinline__ uint32_t bf2_sub(uint32_t a, uint32_t b) { uint32_t r; asm("sub.rn.bf16x2 %0, %1, %2;" : "=r"(r) : "r"(a), "r"(b)); return r; }
__device__ __forceinline__ uint32_t bf2_mul(uint32_t a, uint32_t b) { uint32_t r; asm("mul.rn.bf16x2 %0, %1, %2;" : "=r"(r) : "r"(a), "r"(b)); return r; }
__device__ __forceinline__ uint32_t gtime32() { uint32_t c; asm volatile("mov.u32 %0, %%globaltimer_lo;" : "=r"(c)); return c; }
__device__ __forceinline__ uint32_t clock32() { uint32_t c; asm volatile("mov.u32 %0, %%clock;" : "=r"(c)); return c; }

__device__ __forceinline__ float warp_sum(float v) {
#pragma unroll
    for (int o = 16; o > 0; o >>= 1) v += __shfl_xor_sync(0xffffffffu, v, o);
    return v;
}

struct Params {
    const __nv_bfloat16 *x, *kc, *vc, *b1, *b2, *c;
    __nv_bfloat16* out;
};

__device__ __forceinline__ void tma2d(uint32_t dst, const CUtensorMap* tm, int x, int y, uint32_t bar) {
    asm volatile("cp.async.bulk.tensor.2d.shared::cluster.global.mbarrier::complete_tx::bytes [%0], [%1, {%2, %3}], [%4];"
                 ::"r"(dst), "l"(tm), "r"(x), "r"(y), "r"(bar) : "memory");
}

__device__ __forceinline__ void tma2d_hint(uint32_t dst, const CUtensorMap* tm, int x, int y, uint32_t bar, uint64_t pol) {
    asm volatile("cp.async.bulk.tensor.2d.shared::cluster.global.mbarrier::complete_tx::bytes.L2::cache_hint [%0], [%1, {%2, %3}], [%4], %5;"
                 ::"r"(dst), "l"(tm), "r"(x), "r"(y), "r"(bar), "l"(pol) : "memory");
}
__device__ __forceinline__ uint32_t flag(float v) { return __float_as_uint(v) | 1u; }
__device__ __forceinline__ uint32_t and3(uint32_t a, uint32_t b, uint32_t c) { uint32_t r; asm("lop3.b32 %0, %1, %2, %3, 0x80;" : "=r"(r) : "r"(a), "r"(b), "r"(c)); return r; }
__device__ __forceinline__ uint32_t* slot_ptr(uint32_t lo) {
    uint32_t* r;
    asm volatile("mov.b64 %0, {%1, %2};" : "=l"(r) : "r"(lo), "r"((uint32_t)((size_t)slot(0, 0) >> 32)));
    return r;
}

__device__ __forceinline__ void load_bfrag(uint32_t vec, int stride, int k0, int g, int t, uint32_t& b0, uint32_t& b1) {
    uint32_t a = vec + (g & 3) * stride + (k0 + 2 * t) * 2;
    b0 = lds32(a);
    b1 = lds32(a + 16);
}

__device__ __forceinline__ void ln_finish(float pivot, float sum, float sumsq, uint32_t& m2, float& rden) {
    float dm = sum * (1.f / D);
    float var = fmaxf(sumsq * (1.f / D) - dm * dm, 0.f);
    float mean = pivot + dm;
    m2 = pack_bf(mean, mean);
    rden = rcp_fast(bfr(sqrt_fast(bfr(bfr(var) + 1e-5f))));
}
__device__ __forceinline__ uint32_t ln_mod_pair(uint32_t xw, uint32_t cw, uint32_t sw, uint32_t m2, float rden) {
    uint32_t d = bf2_sub(xw, m2);
    uint32_t ln = pack_bf(bf_lo(d) * rden, bf_hi(d) * rden);
    return bf2_add(bf2_mul(ln, bf2_add(cw, 0x3f803f80u)), sw);
}
__device__ __forceinline__ uint4 ln_mod4(const uint4& x, const uint4& c, const uint4& s, uint32_t m2, float rden) {
    return make_uint4(ln_mod_pair(x.x, c.x, s.x, m2, rden), ln_mod_pair(x.y, c.y, s.y, m2, rden),
                      ln_mod_pair(x.z, c.z, s.z, m2, rden), ln_mod_pair(x.w, c.w, s.w, m2, rden));
}
__device__ __forceinline__ void acc_stats(const uint4& v, float pv, float& s, float& q) {
    const float a0 = bf_lo(v.x) - pv, a1 = bf_hi(v.x) - pv, a2 = bf_lo(v.y) - pv, a3 = bf_hi(v.y) - pv;
    const float a4 = bf_lo(v.z) - pv, a5 = bf_hi(v.z) - pv, a6 = bf_lo(v.w) - pv, a7 = bf_hi(v.w) - pv;
    s += ((a0 + a1) + (a2 + a3)) + ((a4 + a5) + (a6 + a7));
    q += (fmaf(a0, a0, a1 * a1) + fmaf(a2, a2, a3 * a3)) + (fmaf(a4, a4, a5 * a5) + fmaf(a6, a6, a7 * a7));
}
__device__ __forceinline__ uint32_t* mod_slot(int kind, int j, int b) { return g_mod + (kind * 20 + (j >> 2)) * 64 + b * 16 + (j & 3) * 4; }

template <int N>
__device__ __forceinline__ void poll_n(uint4 (&v)[N], const uint32_t* const* ptr, const bool* on) {
    bool pend[N];
#pragma unroll
    for (int i = 0; i < N; i++) pend[i] = on[i];
    int it = 0;
    while (true) {
#pragma unroll
        for (int i = 0; i < N; i++) if (pend[i]) v[i] = ldg_relaxed(ptr[i]);
        bool any = false;
#pragma unroll
        for (int i = 0; i < N; i++) { pend[i] = pend[i] && !ready(v[i]); any |= pend[i]; }
        if (!__any_sync(0xffffffffu, any)) break;
        if (++it > SPIN_LIMIT) __trap();
    }
#pragma unroll
    for (int i = 0; i < N; i++) v[i] = inv4(v[i]);
}
__device__ __forceinline__ uint4 poll1(const uint32_t* p, bool on) {
    uint4 v[1] = {make_uint4(0, 0, 0, 0)};
    const uint32_t* const ptr[1] = {p};
    const bool o[1] = {on};
    poll_n<1>(v, ptr, o);
    return v[0];
}

__device__ __forceinline__ void gelu_stage(uint32_t sb, int m, int lane) {
    const int g = lane >> 2, b = lane & 3;
    const uint32_t y_ld = pin_hard(sb + SC_Y + m * 256 + lane * 8), s_ld = pin_hard(sb + SC_ST + b * 64);
    const uint32_t h_st = pin_hard(sb + SC_H1 + b * 64 + (g >> 1) * 16 + m * 8 + (g & 1) * 2);
    float a0 = 0.f, b0 = lds_f32(sb + OWN_B1 + (16 * m + g) * 4), a1 = 0.f, b1 = lds_f32(sb + OWN_B1 + (16 * m + g + 8) * 4);
    const float piv = bf_hi(lds32(sb + OFF_STAT + b * 8));
    nbar_sync<NB_AB, 320>();
#pragma unroll
    for (int w = 0; w < 8; w++) {
        const float4 t = lds_f32x4(sb + SC_AB + w * 1024 + m * 512 + lane * 16);
        a0 += t.x; b0 += t.y; a1 += t.z; b1 += t.w;
    }
    sts128(sb + SC_AB + m * 512 + lane * 16, make_uint4(__float_as_uint(a0), __float_as_uint(b0), __float_as_uint(a1), __float_as_uint(b1)));
    nbar_sync<NB_Y, 320>();
    float4 q[4];
    float2 y[8];
#pragma unroll
    for (int i = 0; i < 4; i++) q[i] = lds_f32x4(s_ld + i * 16);
#pragma unroll
    for (int w = 0; w < 8; w++) y[w] = lds_f32x2(y_ld + w * 512);
    const float dm = (((q[0].y + q[0].w) + (q[1].y + q[1].w)) + ((q[2].y + q[2].w) + (q[3].y + q[3].w))) * (1.f / D);
    const float sq = ((q[0].x + q[0].z) + (q[1].x + q[1].z)) + ((q[2].x + q[2].z) + (q[3].x + q[3].z));
    const float r = rsqrt_fast(fmaxf(fmaf(-dm, dm, fmaf(sq, 1.f / D, 1e-5f)), 1e-5f));
    const float y0 = ((y[0].x + y[1].x) + (y[2].x + y[3].x)) + ((y[4].x + y[5].x) + (y[6].x + y[7].x));
    const float y1 = ((y[0].y + y[1].y) + (y[2].y + y[3].y)) + ((y[4].y + y[5].y) + (y[6].y + y[7].y));
    const float dmr = piv - bfr(piv - dm);
    const float u0 = fmaf(r, fmaf(dmr, a0, -y0), b0), u1 = fmaf(r, fmaf(dmr, a1, -y1), b1);
    const float e0 = ex2(u0 * fmaf(u0 * u0, -0.044715f * 2.302208198144325f, -2.302208198144325f));
    const float e1 = ex2(u1 * fmaf(u1 * u1, -0.044715f * 2.302208198144325f, -2.302208198144325f));
    sts16(h_st, pack_bf(u0 * rcp_fast(1.f + e0), 0.f));
    sts16(h_st + 4, pack_bf(u1 * rcp_fast(1.f + e1), 0.f));
#pragma unroll
    for (int w = 0; w < 8; w++) asm volatile("bar.arrive %0, 96;" ::"r"(NB_O + w) : "memory");
}

struct Roles { bool is_f, is_owner; int f, own; };
__device__ __forceinline__ Roles roles(int cta) {
    Roles r;
    r.f = (cta * 27) >> 6;
    r.is_f = (((cta + 1) * 27) >> 6) != r.f;
    r.is_owner = !r.is_f || r.f % 9 == 4;
    r.own = r.is_f ? 74 + r.f / 9 : cta - r.f;
    return r;
}

__global__ void __launch_bounds__(NTHREADS, 1)
fused_kernel(const Params p, const __grid_constant__ CUtensorMap tm_wmod, const __grid_constant__ CUtensorMap tm_wq,
             const __grid_constant__ CUtensorMap tm_wo, const __grid_constant__ CUtensorMap tm_w1, const __grid_constant__ CUtensorMap tm_w2,
             const __grid_constant__ CUtensorMap tm_v, const __grid_constant__ CUtensorMap tm_gb) {
    extern __shared__ __align__(1024) unsigned char smem[];
    const uint32_t t_start = gtime32();
    if (threadIdx.x == 0) {
        const uint32_t c_ = blockIdx.x;
        const uint32_t off = ((c_ & 3) << 26) + (c_ >> 2) * (1u << 21) + (ROT(c_) << 14) + (SK - WIN) * DH * 2;
        asm volatile("cp.async.bulk.prefetch.L2.global.L2::cache_hint [%0], %1, %2;" ::"l"((const char*)p.kc + off), "r"(TILE_BYTES), "l"(0x12f0000000000000ull  ) : "memory");
    }
    const uint32_t sb = smem_u32(smem);
    const int cta = blockIdx.x;
    const int head = cta >> 2, bown = cta & 3;
    const int rot = ROT(cta);
    const char* const kb = (const char*)(p.kc + ((size_t)(bown * NH + head) * SK + (SK - WIN)) * DH);
    uint64_t pol = 0;
    if (threadIdx.x == 256) {
        mbar_init(sb + OFF_BAR, 1);
        asm volatile("fence.mbarrier_init.release.cluster;" ::: "memory");
        asm volatile("createpolicy.fractional.L2::evict_first.b64 %0, 1.0;" : "=l"(pol));
        mbar_expect_tx(sb + OFF_BAR, TILE_BYTES);
        bulk_load(sb + OFF_RING, kb + (size_t)rot * TILE_BYTES, TILE_BYTES, sb + OFF_BAR, pol);
        if ((((head + 1) * 5) >> 4) != ((head * 5) >> 4)) {
            const uint32_t bar = sb + OFF_BAR + 2 * NS * 8;
            mbar_init(bar, 1);
            asm volatile("fence.mbarrier_init.release.cluster;" ::: "memory");
            mbar_expect_tx(bar, D * 64);
#pragma unroll 1
            for (int r = 0; r < D; r += 160) tma2d(sb + X_WM + r * 64, &tm_wmod, 32 * (((head * 5) >> 4) * 4 + bown), r, bar);
        }
    }
    const uint32_t bar_full = sb + OFF_BAR, bar_empty = bar_full + NS * 8;
    const uint32_t bar_wm = bar_empty + NS * 8, bar_wq = bar_wm + 8, bar_xfree = bar_wq + 8, bar_wo = bar_xfree + 8  ;
    const uint32_t bar_w1 = bar_wo + 40  , bar_w2 = bar_w1 + 32  , bar_help = bar_w2 + 80, bar_v = bar_help + 8  ;
    const uint32_t bar_gb = bar_v + 32  , bar_x1 = bar_gb + 32;
    const int tid = threadIdx.x, warp = tid >> 5, lane = tid & 31;
    const Roles role = roles(cta);
    const bool is_f = role.is_f, is_owner = role.is_owner;
    const int f = role.f, own = role.own;
    const bool crit = (((head + 1) * 5) >> 4) != ((head * 5) >> 4);
    const int mr = cta - ((head * 5) >> 4) * 4, mq = ((head * 5) >> 4) * 4 + bown;
    const int ml = mr * 31 / 44;
    const bool late = !crit && (mr + 1) * 31 / 44 != ml;
    const int mc = crit ? mq : ml < 60 ? 40 + ml : 58 + ml;
    const bool gb_own = is_owner && own < 72;

    PROF_DECL
    PROF(0);
    uint4 xa = make_uint4(0, 0, 0, 0), xb = xa, ca0 = xa, ca1 = xa, xs[3] = {xa, xa, xa};
    uint32_t own0 = 0;
    __nv_bfloat16 own2 = __float2bfloat16(0.f);
    if (warp < 8) {
        xa = *(const uint4*)(p.x + (tid & 3) * D + (tid >> 2) * 8);
        ca0 = ((const uint4*)p.c)[tid];
        if (tid < 64) { xb = *(const uint4*)(p.x + (tid & 3) * D + (64 + (tid >> 2)) * 8); ca1 = ((const uint4*)p.c)[256 + tid]; }
        if (warp < 4) {
#pragma unroll
            for (int i = 0; i < 3; i++) if (lane + 32 * i < 80) xs[i] = ((const uint4*)p.x)[warp * 80 + lane + 32 * i];
        } else if (warp == 4) {
            if (is_owner) own0 = *(const uint32_t*)((lane < 16 ? p.x + (lane >> 2) * D : p.b2) + 8 * own + 2 * (lane & 3));
            if (is_f) own2 = p.b1[32 * f + lane];
        }
    }
    const char* const vb = (const char*)(p.vc + ((size_t)(bown * NH + head) * SK + (SK - WIN)) * DH);
    const uint32_t bar_first = crit ? bar_wm : bar_wq;
    if (threadIdx.x == 256) {
        if (!crit) {
            mbar_init(bar_wq, 1);
            asm volatile("fence.mbarrier_init.release.cluster;" ::: "memory");
            mbar_expect_tx(bar_wq, D * 64);
            const uint32_t c0 = clock32();
            while (clock32() - c0 < WQ_DELAY) { }
#pragma unroll
            for (int r = 0; r < D; r += 160) tma2d(sb + X_WQ + r * 64, &tm_wq, 32 * cta, r, bar_wq);
        }
    } else if (threadIdx.x == 0) {
#pragma unroll
        for (int s = 0; s < NS; s++) { if (s) mbar_init(bar_full + s * 8, 1); mbar_init(bar_empty + s * 8, 4); }
        mbar_init(crit ? bar_wq : bar_wm, 1);
        mbar_init(bar_xfree, 1);
#pragma unroll
        for (int i = 0; i < 5; i++) { mbar_init(bar_wo + i * 8, 1); mbar_init(bar_w2 + i * 16, 1); mbar_init(bar_w2 + i * 16 + 8, 1); }
        mbar_init(bar_help, 1); mbar_init(bar_x1, 1);
#pragma unroll
        for (int i = 0; i < 4; i++) { mbar_init(bar_v + i * 8, 1); mbar_init(bar_w1 + i * 8, 1); mbar_init(bar_gb + i * 8, 1); }
        asm volatile("fence.mbarrier_init.release.cluster;" ::: "memory");
    }
    __syncthreads();

    if (warp == 8) {
        if (lane == 0) {
            int tp = NS;
            int sched = PACE_A - NS * PACE_TAU;
            int phase = 0;
#pragma unroll 1
            for (int t = 1; t <= NITEM; t++) {
                if (t == 1) mbar_wait(bar_full, 0);
                if (t == 2) {
                    mbar_wait(bar_first, 0);
                    if (crit) {
                        mbar_expect_tx(bar_wq, D * 64);
#pragma unroll 1
                        for (int r = 0; r < D; r += 160) tma2d(sb + X_WQ + r * 64, &tm_wq, 32 * cta, r, bar_wq);
                    }
                }
                if (t == 3) {
                    asm volatile("prefetch.tensormap [%0];" ::"l"(&tm_v) : "memory");
                    asm volatile("prefetch.tensormap [%0];" ::"l"(&tm_wo) : "memory");
                    asm volatile("prefetch.tensormap [%0];" ::"l"(&tm_w1) : "memory");
                    asm volatile("prefetch.tensormap [%0];" ::"l"(&tm_w2) : "memory");
                    asm volatile("prefetch.tensormap [%0];" ::"l"(&tm_gb) : "memory");
                }
                if (t == NS && late) {
                    mbar_wait(bar_full + (NS - INFLIGHT) * 8, 0);
                    mbar_expect_tx(bar_wm, D * 64);
#pragma unroll 1
                    for (int r = 0; r < D; r += 160) tma2d(sb + X_WM + r * 64, &tm_wmod, 32 * mc, r, bar_wm);
                }
                if (t >= NS && t < PF_END) {
                    int it = 0;
                    while (!mbar_test(bar_empty + (t & (NS - 1)) * 8, ((t >> 3) - 1) & 1)) {
                        if (tp < PF_END && (int)(gtime32() - t_start) >= PACE_A + (tp - NS) * PACE_TAU) {
                            asm volatile("cp.async.bulk.prefetch.L2.global.L2::cache_hint [%0], %1, %2;"
                                         ::"l"(((tp & 1) ? vb : kb) + (size_t)(((tp >> 1) + rot) & (NITEM / 2 - 1)) * TILE_BYTES), "r"(TILE_BYTES), "l"(pol) : "memory");
                            tp++;
                        }
                        if (++it > 16 * SPIN_LIMIT) __trap();
                    }
                    if (tp <= t) tp = t + 1;
                }
                if (t == NITEM) {
                    mbar_wait(bar_xfree, 0);
                    const uint32_t t_ref = t_start + phase + (NITEM - 1) * PACE_TAU;
#pragma unroll 1
                    for (int i = 0; i < 5; i++) {
                        while ((int)(gtime32() - t_ref) < WO_T + i * WO_S) { }
                        mbar_expect_tx(bar_wo + i * 8, DH * 64);
                        tma2d(sb + X_WO + i * (DH * 64), &tm_wo, bown * 160 + i * 32, head * DH, bar_wo + i * 8);
                    }
                    if (gb_own) {
                        mbar_wait(bar_empty + 3 * 8, ((NITEM >> 3) - 1) & 1);
                        mbar_wait(bar_x1, 0);
                        { const uint32_t c0 = clock32(); while (clock32() - c0 < GB_EV) { } }
                        while ((int)(gtime32() - t_ref) < GB_T) { }
#pragma unroll 1
                        for (int i = 0; i < 4; i++) {
                            mbar_expect_tx(bar_gb + i * 8, 160 * 16);
                            tma2d(sb + X_GB + i * (160 * 16), &tm_gb, 5 * D + 8 * own, 160 * i, bar_gb + i * 8);
                        }
                    }
                    if (is_f) {
#pragma unroll 1
                        for (int i = 0; i < 3; i++) mbar_wait(bar_empty + i * 8, ((NITEM >> 3) - 1) & 1);
                        while ((int)(gtime32() - t_ref) < W1_T) { }
#pragma unroll 1
                        for (int i = 0; i < 4; i++) {
                            mbar_expect_tx(bar_w1 + i * 8, 160 * 64);
                            tma2d(sb + X_W1 + i * (160 * 64), &tm_w1, 32 * f, 160 * i, bar_w1 + i * 8);
                        }
                        while ((int)(gtime32() - t_ref) < W2_T) { }
#pragma unroll 1
                        for (int i = 0; i < 10; i++) {
                            mbar_expect_tx(bar_w2 + i * 8, 4096);
                            tma2d(sb + X_W2 + i * 4096, &tm_w2, 64 * i, 32 * f, bar_w2 + i * 8);
                        }
                    }
                    break;
                }
                const int s = t & (NS - 1);
                if (t >= NS) {
                    mbar_wait(bar_empty + s * 8, ((t >> 3) - 1) & 1);
                    while ((int)(gtime32() - t_start) < sched + t * PACE_TAU) { }
                } else if (t >= INFLIGHT) {
                    mbar_wait(bar_full + (t - INFLIGHT) * 8, 0);
                }
                if (t < NITEM - 2) {
                    const int pair = t == NITEM - 3 ? NITEM / 2 - 1 : t >> 1;
                    mbar_expect_tx(bar_full + s * 8, TILE_BYTES);
                    bulk_load(sb + OFF_RING + s * TILE_BYTES, ((t & 1) && t != NITEM - 3 ? vb : kb) + (size_t)((pair + rot) & (NITEM / 2 - 1)) * TILE_BYTES, TILE_BYTES, bar_full + s * 8, pol);
                } else {
                    const int row = (bown * NH + head) * SK + (SK - WIN) + ((t - NITEM / 2 + rot) & (NITEM / 2 - 1)) * TILE_KEYS;
#pragma unroll 1
                    for (int i = 0; i < 2; i++) {
                        const uint32_t bar = bar_v + (2 * (t - (NITEM - 2)) + i) * 8;
                        mbar_expect_tx(bar, TILE_BYTES / 2);
                        tma2d_hint(sb + OFF_RING + s * TILE_BYTES + i * (TILE_BYTES / 2), &tm_v, 64 * i, row, bar, pol);
                    }
                }
                if (t >= PH_FIRST && (t & 7) == PH_LAG) {
                    const int now = (int)(gtime32() - t_start) - (t - PH_LAG) * PACE_TAU;
                    uint32_t ph;
                    asm volatile("atom.relaxed.gpu.global.add.u32 %0, [%1], 0;" : "=r"(ph) : "l"(g_phase + (t >> 3) * 32) : "memory");
                    phase = (int)min(((ph & 0xffffffu) * 4 + (NCTA - (ph >> 24)) * now) / NCTA, 65535u);
                    sched += (phase - LAT_T - sched) * 3 / 4;
                }
            }
        }
        __syncwarp();
    }

    if (warp == 9) {
        int side = 0;
        if (lane == 0) {
            uint32_t best[2] = {~0u, ~0u};
#pragma unroll
            for (int i = 0; i < 4; i++) stg_zero4(slot(SL_SIDE, i >> 1) + cta * 8 + (i & 1) * 4);
            uint32_t n = 0;
#pragma unroll 1
            for (int i = 0; (i & 1) || (n < NPROBE - 1 && (int)(gtime32() - t_start) < PROBE_END); i++) {
                uint32_t t0 = clock32(), t1;
                asm volatile("atom.relaxed.gpu.global.inc.u32 %0, [%1], %2;" : "=r"(n) : "l"(slot(SL_SIDE, i & 1) + cta * 8), "r"(0xffffu) : "memory");
                asm volatile("{\n.reg .pred p;\nsetp.ne.u32 p, %1, 0xffffffff;\nmov.u32 %0, 0;\n@p mov.u32 %0, %%clock;\n}" : "=r"(t1) : "r"(n) : "memory");
                if (i & 1) best[1] = min(best[1], t1 - t0); else best[0] = min(best[0], t1 - t0);
            }
            side = best[1] < best[0];
        }
        side = __shfl_sync(0xffffffffu, side, 0);
        HPROF(1);
        mbar_wait(bar_full + (NS - 1) * 8, 0);
        stg_zero4(slot(SL_O + (cta >> 4), lane >> 4) + (cta & 15) * 64 + (lane & 15) * 4);
        if (is_owner) {
#pragma unroll 1
            for (int i = lane; i < NH * 8; i += 32) stg_zero4(slot(SL_P1 + own, side) + i * 4);
#pragma unroll 1
            for (int i = lane; i < NF * 8; i += 32) stg_zero4(slot(SL_P2 + 2 * own + (i >> 8), side) + (i & 255) * 4);
            if (lane < 8) stg_zero4(slot(SL_X1 + own / 30, lane >> 2) + (own % 30) * 32 + (lane & 3) * 4);
        }
        __threadfence();
        __syncwarp();
        if (lane == 0) stg_relaxed(g_clr + cta, 1u + side);
        HPROF(0);
        HPROF(2);
        while ((int)(gtime32() - t_start) < CLR_CHECK) __nanosleep(1000);
        mbar_wait(bar_xfree, 0);
        {
            uint4 v = make_uint4(1, 1, 1, 1), gv = v, mv[20];
#pragma unroll
            for (int i = 0; i < 20; i++) mv[i] = v;
#pragma unroll 1
            for (int it = 0;; it++) {
                v = ldg_relaxed(g_clr + lane * 4);

                ldg_relaxed_if(is_owner && lane < (gb_own ? 4 : 8), gv, mod_slot(lane < 4 ? 2 : 5, own, lane & 3));
#pragma unroll
                for (int i = 0; i < 20; i++) ldg_relaxed_if(is_f, mv[i], mod_slot(3, 8 * i + (lane >> 2), lane & 3));
                bool ok = ready(v) && ready(gv);
#pragma unroll
                for (int i = 0; i < 20; i++) ok = ok && ready(mv[i]);
                if (__all_sync(0xffffffffu, ok)) break;
                if (it > SPIN_LIMIT) __trap();
                __nanosleep(2000);
            }
            const uint32_t w[4] = {v.x, v.y, v.z, v.w};
#pragma unroll
            for (int i = 0; i < 4; i++) {
                const Roles r = roles(4 * lane + i);
                if (r.is_owner) {
                    sts32(sb + OFF_TAB1 + r.own * 4, (uint32_t)(size_t)(slot(SL_P1 + r.own, w[i] - 1) + head * 32));
                    sts32(sb + OFF_TAB2 + r.own * 4, (uint32_t)(size_t)(slot(SL_P2 + 2 * r.own + (f >> 5), w[i] - 1) + (f & 31) * 32));
                }
            }
            if (lane == 0) sts32(sb + OFF_SIDE, side);
            if (lane < 8) sts128(sb + OWN_GA + lane * 16, inv4(gv));
            const uint32_t dst = sb + OFF_VB + (lane & 3) * VEC_STRIDE + (lane >> 2) * 16;
#pragma unroll
            for (int i = 0; i < 10; i++) {
                const uint4 c = inv4(mv[10 + i]);
                sts128(dst + i * 128, make_uint4(bf2_add(c.x, 0x3f803f80u), bf2_add(c.y, 0x3f803f80u), bf2_add(c.z, 0x3f803f80u), bf2_add(c.w, 0x3f803f80u)));
                sts128(dst + (OFF_RED - OFF_VB) + i * 128, inv4(mv[i]));
            }
        }
        asm volatile("fence.acq_rel.gpu;" ::: "memory");
        __syncwarp();
        HPROF(3);
        if (lane == 0) mbar_arrive(bar_help);
        {
            const uint32_t* const src = pin(slot(SL_O + (cta >> 4), side) + (cta & 12) * 64 + lane * 4);
            const uint32_t dst = pin(sb + OFF_O + (lane >> 4) * O_STRIDE + (lane & 15) * 16);
            mbar_wait(bar_v + 16, 0);
            mbar_wait(bar_v + 24, 0);
            uint4 v[2];
            const uint32_t* const ptr[2] = {src, src + 128};
            const bool on[2] = {true, true};
            poll_n<2>(v, ptr, on);
            sts128(dst, v[0]);
            sts128(dst + 2 * O_STRIDE, v[1]);
#pragma unroll
            for (int w = 0; w < 8; w++) asm volatile("bar.arrive %0, 64;" ::"r"(NB_O + w) : "memory");
        }
        HPROF(4);
    }
    if (warp >= 8) {
        if (gb_own && warp == 9) {
            uint32_t a[20][4];
#pragma unroll
            for (int i = 0; i < 20; i++) ldsm4(a[i], sb + OFF_VA + (lane & 3) * VEC_STRIDE + (4 * i + (lane >> 3)) * 16);
            float c[4][4];
#pragma unroll
            for (int i = 0; i < 4; i++) c[i][0] = c[i][1] = c[i][2] = c[i][3] = 0.f;
#pragma unroll
            for (int bx = 0; bx < 4; bx++) {
                mbar_wait(bar_gb + bx * 8, 0);
#pragma unroll
                for (int i = 5 * bx; i < 5 * bx + 5; i++) {
                    uint32_t w[4];
                    ldsm4t(w, sb + X_GB + (32 * i + lane) * 16);
                    const uint32_t a0[4] = {a[i][0], 0u, a[i][1], 0u}, a1[4] = {a[i][2], 0u, a[i][3], 0u};
                    mma16816(c[(2 * i) & 3], a0, w[0], w[1]);
                    mma16816(c[(2 * i + 1) & 3], a1, w[2], w[3]);
                }
            }
            if (lane < 16) sts32(sb + OWN_GB + lane * 4, pack_bf((c[0][0] + c[1][0]) + (c[2][0] + c[3][0]), (c[0][1] + c[1][1]) + (c[2][1] + c[3][1])));
            HPROF(6);
        }
        if (is_owner && warp == 9) nbar_arrive<NB_E6, 288>();
        if (is_f) gelu_stage(sb, warp - 8, lane);
        return;
    }

    const int g = lane >> 2, t4 = lane & 3;
    const int mi = lane >> 3, r8 = lane & 7;

    {
        auto silu4 = [&](const uint4& cv) {
            uint32_t w4[4] = {cv.x, cv.y, cv.z, cv.w};
#pragma unroll
            for (int e = 0; e < 4; e++) {
                float c0 = bf_lo(w4[e]), c1 = bf_hi(w4[e]);
                w4[e] = pack_bf(c0 * rcp_fast(1.f + ex2(-1.4426950408889634f * c0)), c1 * rcp_fast(1.f + ex2(-1.4426950408889634f * c1)));
            }
            return make_uint4(w4[0], w4[1], w4[2], w4[3]);
        };
        {
            uint4 v = silu4(ca0);
            sts128(sb + OFF_VA + (tid / 80) * VEC_STRIDE + (tid % 80) * 16, v);
            if (tid < 64) { v = silu4(ca1); sts128(sb + OFF_VA + 3 * VEC_STRIDE + (16 + tid) * 16, v); }
        }
        if (warp < 4) {
            float s = 0.f, q = 0.f;
            const float pv = __shfl_sync(0xffffffffu, bf_lo(xs[0].x), 0);
#pragma unroll
            for (int i = 0; i < 3; i++) if (i < 2 || lane < 16) acc_stats(xs[i], pv, s, q);
#pragma unroll
            for (int of = 16; of > 0; of >>= 1) { s += __shfl_xor_sync(0xffffffffu, s, of); q += __shfl_xor_sync(0xffffffffu, q, of); }
            uint32_t m2; float rden;
            ln_finish(pv, s, q, m2, rden);
            if (lane == 0) { sts32(sb + OFF_STAT + warp * 8, m2); sts_f32(sb + OFF_STAT + warp * 8 + 4, rden); }
        } else if (warp == 4) {
            sts32(sb + OWN_X + lane * 4, bf2_add(own0, 0u));
            sts_f32(sb + OWN_B1 + lane * 4, bf2f(own2));
        }
    }
    bar_cons();
    PROF(24);
    uint32_t qf[8][2];
    float o[8][4];
#pragma unroll
    for (int c = 0; c < 8; c++) { o[c][0] = o[c][1] = o[c][2] = o[c][3] = 0.f; }
    float m_run = -INFINITY, l_run = 0.f;
    const bool diag = (t4 == (g >> 1));
    const bool odd = g & 1;
    const uint32_t koff = (warp & 3) * 4096 + (r8 + 8 * (mi & 1)) * 256 + (mi >> 1) * 128 + (r8 << 4);
    const uint32_t voff = TILE_BYTES + (warp & 3) * 4096 + (r8 + 8 * (mi >> 1)) * 256 + (mi & 1) * 128 + (r8 << 4);
    const int src0 = (2 * t4) * 4 + t4, src1 = (2 * t4 + 1) * 4 + t4;
#pragma unroll 1
    for (int step = crit ? 0 : 1; step < 3; step++) {
        if (step < 2 || late) {
            if (step == 1) {
                if (!crit) mbar_wait(bar_wq, 0);
                const uint32_t m2 = lds32(sb + OFF_STAT + (tid & 3) * 8);
                const float rden = lds_f32(sb + OFF_STAT + (tid & 3) * 8 + 4);
                uint4 v[4];
                v[2] = v[3] = make_uint4(1, 1, 1, 1);
                const uint32_t* const p0 = mod_slot(0, tid >> 2, tid & 3);
                while ((int)(gtime32() - t_start) < MOD_T) { }
                PROF(2);
#pragma unroll 1
                for (int it = 0;; it++) {
                    ldg_relaxed_if(tid < 64, v[2], p0 + 16 * 64);
                    ldg_relaxed_if(tid < 64, v[3], p0 + 36 * 64);
                    v[0] = ldg_relaxed(p0);
                    v[1] = ldg_relaxed(p0 + 20 * 64);
                    if (__all_sync(0xffffffffu, min(min(min4(v[0]), min4(v[1])), min(min4(v[2]), min4(v[3]))) != 0u)) break;
                    if (it > SPIN_LIMIT) __trap();
                }
#pragma unroll
                for (int i = 0; i < 4; i++) v[i] = inv4(v[i]);
                PROF(3);
                uint4 h0 = ln_mod4(xa, v[1], v[0], m2, rden);
                sts128(sb + OFF_VB + (tid & 3) * VEC_STRIDE + (tid >> 2) * 16, h0);
                if (tid < 64) {
                    h0 = ln_mod4(xb, v[3], v[2], m2, rden);
                    sts128(sb + OFF_VB + (tid & 3) * VEC_STRIDE + (64 + (tid >> 2)) * 16, h0);
                }
            }
            mbar_wait(step == 1 ? bar_wq : bar_wm, 0);
            bar_cons();
            const uint32_t strip = sb + (step == 1 ? X_WQ : X_WM), vec = sb + (step == 1 ? OFF_VB : OFF_VA);
            float acc[2][4];
#pragma unroll
            for (int m = 0; m < 2; m++) { acc[m][0] = acc[m][1] = acc[m][2] = acc[m][3] = 0.f; }
#pragma unroll
            for (int i = 0; i < 5; i++) {
                int k0 = (warp * 5 + i) * 16;
                uint32_t b0, b1;
                load_bfrag(vec, VEC_STRIDE, k0, g, t4, b0, b1);
                int krow = k0 + r8 + 8 * (mi >> 1);
#pragma unroll
                for (int m = 0; m < 2; m++) {
                    uint32_t a[4];
                    int ch = 2 * m + (mi & 1);
                    ldsm4t(a, strip + krow * 64 + ((ch ^ ((krow >> 1) & 3)) << 4));
                    mma16816(acc[m], a, b0, b1);
                }
            }
            if (t4 < 2) {
#pragma unroll
                for (int m = 0; m < 2; m++) {
                    sts_f32x2(sb + OFF_RED + ((warp * 32 + m * 16 + g) * 4 + 2 * t4) * 4, acc[m][0], acc[m][1]);
                    sts_f32x2(sb + OFF_RED + ((warp * 32 + m * 16 + g + 8) * 4 + 2 * t4) * 4, acc[m][2], acc[m][3]);
                }
            }
            bar_cons();
            if (tid < 64) {
                float v0 = 0.f, v1 = 0.f;
#pragma unroll
                for (int w = 0; w < 8; w++) {
                    v0 += lds_f32(sb + OFF_RED + (w * 128 + (tid & 15) * 8 + (tid >> 4)) * 4);
                    v1 += lds_f32(sb + OFF_RED + (w * 128 + (tid & 15) * 8 + 4 + (tid >> 4)) * 4);
                }
                stg_relaxed(step == 1 ? g_q + (((cta & ~3) + (tid >> 4)) * 4 + bown) * 32 + (tid & 15) : g_mod + mc * 64 + tid, ~pack_bf(v0, v1));
            }
        }
        if (step == 0) continue;
        if (step == 1) {
            if (warp == 0) {
                { const uint32_t c0 = clock32(); while (clock32() - c0 < Q_PAUSE) { } }
                uint4 v = poll1(g_q + (cta * 4 + ((lane >> 2) & 3)) * 32 + (lane & 3) * 4, lane < 16);
                if (lane < 16) {
                    sts128(sb + OFF_Q + lane * 16, v);
                    stg_zero4(g_q + (cta * 4 + (lane >> 2)) * 32 + (lane & 3) * 4);
                }
            }
            bar_cons();
            PROF(4);

#pragma unroll
            for (int c = 0; c < 8; c++) {
                qf[c][0] = lds32(sb + OFF_Q + (((c ^ g) * 4 + t4) << 2));
                qf[c][1] = lds32(sb + OFF_Q + 128 + (((c ^ g) * 4 + t4) << 2));
            }
        } else {
            bar_cons();
            if (tid == 0) mbar_arrive(bar_xfree);
        }
#pragma unroll 1
        for (int j = (step == 1 ? 0 : SEG_J) + (warp >> 2); j < (step == 1 ? SEG_J : NITEM / 2 - 2); j += 2) {
            const int s = (2 * j) & (NS - 1);
            const uint32_t par = (j >> 2) & 1;
            mbar_wait(bar_full + s * 8, par);
            if (tid == 0 && 2 * j >= PH_FIRST && (j & 3) == 0) {
                const int x = min(max((int)(gtime32() - t_start) - 2 * j * PACE_TAU, 0), 65535);
                asm volatile("red.relaxed.gpu.global.add.u32 [%0], %1;" ::"l"(g_phase + (j >> 2) * 32), "r"((1u << 24) + (x >> 2)) : "memory");
            }
            const uint32_t base = sb + OFF_RING + s * TILE_BYTES;
            float sa[4] = {0.f, 0.f, 0.f, 0.f}, sb2[4] = {0.f, 0.f, 0.f, 0.f};
#pragma unroll
            for (int c = 0; c < 8; c += 2) {
                uint32_t a[4], a2[4];
                ldsm4(a, (base + koff) ^ (c << 4));
                ldsm4(a2, (base + koff) ^ ((c + 1) << 4));
                mma16816(sa, a, qf[c][0], qf[c][1]);
                mma16816(sb2, a2, qf[c + 1][0], qf[c + 1][1]);
            }
            const uint32_t sw = pack_bf(odd ? sa[1] + sb2[1] : sa[0] + sb2[0], odd ? sa[3] + sb2[3] : sa[2] + sb2[2]);
            const uint32_t sv = pack_bf(bf_lo(sw) * 0.08838834764831845f, bf_hi(sw) * 0.08838834764831845f);
            const float s0 = bf_lo(sv) * 1.4426950408889634f, s1 = bf_hi(sv) * 1.4426950408889634f;
            float m_new = fmaxf(m_run, fmaxf(s0, s1));
            const bool grow = __any_sync(0xffffffffu, (diag && (m_new > m_run)));
            if (lane == 0) mbar_arrive(bar_empty + s * 8);
            if (grow) {
                float al = ex2(m_run - m_new);
                float a0 = __shfl_sync(0xffffffffu, al, src0), a1 = __shfl_sync(0xffffffffu, al, src1);
#pragma unroll
                for (int c = 0; c < 8; c++) { o[c][0] *= a0; o[c][1] *= a1; o[c][2] *= a0; o[c][3] *= a1; }
                l_run *= al;
                m_run = m_new;
            }
            uint32_t pw = pack_bf(ex2(s0 - m_run), ex2(s1 - m_run));
            l_run += bf_lo(pw) + bf_hi(pw);
            uint32_t b0 = odd ? (pw << 16) : (pw & 0xffffu);
            uint32_t b1 = odd ? (pw & 0xffff0000u) : (pw >> 16);
            if (!diag) { b0 = 0u; b1 = 0u; }
            mbar_wait(bar_full + (s + 1) * 8, par);
#pragma unroll
            for (int c = 0; c < 8; c++) {
                uint32_t a[4];
                ldsm4t(a, (base + voff) ^ (c << 4));
                mma16816(o[c], a, b0, b1);
            }
            __syncwarp();
            if (lane == 0) mbar_arrive(bar_empty + (s + 1) * 8);
        }
    }
    PROF(5);
    float acc[4][4];
    uint32_t pa[8][2];
    float rinv;
    {
        const int s = 4 + (warp >> 2);
        mbar_wait(bar_full + s * 8, 1);
        const uint32_t base = sb + OFF_RING + s * TILE_BYTES;
        float sa[4] = {0.f, 0.f, 0.f, 0.f}, sb2[4] = {0.f, 0.f, 0.f, 0.f};
#pragma unroll
        for (int c = 0; c < 8; c += 2) {
            uint32_t a[4], a2[4];
            ldsm4(a, (base + koff) ^ (c << 4));
            ldsm4(a2, (base + koff) ^ ((c + 1) << 4));
            mma16816(sa, a, qf[c][0], qf[c][1]);
            mma16816(sb2, a2, qf[c + 1][0], qf[c + 1][1]);
        }
        const uint32_t sw = pack_bf(odd ? sa[1] + sb2[1] : sa[0] + sb2[0], odd ? sa[3] + sb2[3] : sa[2] + sb2[2]);
        const uint32_t sv = pack_bf(bf_lo(sw) * 0.08838834764831845f, bf_hi(sw) * 0.08838834764831845f);
        const float s0 = bf_lo(sv) * 1.4426950408889634f, s1 = bf_hi(sv) * 1.4426950408889634f;
        int mi_ = __float_as_int(diag ? fmaxf(m_run, fmaxf(s0, s1)) : -INFINITY);
        mi_ ^= (mi_ >> 31) & 0x7fffffff;
        mi_ = __reduce_max_sync(0xffffffffu, mi_);
        mi_ ^= (mi_ >> 31) & 0x7fffffff;
        if (lane == 0) sts32(sb + OFF_ML + warp * 4, mi_);
        bar_cons();
        const float4 m0 = lds_f32x4(sb + OFF_ML), m1 = lds_f32x4(sb + OFF_ML + 16);
        const float mx = fmaxf(fmaxf(fmaxf(m0.x, m0.y), fmaxf(m0.z, m0.w)), fmaxf(fmaxf(m1.x, m1.y), fmaxf(m1.z, m1.w)));
        const float scl = ex2(m_run - mx);
        const uint32_t pw = pack_bf(ex2(s0 - mx), ex2(s1 - mx));
        if (diag) { sts16(sb + SC_P + (warp * 16 + g) * 2, pw); sts16(sb + SC_P + (warp * 16 + g + 8) * 2, pw >> 16); }
        const float lw = warp_sum(diag ? fmaf(l_run, scl, bf_lo(pw) + bf_hi(pw)) : 0.f);
        const float a0 = __shfl_sync(0xffffffffu, scl, src0), a1 = __shfl_sync(0xffffffffu, scl, src1);
        float v[8], u[8];
#pragma unroll
        for (int c = 0; c < 8; c++) {
            v[c] = a0 * o[c][0] + a1 * o[c ^ 1][1];
            u[c] = a0 * o[c][2] + a1 * o[c ^ 1][3];
        }
#pragma unroll
        for (int c = 0; c < 8; c++) {
            if (!(c & 2)) {
                v[c] += __shfl_xor_sync(0xffffffffu, v[c ^ 2], 1);
                u[c] += __shfl_xor_sync(0xffffffffu, u[c ^ 2], 1);
            }
        }
#pragma unroll
        for (int c = 0; c < 2; c++) {
            v[c] += __shfl_xor_sync(0xffffffffu, v[c ^ 4], 2);
            u[c] += __shfl_xor_sync(0xffffffffu, u[c ^ 4], 2);
        }
        const uint32_t dst = sb + SC_OP + (warp * 128 + 16 * t4 + g) * 4;
        sts_f32(dst, v[0]); sts_f32(dst + 32, v[1]); sts_f32(dst + 256, u[0]); sts_f32(dst + 288, u[1]);
        if (lane == 0) sts_f32(sb + OFF_ML + 32 + warp * 4, lw);
        mbar_wait(bar_help, 0);
        bar_cons();
        const float4 l0 = lds_f32x4(sb + OFF_ML + 32), l1 = lds_f32x4(sb + OFF_ML + 48);
        rinv = rcp_fast(((l0.x + l0.y) + (l0.z + l0.w)) + ((l1.x + l1.y) + (l1.z + l1.w)));
#pragma unroll
        for (int i = 0; i < 4; i++) acc[i][0] = acc[i][1] = acc[i][2] = acc[i][3] = 0.f;
#pragma unroll
        for (int w = 0; w < 8; w++) {
            const float2 x0 = lds_f32x2(sb + SC_OP + (w * 128 + 16 * warp + 2 * t4) * 4), x1 = lds_f32x2(sb + SC_OP + (w * 128 + 16 * warp + 8 + 2 * t4) * 4);
            acc[2 * (w & 1)][0] += x0.x; acc[2 * (w & 1)][1] += x0.y;
            acc[2 * (w & 1) + 1][0] += x1.x; acc[2 * (w & 1) + 1][1] += x1.y;
        }
#pragma unroll
        for (int ks = 0; ks < 8; ks++) { pa[ks][0] = lds32(sb + SC_P + (8 * ks + t4) * 4); pa[ks][1] = lds32(sb + SC_P + (8 * ks + 4 + t4) * 4); }
    }
    PROF(20);
    const int mt = warp < 2 ? warp : warp + 2;
    {
        const uint32_t va = pin(sb + OFF_RING + 6 * TILE_BYTES + (warp >> 2) * (TILE_BYTES / 2) + (8 * (mi & 1) + r8) * 128 + (((2 * (warp & 3) + (mi >> 1)) ^ r8) << 4));
        const uint32_t vbar = pin(bar_v + (warp >> 2) * 8);
        uint32_t* const o_dst = pin(slot(SL_O + (cta >> 4), g) + (cta & 15) * 64 + warp * 8 + 2 * t4);
#pragma unroll
        for (int tl = 0; tl < 2; tl++) {
            mbar_wait(vbar + tl * 16, 0);
            uint32_t r[4][4];
#pragma unroll
            for (int ks = 0; ks < 4; ks++) ldsm4t(r[ks], va + tl * TILE_BYTES + ks * 2048);
#pragma unroll
            for (int ks = 0; ks < 4; ks++) {
                const uint32_t a[4] = {pa[4 * tl + ks][0], 0u, pa[4 * tl + ks][1], 0u};
                mma16816(acc[2 * (ks & 1)], a, r[ks][0], r[ks][1]);
                mma16816(acc[2 * (ks & 1) + 1], a, r[ks][2], r[ks][3]);
            }
        }
        stg_relaxed2_if(g < 2, o_dst, ~pack_bf((acc[0][0] + acc[2][0]) * rinv, (acc[0][1] + acc[2][1]) * rinv),
                        ~pack_bf((acc[1][0] + acc[3][0]) * rinv, (acc[1][1] + acc[3][1]) * rinv));
    }
    PROF(7);
    const int side = lds32(sb + OFF_SIDE);
    const uint32_t red_st = pin(sb + SC_E4 + ((warp * 4 + 2 * ((lane >> 3) & 1) + (lane >> 4)) * 8 + (lane & 7)) * 4);
    const uint32_t red_ld = pin(sb + SC_E4 + (lane & 15) * 8);
    const uint32_t* const in1 = pin(slot(SL_P1 + own, side) + tid * 4);
    const uint32_t* const in2a = pin(slot(SL_P2 + 2 * own, side) + tid * 4);
    const uint32_t* const in2b = pin(slot(SL_P2 + 2 * own + 1, side) + tid * 4);
    uint32_t* const out_dst = pin((uint32_t*)(p.out + ((lane >> 2) & 3) * D + 8 * own) + t4);
    uint32_t* const x1_dst = pin(slot(SL_X1 + own / 30, lane >> 4) + (own % 30) * 32 + (lane & 15));
    uint32_t* const rst = pin(tid >= 32 && tid < 56 ? mod_slot(lane >> 2, own, lane & 3) : own < 32 && tid == 64 ? g_clr + own * 4 : own < 8 && tid == 96 ? g_phase + own * 32 : nullptr);
    const uint32_t xw = lds32(sb + OWN_X + (lane & 15) * 4), ga_w = lds32(sb + OWN_GA + (lane & 15) * 4);
    uint32_t cs[15];
    uint32_t* dst2[5];
    uint32_t w2a[5];
#pragma unroll
    for (int j = 0; j < 10; j++) cs[j] = lds32(sb + OFF_VB + ((g & 1) * 4 + (g >> 1)) * VEC_STRIDE + warp * 160 + t4 * 4 + j * 16);
#pragma unroll
    for (int i = 0; i < 5; i++) {
        cs[10 + i] = lds32(sb + OFF_VB + (g >> 1) * VEC_STRIDE + warp * 160 + (g & 1) * 16 + t4 * 4 + i * 32);
        const uint2 t = lds64(sb + OFF_TAB2 + warp * 40 + i * 8);
        dst2[i] = slot_ptr((t4 < 2 ? t.x : t.y) + g * 16 + (t4 & 1) * 8);
        const int cc = 2 * (warp * 5 + i) + (mi & 1);
        w2a[i] = pin(sb + X_W2 + (cc >> 3) * 4096 + (r8 + 8 * (mi >> 1)) * 128 + (((cc & 7) ^ r8) << 4));
    }
    const uint32_t piv = lds32(sb + OFF_STAT + (g >> 1) * 8);
    const uint32_t* const xin = pin(slot(SL_X1 + warp / 3, side) + ((warp % 3) * 10 + (g & 1)) * 32 + (g >> 1) * 4 + t4);
    const uint32_t w1a = pin(sb + X_W1 + (warp * 80 + r8 + 8 * (mi >> 1)) * 64 + (((mi & 1) ^ ((r8 >> 1) & 3)) << 4));
    const uint32_t w1bar = pin(bar_w1 + (warp >> 1) * 8), w2bar = pin(bar_w2 + (warp + (warp >> 2)) * 8);
    const uint32_t wbar = pin(NB_O + warp);
    const uint32_t ab_st = pin(sb + SC_AB + warp * 1024 + lane * 16), y_st = pin(sb + SC_Y + warp * 512 + lane * 8), s_st = pin(sb + SC_ST + (t4 * 8 + warp) * 8);
    const uint32_t h_ld = pin(sb + SC_H1 + ((g & 3) ^ (2 * (f & 1) + ((f >> 1) & 1))) * 64 + t4 * 16);
    {
        const int kap = 2 * (head & 1) + ((head >> 1) & 1);
        const uint32_t wa = pin(sb + X_WO + (mt >> 1) * (DH * 64) + (r8 + 8 * (mi >> 1)) * 64 + ((((mt & 1) * 2 + (mi & 1)) ^ ((r8 >> 1) & 3)) << 4));
        const uint32_t oa = pin(sb + OFF_O + ((g & 3) ^ kap) * O_STRIDE + t4 * 8);
        uint32_t* dst[4];
#pragma unroll
        for (int i = 0; i < 2; i++) {
            const uint2 t = lds64(sb + OFF_TAB1 + (bown * 20 + 2 * mt + (warp < 2 ? 4 * i : 0)) * 4);
            dst[2 * i] = slot_ptr(t.x + g * 16 + t4 * 8);
            dst[2 * i + 1] = slot_ptr(t.y + g * 16 + t4 * 8);
        }
        PROF(6);
        const uint32_t wobar = pin(bar_wo + (mt >> 1) * 8);
        asm volatile("bar.sync %0, 64;" ::"r"(wbar) : "memory");
        uint2 ob[8];
#pragma unroll
        for (int ks = 0; ks < 8; ks++) ob[ks] = lds64(oa + ks * 32);
#pragma unroll
        for (int m = 0; m < 2; m++) {
            if (m == 0 || warp < 2) {
                mbar_wait(wobar + m * 8, 0);
                PROF(8);
                uint32_t wf[8][4];
#pragma unroll
                for (int ks = 0; ks < 8; ks++) ldsm4t(wf[ks], wa + m * (DH * 64) + ks * 1024);
                float c[4][4];
#pragma unroll
                for (int ks = 0; ks < 8; ks++) {
                    if (ks < 4) c[ks][0] = c[ks][1] = c[ks][2] = c[ks][3] = 0.f;
                    mma16816(c[ks & 3], wf[ks], ob[ks].x, ob[ks].y);
                }
                stg_relaxed2_if(t4 < 2, dst[2 * m], flag((c[0][0] + c[1][0]) + (c[2][0] + c[3][0])), flag((c[0][1] + c[1][1]) + (c[2][1] + c[3][1])));
                stg_relaxed2_if(t4 < 2, dst[2 * m + 1], flag((c[0][2] + c[1][2]) + (c[2][2] + c[3][2])), flag((c[0][3] + c[1][3]) + (c[2][3] + c[3][3])));
            }
        }
    }
    PROF(9);
    uint32_t x1w = 0;
    if (is_owner) {
        uint4 v;
        for (int it = 0;; it++) {
            v = ldg_relaxed(in1);
            if (__all_sync(0xffffffffu, and3(and3(v.x, v.y, v.z), v.w, 1u))) break;
            if (it > SPIN_LIMIT) __trap();
        }
        PROF(11);
        const float s0 = __uint_as_float(v.x) + __shfl_xor_sync(0xffffffffu, __uint_as_float(v.z), 8);
        const float s1 = __uint_as_float(v.y) + __shfl_xor_sync(0xffffffffu, __uint_as_float(v.w), 8);
        sts_f32(red_st, s0 + __shfl_xor_sync(0xffffffffu, s1, 16));
        nbar_sync<NB_E4, 256>();
        if (warp == 0) {
            float2 a[8];
#pragma unroll
            for (int w = 0; w < 8; w++) a[w] = lds_f32x2(red_ld + w * 128);
            const uint32_t aw = pack_bf(((a[0].x + a[1].x) + (a[2].x + a[3].x)) + ((a[4].x + a[5].x) + (a[6].x + a[7].x)),
                                        ((a[0].y + a[1].y) + (a[2].y + a[3].y)) + ((a[4].y + a[5].y) + (a[6].y + a[7].y)));
            x1w = bf2_add(xw, bf2_mul(ga_w, aw));
            stg_relaxed(x1_dst, x1w ^ 0x80008000u);
            if (lane == 0) mbar_arrive(bar_x1);
        }
        if (rst) stg_zero4(rst);
    }
    PROF(12);
    if (is_f) {
        uint32_t f1[5][2][4], f2[5][2][4];
        uint32_t d[6];
        auto load_x1 = [&] {
#pragma unroll
            for (int i = 0; i < 5; i++) d[i] = ldg_relaxed32(xin + i * 64);
        };
        auto have_x1 = [&] { return __all_sync(0xffffffffu, __vimin3_u32(__vimin3_u32(d[0], d[1], d[2]), d[3], d[4]) != 0u); };
        mbar_wait(w1bar, 0);
        load_x1();
        {
#pragma unroll
            for (int i = 0; i < 5; i++) { ldsm4t(f1[i][0], w1a + i * 1024); ldsm4t(f1[i][1], (w1a ^ 32) + i * 1024); }
            float c[2][4];
#pragma unroll
            for (int m = 0; m < 2; m++) c[m][0] = c[m][1] = c[m][2] = c[m][3] = 0.f;
#pragma unroll
            for (int i = 0; i < 5; i++) { mma16816(c[0], f1[i][0], cs[2 * i], cs[2 * i + 1]); mma16816(c[1], f1[i][1], cs[2 * i], cs[2 * i + 1]); }
#pragma unroll
            for (int i = 0; i < 5; i++) { cs[2 * i] = pin(odd ? 0u : cs[10 + i]); cs[2 * i + 1] = pin(odd ? cs[10 + i] : 0u); }
#pragma unroll
            for (int m = 0; m < 2; m++) sts128(ab_st + m * 512, make_uint4(__float_as_uint(c[m][0]), __float_as_uint(c[m][1]), __float_as_uint(c[m][2]), __float_as_uint(c[m][3])));
            nbar_arrive<NB_AB, 320>();
            d[0] |= __float_as_uint(c[1][3]) & (side >> 1);
        }
        PROF(10);
#pragma unroll 1
        for (int it = 0; !have_x1(); it++) {
            load_x1();
            if (it > SPIN_LIMIT) __trap();
        }
        PROF(13);
        {
            float y[2][4], st[4] = {0.f, 0.f, 0.f, 0.f};
#pragma unroll
            for (int m = 0; m < 2; m++) y[m][0] = y[m][1] = y[m][2] = y[m][3] = 0.f;
#pragma unroll
            for (int i = 0; i < 5; i++) d[i] = bf2_add(d[i], piv);
            d[5] = 0u;
#pragma unroll
            for (int i = 0; i < 5; i++) {
                if (i < 3) {
                    const uint32_t a[4] = {d[2 * i], 0x3f803f80u, d[2 * i + 1], 0x3f803f80u};
                    mma16816(st, a, d[2 * i], d[2 * i + 1]);
                }
                const uint32_t y0 = bf2_mul(d[i], cs[2 * i]), y1 = bf2_mul(d[i], cs[2 * i + 1]);
                mma16816(y[0], f1[i][0], y0, y1);
                mma16816(y[1], f1[i][1], y0, y1);
            }
            const float q = odd ? st[1] : st[0];
            const float q2 = q + __shfl_xor_sync(0xffffffffu, q, 4);
            if (diag && !odd) sts_f32x2(s_st, q2, st[2] + st[3]);
#pragma unroll
            for (int m = 0; m < 2; m++) sts_f32x2(y_st + m * 256, y[m][0] + y[m][1], y[m][2] + y[m][3]);
        }
        nbar_arrive<NB_Y, 320>();
        PROF(14);
        mbar_wait(w2bar, 0);
        mbar_wait(w2bar + 8, 0);
#pragma unroll
        for (int i = 0; i < 5; i++) { ldsm4t(f2[i][0], w2a[i]); ldsm4t(f2[i][1], w2a[i] + 2048); }
        asm volatile("bar.sync %0, 96;" ::"r"(wbar) : "memory");
        PROF(15);
        {
            const uint4 hb = lds128(h_ld);
            float c[5][4];
#pragma unroll
            for (int i = 0; i < 5; i++) { c[i][0] = c[i][1] = c[i][2] = c[i][3] = 0.f; mma16816(c[i], f2[i][0], hb.x, hb.y); }
#pragma unroll
            for (int i = 0; i < 5; i++) {
                mma16816(c[i], f2[i][1], hb.z, hb.w);
                stg_relaxed2_if(true, dst2[i], flag(t4 < 2 ? c[i][0] : c[i][2]), flag(t4 < 2 ? c[i][1] : c[i][3]));
            }
        }
    }
    PROF(16);
    if (is_owner) {
        const uint32_t b2w = lds32(sb + OWN_B2 + (lane & 15) * 4), gb_ld = pin(sb + OWN_GB + (lane & 15) * 4);
        const bool two = tid < NF * 8 - 256;
        uint4 v, w = make_uint4(1, 1, 1, 1);
        for (int it = 0;; it++) {
            ldg_relaxed_if(two, w, in2b);
            v = ldg_relaxed(in2a);
            if (__all_sync(0xffffffffu, and3(and3(v.x, v.y, v.z), and3(v.w, w.x, w.y), and3(w.z, w.w, 1u)))) break;
            if (it > SPIN_LIMIT) __trap();
        }
        PROF(17);
        const float s0 = (__uint_as_float(v.x) + __uint_as_float(w.x)) + __shfl_xor_sync(0xffffffffu, __uint_as_float(v.z) + __uint_as_float(w.z), 8);
        const float s1 = (__uint_as_float(v.y) + __uint_as_float(w.y)) + __shfl_xor_sync(0xffffffffu, __uint_as_float(v.w) + __uint_as_float(w.w), 8);
        sts_f32(red_st + (SC_E6 - SC_E4), s0 + __shfl_xor_sync(0xffffffffu, s1, 16));
        if (warp != 0) {
            nbar_arrive<NB_E6, 288>();
        } else {
            nbar_sync<NB_E6, 288>();
            float2 a[8];
#pragma unroll
            for (int i = 0; i < 8; i++) a[i] = lds_f32x2(red_ld + (SC_E6 - SC_E4) + i * 128);
            const uint32_t gb_w = lds32(gb_ld);
            const uint32_t aw = pack_bf(((a[0].x + a[1].x) + (a[2].x + a[3].x)) + ((a[4].x + a[5].x) + (a[6].x + a[7].x)),
                                        ((a[0].y + a[1].y) + (a[2].y + a[3].y)) + ((a[4].y + a[5].y) + (a[6].y + a[7].y)));
            x1w = bf2_add(x1w, bf2_mul(gb_w, bf2_add(aw, b2w)));
            if (lane < 16) asm volatile("st.global.u32 [%0], %1;" ::"l"(out_dst), "r"(x1w) : "memory");
        }
    }
    PROF(18);
    PROF_DUMP;
}

typedef CUresult (*EncodeFn)(CUtensorMap*, CUtensorMapDataType, cuuint32_t, void*, const cuuint64_t*, const cuuint64_t*, const cuuint32_t*,
                             const cuuint32_t*, CUtensorMapInterleave, CUtensorMapSwizzle, CUtensorMapL2promotion, CUtensorMapFloatOOBfill);

static CUtensorMap make_map(EncodeFn enc, const void* ptr, int cols, int rows, int box_cols, int box_rows, CUtensorMapSwizzle sw,
                            CUtensorMapL2promotion promo = CU_TENSOR_MAP_L2_PROMOTION_NONE) {
    CUtensorMap m;
    cuuint64_t dims[2] = {(cuuint64_t)cols, (cuuint64_t)rows};
    cuuint64_t strides[1] = {(cuuint64_t)cols * 2};
    cuuint32_t box[2] = {(cuuint32_t)box_cols, (cuuint32_t)box_rows};
    cuuint32_t es[2] = {1, 1};
    enc(&m, CU_TENSOR_MAP_DATA_TYPE_BFLOAT16, 2, const_cast<void*>(ptr), dims, strides, box, es, CU_TENSOR_MAP_INTERLEAVE_NONE, sw,
        promo, CU_TENSOR_MAP_FLOAT_OOB_FILL_NONE);
    return m;
}

}

extern "C" void kernel_launch(void* const* d_in, const int* in_sizes, int n_in, void* d_out, int out_size) {
    (void)in_sizes; (void)n_in; (void)out_size;
    static EncodeFn enc = nullptr;
    if (!enc) {
        void* fn = nullptr;
        cudaDriverEntryPointQueryResult qr;
        cudaGetDriverEntryPoint("cuTensorMapEncodeTiled", &fn, cudaEnableDefault, &qr);
        enc = (EncodeFn)fn;
        cudaFuncSetAttribute(fused_kernel, cudaFuncAttributeMaxDynamicSharedMemorySize, SMEM_BYTES);
    }
    Params p;
    p.x = (const __nv_bfloat16*)d_in[0];
    p.kc = (const __nv_bfloat16*)d_in[1];
    p.vc = (const __nv_bfloat16*)d_in[2];
    p.b1 = (const __nv_bfloat16*)d_in[7];
    p.b2 = (const __nv_bfloat16*)d_in[9];
    p.c = (const __nv_bfloat16*)d_in[10];
    p.out = (__nv_bfloat16*)d_out;
    CUtensorMap tm_wmod = make_map(enc, d_in[11], NMOD, D, 32, 160, CU_TENSOR_MAP_SWIZZLE_64B, CU_TENSOR_MAP_L2_PROMOTION_L2_128B);
    CUtensorMap tm_wq = make_map(enc, d_in[3], NH * DH, D, 32, 160, CU_TENSOR_MAP_SWIZZLE_64B, CU_TENSOR_MAP_L2_PROMOTION_L2_128B);
    CUtensorMap tm_wo = make_map(enc, d_in[4], D, NH * DH, 32, 128, CU_TENSOR_MAP_SWIZZLE_64B);
    CUtensorMap tm_w1 = make_map(enc, d_in[6], FF, D, 32, 160, CU_TENSOR_MAP_SWIZZLE_64B);
    CUtensorMap tm_w2 = make_map(enc, d_in[8], D, FF, 64, 32, CU_TENSOR_MAP_SWIZZLE_128B);
    CUtensorMap tm_v = make_map(enc, d_in[2], DH, NB * NH * SK, 64, TILE_KEYS, CU_TENSOR_MAP_SWIZZLE_128B);
    CUtensorMap tm_gb = make_map(enc, d_in[11], NMOD, D, 8, 160, CU_TENSOR_MAP_SWIZZLE_NONE, CU_TENSOR_MAP_L2_PROMOTION_L2_128B);
    fused_kernel<<<NCTA, NTHREADS, SMEM_BYTES>>>(p, tm_wmod, tm_wq, tm_wo, tm_w1, tm_w2, tm_v, tm_gb);
}
```

```cpp
#include <cuda_runtime.h>
#include <cuda.h>
#include <cuda_bf16.h>
#include <stdint.h>
#include <stdlib.h>

namespace {

constexpr int NB = 4, D = 640, NH = 32, DH = 128, SK = 8192, WIN = 2048, FF = 1728, NMOD = 6 * D;
constexpr int NCTA = 128;
constexpr int NOWN = 80;
constexpr int NF = 54;
constexpr int NTHREADS = 320;
constexpr int TILE_KEYS = 64;
constexpr int TILE_BYTES = TILE_KEYS * DH * 2;
constexpr int NITEM = 2 * WIN / TILE_KEYS;
constexpr int NS = 8;
constexpr int NMODC = 120;
constexpr int SPIN_LIMIT = 1 << 18;
#define INFLIGHT 3
#define WQ_DELAY 500
#define MOD_T 4200
#define Q_PAUSE 1100
#define PACE_A 7500
#define PACE_TAU 635
#define ROT(c) 0
#define PF_END 16
#define PH_FIRST 24
#define PH_LAG 5
#define LAT_T 2300
#define WO_T -1050
#define WO_S 250
#define W1_T 900
#define W2_T 1600
#define GB_T 2350
#define GB_EV 600
#define CLR_CHECK 28000
constexpr int NPROBE = 8, PROBE_END = 10000;
constexpr int SEG_J = 8;

constexpr int OFF_RING = 0;
constexpr int OFF_X = OFF_RING + NS * TILE_BYTES;
constexpr int X_WM = OFF_X;
constexpr int X_WQ = OFF_X + D * 64;
constexpr int X_WO = OFF_X;
constexpr int X_W1 = X_WO + 5 * DH * 64;
constexpr int X_END = X_W1 + D * 64;
constexpr int X_W2 = OFF_RING;
constexpr int X_GB = OFF_RING + 3 * TILE_BYTES;
static_assert(X_WQ + D * 64 <= X_END, "prologue weights must fit");
constexpr int VEC_STRIDE = 1296;
constexpr int OFF_VA = X_END;
constexpr int OFF_VB = OFF_VA + 4 * VEC_STRIDE;
constexpr int OFF_RED = OFF_VB + 4 * VEC_STRIDE;
constexpr int OFF_ML = OFF_RED + 4 * VEC_STRIDE;
constexpr int O_STRIDE = 288;
constexpr int OFF_O = OFF_ML + 64;
constexpr int OFF_Q = OFF_O + 4 * O_STRIDE;
constexpr int OFF_OWN = OFF_Q + 256;
constexpr int OWN_X = OFF_OWN, OWN_B2 = OWN_X + 64, OWN_GA = OWN_B2 + 64, OWN_GB = OWN_GA + 64, OWN_B1 = OWN_GB + 64;
constexpr int OFF_STAT = OWN_B1 + 128;
constexpr int OFF_TAB1 = OFF_STAT + 32;
constexpr int OFF_TAB2 = OFF_TAB1 + NOWN * 4;
constexpr int OFF_SIDE = OFF_TAB2 + NOWN * 4;
constexpr int OFF_BAR = OFF_SIDE + 8;
constexpr int NBAR = 2 * NS + 32;
constexpr int SMEM_BYTES = OFF_BAR + NBAR * 8;
constexpr int SC_OP = OFF_RING + 4 * TILE_BYTES;
constexpr int SC_AB = SC_OP + 4096;
constexpr int SC_Y = SC_AB + 8192;
constexpr int SC_ST = SC_Y + 4096;
constexpr int SC_E4 = SC_ST + 256;
constexpr int SC_E6 = SC_E4 + 1024;
constexpr int SC_P = SC_E6 + 1024;
constexpr int SC_H1 = SC_P + 256;
static_assert(SMEM_BYTES <= 232448, "smem");
static_assert(OFF_BAR % 8 == 0 && OFF_X % 1024 == 0 && X_WQ % 512 == 0 && X_W1 % 512 == 0 && OFF_VA % 16 == 0 && OFF_RED % 16 == 0 && OFF_ML % 16 == 0 && OFF_O % 16 == 0 && OFF_Q % 16 == 0, "align");
constexpr int NB_O = 2  , NB_E4 = 10, NB_E6 = 11, NB_AB = 12, NB_Y = 13, NB_H1 = 14  ;

__device__ __align__(128) uint32_t g_mod[NMODC * 64];
__device__ __align__(128) uint32_t g_q[NCTA * 128];
__device__ uint32_t g_clr[NCTA];
__device__ __align__(128) uint32_t g_phase[8 * 32];
constexpr int SL_P1 = 0;
constexpr int SL_P2 = SL_P1 + NOWN;
constexpr int SL_O = SL_P2 + 2 * NOWN;
constexpr int SL_X1 = SL_O + 8;
constexpr int SL_SIDE = SL_X1 + 3;
static_assert(SL_SIDE < 256, "one 2 MB page");
__device__ uint32_t g_slots[2 * 256 * 2048];
__device__ __forceinline__ uint32_t* slot(int i, int side) {
    const size_t base = ((size_t)g_slots + 0x1fffff) & ~(size_t)0x1fffff;
    return (uint32_t*)base + i * 2048 + (((__popc(i & 0x59) ^ side) & 1) << 10);
}
#define PROF_DECL
#define HPROF(i) do { } while (0)
#define PROF(i) do { } while (0)
#define PROF_DUMP do { } while (0)

__device__ __forceinline__ uint32_t smem_u32(const void* p) { return (uint32_t)__cvta_generic_to_shared(p); }
__device__ __forceinline__ void mbar_init(uint32_t bar, uint32_t cnt) { asm volatile("mbarrier.init.shared::cta.b64 [%0], %1;" ::"r"(bar), "r"(cnt) : "memory"); }
__device__ __forceinline__ void mbar_expect_tx(uint32_t bar, uint32_t bytes) { asm volatile("mbarrier.arrive.expect_tx.shared::cta.b64 _, [%0], %1;" ::"r"(bar), "r"(bytes) : "memory"); }
__device__ __forceinline__ void mbar_arrive(uint32_t bar) { asm volatile("mbarrier.arrive.shared::cta.b64 _, [%0];" ::"r"(bar) : "memory"); }
__device__ __forceinline__ void mbar_wait(uint32_t bar, uint32_t parity) {
    uint32_t ok;
    int it = 0;
    while (true) {
        asm volatile("{\n.reg .pred p;\nmbarrier.try_wait.parity.shared::cta.b64 p, [%1], %2;\nselp.u32 %0, 1, 0, p;\n}" : "=r"(ok) : "r"(bar), "r"(parity) : "memory");
        if (ok) break;
        if (++it > SPIN_LIMIT) __trap();
    }
}
__device__ __forceinline__ void bulk_load(uint32_t dst, const void* src, uint32_t bytes, uint32_t bar, uint64_t pol) {
    asm volatile("cp.async.bulk.shared::cluster.global.mbarrier::complete_tx::bytes.L2::cache_hint [%0], [%1], %2, [%3], %4;"
                 ::"r"(dst), "l"(src), "r"(bytes), "r"(bar), "l"(pol) : "memory");
}
__device__ __forceinline__ void bar_cons() { asm volatile("bar.sync 1, 256;" ::: "memory"); }
template <int ID, int N> __device__ __forceinline__ void nbar_sync() { asm volatile("bar.sync %0, %1;" ::"n"(ID), "n"(N) : "memory"); }
template <int ID, int N> __device__ __forceinline__ void nbar_arrive() { asm volatile("bar.arrive %0, %1;" ::"n"(ID), "n"(N) : "memory"); }
__device__ __forceinline__ bool mbar_test(uint32_t bar, uint32_t parity) {
    uint32_t ok;
    asm volatile("{\n.reg .pred p;\nmbarrier.test_wait.parity.shared::cta.b64 p, [%1], %2;\nselp.u32 %0, 1, 0, p;\n}" : "=r"(ok) : "r"(bar), "r"(parity) : "memory");
    return ok;
}
__device__ __forceinline__ uint32_t pin(uint32_t v) { asm volatile("" : "+r"(v)); return v; }
template <class T> __device__ __forceinline__ T pin_hard(T v) { return __shfl_sync(0xffffffffu, v, threadIdx.x & 31); }
template <class T> __device__ __forceinline__ T* pin(T* v) { asm volatile("" : "+l"(v)); return v; }
__device__ __forceinline__ void ldsm4(uint32_t (&a)[4], uint32_t addr) {
    asm volatile("ldmatrix.sync.aligned.m8n8.x4.shared.b16 {%0,%1,%2,%3}, [%4];" : "=r"(a[0]), "=r"(a[1]), "=r"(a[2]), "=r"(a[3]) : "r"(addr) : "memory");
}
__device__ __forceinline__ void ldsm4t(uint32_t (&a)[4], uint32_t addr) {
    asm volatile("ldmatrix.sync.aligned.m8n8.x4.trans.shared.b16 {%0,%1,%2,%3}, [%4];" : "=r"(a[0]), "=r"(a[1]), "=r"(a[2]), "=r"(a[3]) : "r"(addr) : "memory");
}
__device__ __forceinline__ void mma16816(float (&c)[4], const uint32_t (&a)[4], uint32_t b0, uint32_t b1) {
    asm volatile("mma.sync.aligned.m16n8k16.row.col.f32.bf16.bf16.f32 {%0,%1,%2,%3}, {%4,%5,%6,%7}, {%8,%9}, {%0,%1,%2,%3};"
                 : "+f"(c[0]), "+f"(c[1]), "+f"(c[2]), "+f"(c[3]) : "r"(a[0]), "r"(a[1]), "r"(a[2]), "r"(a[3]), "r"(b0), "r"(b1));
}
__device__ __forceinline__ uint32_t lds32(uint32_t addr) { uint32_t v; asm volatile("ld.shared.u32 %0, [%1];" : "=r"(v) : "r"(addr) : "memory"); return v; }
__device__ __forceinline__ float lds_f32(uint32_t addr) { float v; asm volatile("ld.shared.f32 %0, [%1];" : "=f"(v) : "r"(addr) : "memory"); return v; }
__device__ __forceinline__ float2 lds_f32x2(uint32_t addr) { float2 v; asm volatile("ld.shared.v2.f32 {%0,%1}, [%2];" : "=f"(v.x), "=f"(v.y) : "r"(addr) : "memory"); return v; }
__device__ __forceinline__ float4 lds_f32x4(uint32_t addr) { float4 v; asm volatile("ld.shared.v4.f32 {%0,%1,%2,%3}, [%4];" : "=f"(v.x), "=f"(v.y), "=f"(v.z), "=f"(v.w) : "r"(addr) : "memory"); return v; }
__device__ __forceinline__ uint2 lds64(uint32_t addr) { uint2 v; asm volatile("ld.shared.v2.u32 {%0,%1}, [%2];" : "=r"(v.x), "=r"(v.y) : "r"(addr) : "memory"); return v; }
__device__ __forceinline__ uint4 lds128(uint32_t addr) { uint4 v; asm volatile("ld.shared.v4.u32 {%0,%1,%2,%3}, [%4];" : "=r"(v.x), "=r"(v.y), "=r"(v.z), "=r"(v.w) : "r"(addr) : "memory"); return v; }
__device__ __forceinline__ void sts16(uint32_t addr, uint32_t v) { asm volatile("st.shared.b16 [%0], %1;" ::"r"(addr), "h"((unsigned short)v) : "memory"); }
__device__ __forceinline__ void sts32(uint32_t addr, uint32_t v) { asm volatile("st.shared.u32 [%0], %1;" ::"r"(addr), "r"(v) : "memory"); }
__device__ __forceinline__ void sts_f32(uint32_t addr, float v) { asm volatile("st.shared.f32 [%0], %1;" ::"r"(addr), "f"(v) : "memory"); }
__device__ __forceinline__ void sts_f32x2(uint32_t addr, float a, float b) { asm volatile("st.shared.v2.f32 [%0], {%1,%2};" ::"r"(addr), "f"(a), "f"(b) : "memory"); }
__device__ __forceinline__ void sts128(uint32_t addr, uint4 v) { asm volatile("st.shared.v4.u32 [%0], {%1,%2,%3,%4};" ::"r"(addr), "r"(v.x), "r"(v.y), "r"(v.z), "r"(v.w) : "memory"); }
__device__ __forceinline__ uint4 ldg_relaxed(const uint32_t* p) {
    uint4 v;
    asm volatile("ld.relaxed.gpu.global.v4.u32 {%0,%1,%2,%3}, [%4];" : "=r"(v.x), "=r"(v.y), "=r"(v.z), "=r"(v.w) : "l"(p) : "memory");
    return v;
}
__device__ __forceinline__ void ldg_relaxed_if(bool on, uint4& v, const uint32_t* p) {
    asm volatile("{\n.reg .pred q;\nsetp.ne.u32 q, %5, 0;\n@q ld.relaxed.gpu.global.v4.u32 {%0,%1,%2,%3}, [%4];\n}"
                 : "+r"(v.x), "+r"(v.y), "+r"(v.z), "+r"(v.w) : "l"(p), "r"((uint32_t)on) : "memory");
}
__device__ __forceinline__ void stg_relaxed2_if(bool on, uint32_t* p, uint32_t a, uint32_t b) {
    asm volatile("{\n.reg .pred q;\nsetp.ne.u32 q, %3, 0;\n@q st.relaxed.gpu.global.v2.u32 [%0], {%1,%2};\n}" ::"l"(p), "r"(a), "r"(b), "r"((uint32_t)on) : "memory");
}
__device__ __forceinline__ uint32_t ldg_relaxed32(const uint32_t* p) { uint32_t v; asm volatile("ld.relaxed.gpu.global.u32 %0, [%1];" : "=r"(v) : "l"(p) : "memory"); return v; }
__device__ __forceinline__ void stg_relaxed(uint32_t* p, uint32_t v) { asm volatile("st.relaxed.gpu.global.u32 [%0], %1;" ::"l"(p), "r"(v) : "memory"); }
__device__ __forceinline__ void stg_zero4(uint32_t* p) { asm volatile("st.relaxed.gpu.global.v4.u32 [%0], {%1,%1,%1,%1};" ::"l"(p), "r"(0u) : "memory"); }
__device__ __forceinline__ bool ready(const uint4& v) { return (v.x != 0u) & (v.y != 0u) & (v.z != 0u) & (v.w != 0u); }
__device__ __forceinline__ uint32_t min4(const uint4& v) { return min(__vimin3_u32(v.x, v.y, v.z), v.w); }
__device__ __forceinline__ uint4 inv4(const uint4& v) { return make_uint4(~v.x, ~v.y, ~v.z, ~v.w); }
__device__ __forceinline__ uint32_t pack_bf(float lo, float hi) {
    uint32_t r;
    asm("cvt.rn.bf16x2.f32 %0, %1, %2;" : "=r"(r) : "f"(hi), "f"(lo));
    return r;
}
__device__ __forceinline__ float bfr(float x) { return __uint_as_float(pack_bf(0.f, x) & 0xffff0000u); }
__device__ __forceinline__ float bf_lo(uint32_t w) { return __uint_as_float(w << 16); }
__device__ __forceinline__ float bf_hi(uint32_t w) { return __uint_as_float(w & 0xffff0000u); }
__device__ __forceinline__ float bf2f(__nv_bfloat16 v) { return __bfloat162float(v); }
__device__ __forceinline__ float ex2(float x) { float y; asm("ex2.approx.ftz.f32 %0, %1;" : "=f"(y) : "f"(x)); return y; }
__device__ __forceinline__ float rcp_fast(float x) { float y; asm("rcp.approx.ftz.f32 %0, %1;" : "=f"(y) : "f"(x)); return y; }
__device__ __forceinline__ float rsqrt_fast(float x) { float y; asm("rsqrt.approx.ftz.f32 %0, %1;" : "=f"(y) : "f"(x)); return y; }
__device__ __forceinline__ float sqrt_fast(float x) { float y; asm("sqrt.approx.f32 %0, %1;" : "=f"(y) : "f"(x)); return y; }
__device__ __forceinline__ uint32_t bf2_add(uint32_t a, uint32_t b) { uint32_t r; asm("add.rn.bf16x2 %0, %1, %2;" : "=r"(r) : "r"(a), "r"(b)); return r; }
__device__ __forceinline__ uint32_t bf2_sub(uint32_t a, uint32_t b) { uint32_t r; asm("sub.rn.bf16x2 %0, %1, %2;" : "=r"(r) : "r"(a), "r"(b)); return r; }
__device__ __forceinline__ uint32_t bf2_mul(uint32_t a, uint32_t b) { uint32_t r; asm("mul.rn.bf16x2 %0, %1, %2;" : "=r"(r) : "r"(a), "r"(b)); return r; }
__device__ __forceinline__ uint32_t gtime32() { uint32_t c; asm volatile("mov.u32 %0, %%globaltimer_lo;" : "=r"(c)); return c; }
__device__ __forceinline__ uint32_t clock32() { uint32_t c; asm volatile("mov.u32 %0, %%clock;" : "=r"(c)); return c; }

__device__ __forceinline__ float warp_sum(float v) {
#pragma unroll
    for (int o = 16; o > 0; o >>= 1) v += __shfl_xor_sync(0xffffffffu, v, o);
    return v;
}

struct Params {
    const __nv_bfloat16 *x, *kc, *vc, *b1, *b2, *c;
    __nv_bfloat16* out;
};

__device__ __forceinline__ void tma2d(uint32_t dst, const CUtensorMap* tm, int x, int y, uint32_t bar) {
    asm volatile("cp.async.bulk.tensor.2d.shared::cluster.global.mbarrier::complete_tx::bytes [%0], [%1, {%2, %3}], [%4];"
                 ::"r"(dst), "l"(tm), "r"(x), "r"(y), "r"(bar) : "memory");
}

__device__ __forceinline__ void tma2d_hint(uint32_t dst, const CUtensorMap* tm, int x, int y, uint32_t bar, uint64_t pol) {
    asm volatile("cp.async.bulk.tensor.2d.shared::cluster.global.mbarrier::complete_tx::bytes.L2::cache_hint [%0], [%1, {%2, %3}], [%4], %5;"
                 ::"r"(dst), "l"(tm), "r"(x), "r"(y), "r"(bar), "l"(pol) : "memory");
}
__device__ __forceinline__ uint32_t flag(float v) { return __float_as_uint(v) | 1u; }
__device__ __forceinline__ uint32_t and3(uint32_t a, uint32_t b, uint32_t c) { uint32_t r; asm("lop3.b32 %0, %1, %2, %3, 0x80;" : "=r"(r) : "r"(a), "r"(b), "r"(c)); return r; }
__device__ __forceinline__ uint32_t* slot_ptr(uint32_t lo) {
    uint32_t* r;
    asm volatile("mov.b64 %0, {%1, %2};" : "=l"(r) : "r"(lo), "r"((uint32_t)((size_t)slot(0, 0) >> 32)));
    return r;
}

__device__ __forceinline__ void load_bfrag(uint32_t vec, int stride, int k0, int g, int t, uint32_t& b0, uint32_t& b1) {
    uint32_t a = vec + (g & 3) * stride + (k0 + 2 * t) * 2;
    b0 = lds32(a);
    b1 = lds32(a + 16);
}

__device__ __forceinline__ void ln_finish(float pivot, float sum, float sumsq, uint32_t& m2, float& rden) {
    float dm = sum * (1.f / D);
    float var = fmaxf(sumsq * (1.f / D) - dm * dm, 0.f);
    float mean = pivot + dm;
    m2 = pack_bf(mean, mean);
    rden = rcp_fast(bfr(sqrt_fast(bfr(bfr(var) + 1e-5f))));
}
__device__ __forceinline__ uint32_t ln_mod_pair(uint32_t xw, uint32_t cw, uint32_t sw, uint32_t m2, float rden) {
    uint32_t d = bf2_sub(xw, m2);
    uint32_t ln = pack_bf(bf_lo(d) * rden, bf_hi(d) * rden);
    return bf2_add(bf2_mul(ln, bf2_add(cw, 0x3f803f80u)), sw);
}
__device__ __forceinline__ uint4 ln_mod4(const uint4& x, const uint4& c, const uint4& s, uint32_t m2, float rden) {
    return make_uint4(ln_mod_pair(x.x, c.x, s.x, m2, rden), ln_mod_pair(x.y, c.y, s.y, m2, rden),
                      ln_mod_pair(x.z, c.z, s.z, m2, rden), ln_mod_pair(x.w, c.w, s.w, m2, rden));
}
__device__ __forceinline__ void acc_stats(const uint4& v, float pv, float& s, float& q) {
    const float a0 = bf_lo(v.x) - pv, a1 = bf_hi(v.x) - pv, a2 = bf_lo(v.y) - pv, a3 = bf_hi(v.y) - pv;
    const float a4 = bf_lo(v.z) - pv, a5 = bf_hi(v.z) - pv, a6 = bf_lo(v.w) - pv, a7 = bf_hi(v.w) - pv;
    s += ((a0 + a1) + (a2 + a3)) + ((a4 + a5) + (a6 + a7));
    q += (fmaf(a0, a0, a1 * a1) + fmaf(a2, a2, a3 * a3)) + (fmaf(a4, a4, a5 * a5) + fmaf(a6, a6, a7 * a7));
}
__device__ __forceinline__ uint32_t* mod_slot(int kind, int j, int b) { return g_mod + (kind * 20 + (j >> 2)) * 64 + b * 16 + (j & 3) * 4; }

template <int N>
__device__ __forceinline__ void poll_n(uint4 (&v)[N], const uint32_t* const* ptr, const bool* on) {
    bool pend[N];
#pragma unroll
    for (int i = 0; i < N; i++) pend[i] = on[i];
    int it = 0;
    while (true) {
#pragma unroll
        for (int i = 0; i < N; i++) if (pend[i]) v[i] = ldg_relaxed(ptr[i]);
        bool any = false;
#pragma unroll
        for (int i = 0; i < N; i++) { pend[i] = pend[i] && !ready(v[i]); any |= pend[i]; }
        if (!__any_sync(0xffffffffu, any)) break;
        if (++it > SPIN_LIMIT) __trap();
    }
#pragma unroll
    for (int i = 0; i < N; i++) v[i] = inv4(v[i]);
}
__device__ __forceinline__ uint4 poll1(const uint32_t* p, bool on) {
    uint4 v[1] = {make_uint4(0, 0, 0, 0)};
    const uint32_t* const ptr[1] = {p};
    const bool o[1] = {on};
    poll_n<1>(v, ptr, o);
    return v[0];
}

__device__ __forceinline__ void gelu_stage(uint32_t sb, int m, int lane) {
    const int g = lane >> 2, b = lane & 3;
    const uint32_t y_ld = pin_hard(sb + SC_Y + m * 256 + lane * 8), s_ld = pin_hard(sb + SC_ST + b * 64);
    const uint32_t h_st = pin_hard(sb + SC_H1 + b * 64 + (g >> 1) * 16 + m * 8 + (g & 1) * 2);
    float a0 = 0.f, b0 = lds_f32(sb + OWN_B1 + (16 * m + g) * 4), a1 = 0.f, b1 = lds_f32(sb + OWN_B1 + (16 * m + g + 8) * 4);
    const float piv = bf_hi(lds32(sb + OFF_STAT + b * 8));
    nbar_sync<NB_AB, 320>();
#pragma unroll
    for (int w = 0; w < 8; w++) {
        const float4 t = lds_f32x4(sb + SC_AB + w * 1024 + m * 512 + lane * 16);
        a0 += t.x; b0 += t.y; a1 += t.z; b1 += t.w;
    }
    sts128(sb + SC_AB + m * 512 + lane * 16, make_uint4(__float_as_uint(a0), __float_as_uint(b0), __float_as_uint(a1), __float_as_uint(b1)));
    nbar_sync<NB_Y, 320>();
    float4 q[4];
    float2 y[8];
#pragma unroll
    for (int i = 0; i < 4; i++) q[i] = lds_f32x4(s_ld + i * 16);
#pragma unroll
    for (int w = 0; w < 8; w++) y[w] = lds_f32x2(y_ld + w * 512);
    const float dm = (((q[0].y + q[0].w) + (q[1].y + q[1].w)) + ((q[2].y + q[2].w) + (q[3].y + q[3].w))) * (1.f / D);
    const float sq = ((q[0].x + q[0].z) + (q[1].x + q[1].z)) + ((q[2].x + q[2].z) + (q[3].x + q[3].z));
    const float r = rsqrt_fast(fmaxf(fmaf(-dm, dm, fmaf(sq, 1.f / D, 1e-5f)), 1e-5f));
    const float y0 = ((y[0].x + y[1].x) + (y[2].x + y[3].x)) + ((y[4].x + y[5].x) + (y[6].x + y[7].x));
    const float y1 = ((y[0].y + y[1].y) + (y[2].y + y[3].y)) + ((y[4].y + y[5].y) + (y[6].y + y[7].y));
    const float dmr = piv - bfr(piv - dm);
    const float u0 = fmaf(r, fmaf(dmr, a0, -y0), b0), u1 = fmaf(r, fmaf(dmr, a1, -y1), b1);
    const float e0 = ex2(u0 * fmaf(u0 * u0, -0.044715f * 2.302208198144325f, -2.302208198144325f));
    const float e1 = ex2(u1 * fmaf(u1 * u1, -0.044715f * 2.302208198144325f, -2.302208198144325f));
    sts16(h_st, pack_bf(u0 * rcp_fast(1.f + e0), 0.f));
    sts16(h_st + 4, pack_bf(u1 * rcp_fast(1.f + e1), 0.f));
#pragma unroll
    for (int w = 0; w < 4; w++) asm volatile("bar.arrive %0, 128;" ::"r"((NB_H1 + w) & 15) : "memory");
}

struct Roles { bool is_f, is_owner; int f, own; };
__device__ __forceinline__ Roles roles(int cta) {
    Roles r;
    r.f = (cta * 27) >> 6;
    r.is_f = (((cta + 1) * 27) >> 6) != r.f;
    r.is_owner = !r.is_f || r.f % 9 == 4;
    r.own = r.is_f ? 74 + r.f / 9 : cta - r.f;
    return r;
}

__global__ void __launch_bounds__(NTHREADS, 1)
fused_kernel(const Params p, const __grid_constant__ CUtensorMap tm_wmod, const __grid_constant__ CUtensorMap tm_wq,
             const __grid_constant__ CUtensorMap tm_wo, const __grid_constant__ CUtensorMap tm_w1, const __grid_constant__ CUtensorMap tm_w2,
             const __grid_constant__ CUtensorMap tm_v, const __grid_constant__ CUtensorMap tm_gb) {
    extern __shared__ __align__(1024) unsigned char smem[];
    const uint32_t t_start = gtime32();
    if (threadIdx.x == 0) {
        const uint32_t c_ = blockIdx.x;
        const uint32_t off = ((c_ & 3) << 26) + (c_ >> 2) * (1u << 21) + (ROT(c_) << 14) + (SK - WIN) * DH * 2;
        asm volatile("cp.async.bulk.prefetch.L2.global.L2::cache_hint [%0], %1, %2;" ::"l"((const char*)p.kc + off), "r"(TILE_BYTES), "l"(0x12f0000000000000ull  ) : "memory");
    }
    const uint32_t sb = smem_u32(smem);
    const int cta = blockIdx.x;
    const int head = cta >> 2, bown = cta & 3;
    const int rot = ROT(cta);
    const char* const kb = (const char*)(p.kc + ((size_t)(bown * NH + head) * SK + (SK - WIN)) * DH);
    uint64_t pol = 0;
    if (threadIdx.x == 256) {
        mbar_init(sb + OFF_BAR, 1);
        asm volatile("fence.mbarrier_init.release.cluster;" ::: "memory");
        asm volatile("createpolicy.fractional.L2::evict_first.b64 %0, 1.0;" : "=l"(pol));
        mbar_expect_tx(sb + OFF_BAR, TILE_BYTES);
        bulk_load(sb + OFF_RING, kb + (size_t)rot * TILE_BYTES, TILE_BYTES, sb + OFF_BAR, pol);
        if ((((head + 1) * 5) >> 4) != ((head * 5) >> 4)) {
            const uint32_t bar = sb + OFF_BAR + 2 * NS * 8;
            mbar_init(bar, 1);
            asm volatile("fence.mbarrier_init.release.cluster;" ::: "memory");
            mbar_expect_tx(bar, D * 64);
#pragma unroll 1
            for (int r = 0; r < D; r += 160) tma2d(sb + X_WM + r * 64, &tm_wmod, 32 * (((head * 5) >> 4) * 4 + bown), r, bar);
        }
    }
    const uint32_t bar_full = sb + OFF_BAR, bar_empty = bar_full + NS * 8;
    const uint32_t bar_wm = bar_empty + NS * 8, bar_wq = bar_wm + 8, bar_xfree = bar_wq + 8, bar_wo = bar_xfree + 8  ;
    const uint32_t bar_w1 = bar_wo + 40  , bar_w2 = bar_w1 + 32  , bar_help = bar_w2 + 80, bar_v = bar_help + 8  ;
    const uint32_t bar_gb = bar_v + 32  , bar_x1 = bar_gb + 32;
    const int tid = threadIdx.x, warp = tid >> 5, lane = tid & 31;
    const Roles role = roles(cta);
    const bool is_f = role.is_f, is_owner = role.is_owner;
    const int f = role.f, own = role.own;
    const bool crit = (((head + 1) * 5) >> 4) != ((head * 5) >> 4);
    const int mr = cta - ((head * 5) >> 4) * 4, mq = ((head * 5) >> 4) * 4 + bown;
    const int ml = mr * 31 / 44;
    const bool late = !crit && (mr + 1) * 31 / 44 != ml;
    const int mc = crit ? mq : ml < 60 ? 40 + ml : 58 + ml;
    const bool gb_own = is_owner && own < 72;

    PROF_DECL
    PROF(0);
    uint4 xa = make_uint4(0, 0, 0, 0), xb = xa, ca0 = xa, ca1 = xa, xs[3] = {xa, xa, xa};
    uint32_t own0 = 0;
    __nv_bfloat16 own2 = __float2bfloat16(0.f);
    if (warp < 8) {
        xa = *(const uint4*)(p.x + (tid & 3) * D + (tid >> 2) * 8);
        ca0 = ((const uint4*)p.c)[tid];
        if (tid < 64) { xb = *(const uint4*)(p.x + (tid & 3) * D + (64 + (tid >> 2)) * 8); ca1 = ((const uint4*)p.c)[256 + tid]; }
        if (warp < 4) {
#pragma unroll
            for (int i = 0; i < 3; i++) if (lane + 32 * i < 80) xs[i] = ((const uint4*)p.x)[warp * 80 + lane + 32 * i];
        } else if (warp == 4) {
            if (is_owner) own0 = *(const uint32_t*)((lane < 16 ? p.x + (lane >> 2) * D : p.b2) + 8 * own + 2 * (lane & 3));
            if (is_f) own2 = p.b1[32 * f + lane];
        }
    }
    const char* const vb = (const char*)(p.vc + ((size_t)(bown * NH + head) * SK + (SK - WIN)) * DH);
    const uint32_t bar_first = crit ? bar_wm : bar_wq;
    if (threadIdx.x == 256) {
        if (!crit) {
            mbar_init(bar_wq, 1);
            asm volatile("fence.mbarrier_init.release.cluster;" ::: "memory");
            mbar_expect_tx(bar_wq, D * 64);
            const uint32_t c0 = clock32();
            while (clock32() - c0 < WQ_DELAY) { }
#pragma unroll
            for (int r = 0; r < D; r += 160) tma2d(sb + X_WQ + r * 64, &tm_wq, 32 * cta, r, bar_wq);
        }
    } else if (threadIdx.x == 0) {
#pragma unroll
        for (int s = 0; s < NS; s++) { if (s) mbar_init(bar_full + s * 8, 1); mbar_init(bar_empty + s * 8, 4); }
        mbar_init(crit ? bar_wq : bar_wm, 1);
        mbar_init(bar_xfree, 1);
#pragma unroll
        for (int i = 0; i < 5; i++) { mbar_init(bar_wo + i * 8, 1); mbar_init(bar_w2 + i * 16, 1); mbar_init(bar_w2 + i * 16 + 8, 1); }
        mbar_init(bar_help, 1); mbar_init(bar_x1, 1);
#pragma unroll
        for (int i = 0; i < 4; i++) { mbar_init(bar_v + i * 8, 1); mbar_init(bar_w1 + i * 8, 1); mbar_init(bar_gb + i * 8, 1); }
        asm volatile("fence.mbarrier_init.release.cluster;" ::: "memory");
    }
    __syncthreads();

    if (warp == 8) {
        if (lane == 0) {
            int tp = NS;
            int sched = PACE_A - NS * PACE_TAU;
            int phase = 0;
#pragma unroll 1
            for (int t = 1; t <= NITEM; t++) {
                if (t == 1) mbar_wait(bar_full, 0);
                if (t == 2) {
                    mbar_wait(bar_first, 0);
                    if (crit) {
                        mbar_expect_tx(bar_wq, D * 64);
#pragma unroll 1
                        for (int r = 0; r < D; r += 160) tma2d(sb + X_WQ + r * 64, &tm_wq, 32 * cta, r, bar_wq);
                    }
                }
                if (t == 3) {
                    asm volatile("prefetch.tensormap [%0];" ::"l"(&tm_v) : "memory");
                    asm volatile("prefetch.tensormap [%0];" ::"l"(&tm_wo) : "memory");
                    asm volatile("prefetch.tensormap [%0];" ::"l"(&tm_w1) : "memory");
                    asm volatile("prefetch.tensormap [%0];" ::"l"(&tm_w2) : "memory");
                    asm volatile("prefetch.tensormap [%0];" ::"l"(&tm_gb) : "memory");
                }
                if (t == NS && late) {
                    mbar_wait(bar_full + (NS - INFLIGHT) * 8, 0);
                    mbar_expect_tx(bar_wm, D * 64);
#pragma unroll 1
                    for (int r = 0; r < D; r += 160) tma2d(sb + X_WM + r * 64, &tm_wmod, 32 * mc, r, bar_wm);
                }
                if (t >= NS && t < PF_END) {
                    int it = 0;
                    while (!mbar_test(bar_empty + (t & (NS - 1)) * 8, ((t >> 3) - 1) & 1)) {
                        if (tp < PF_END && (int)(gtime32() - t_start) >= PACE_A + (tp - NS) * PACE_TAU) {
                            asm volatile("cp.async.bulk.prefetch.L2.global.L2::cache_hint [%0], %1, %2;"
                                         ::"l"(((tp & 1) ? vb : kb) + (size_t)(((tp >> 1) + rot) & (NITEM / 2 - 1)) * TILE_BYTES), "r"(TILE_BYTES), "l"(pol) : "memory");
                            tp++;
                        }
                        if (++it > 16 * SPIN_LIMIT) __trap();
                    }
                    if (tp <= t) tp = t + 1;
                }
                if (t == NITEM) {
                    mbar_wait(bar_xfree, 0);
                    const uint32_t t_ref = t_start + phase + (NITEM - 1) * PACE_TAU;
#pragma unroll 1
                    for (int i = 0; i < 5; i++) {
                        while ((int)(gtime32() - t_ref) < WO_T + i * WO_S) { }
                        mbar_expect_tx(bar_wo + i * 8, DH * 64);
                        tma2d(sb + X_WO + i * (DH * 64), &tm_wo, bown * 160 + i * 32, head * DH, bar_wo + i * 8);
                    }
                    if (gb_own) {
                        mbar_wait(bar_empty + 3 * 8, ((NITEM >> 3) - 1) & 1);
                        mbar_wait(bar_x1, 0);
                        { const uint32_t c0 = clock32(); while (clock32() - c0 < GB_EV) { } }
                        while ((int)(gtime32() - t_ref) < GB_T) { }
#pragma unroll 1
                        for (int i = 0; i < 4; i++) {
                            mbar_expect_tx(bar_gb + i * 8, 160 * 16);
                            tma2d(sb + X_GB + i * (160 * 16), &tm_gb, 5 * D + 8 * own, 160 * i, bar_gb + i * 8);
                        }
                    }
                    if (is_f) {
#pragma unroll 1
                        for (int i = 0; i < 3; i++) mbar_wait(bar_empty + i * 8, ((NITEM >> 3) - 1) & 1);
                        while ((int)(gtime32() - t_ref) < W1_T) { }
#pragma unroll 1
                        for (int i = 0; i < 4; i++) {
                            mbar_expect_tx(bar_w1 + i * 8, 160 * 64);
                            tma2d(sb + X_W1 + i * (160 * 64), &tm_w1, 32 * f, 160 * i, bar_w1 + i * 8);
                        }
                        while ((int)(gtime32() - t_ref) < W2_T) { }
#pragma unroll 1
                        for (int i = 0; i < 10; i++) {
                            mbar_expect_tx(bar_w2 + i * 8, 4096);
                            tma2d(sb + X_W2 + i * 4096, &tm_w2, 64 * i, 32 * f, bar_w2 + i * 8);
                        }
                    }
                    break;
                }
                const int s = t & (NS - 1);
                if (t >= NS) {
                    mbar_wait(bar_empty + s * 8, ((t >> 3) - 1) & 1);
                    while ((int)(gtime32() - t_start) < sched + t * PACE_TAU) { }
                } else if (t >= INFLIGHT) {
                    mbar_wait(bar_full + (t - INFLIGHT) * 8, 0);
                }
                if (t < NITEM - 2) {
                    const int pair = t == NITEM - 3 ? NITEM / 2 - 1 : t >> 1;
                    mbar_expect_tx(bar_full + s * 8, TILE_BYTES);
                    bulk_load(sb + OFF_RING + s * TILE_BYTES, ((t & 1) && t != NITEM - 3 ? vb : kb) + (size_t)((pair + rot) & (NITEM / 2 - 1)) * TILE_BYTES, TILE_BYTES, bar_full + s * 8, pol);
                } else {
                    const int row = (bown * NH + head) * SK + (SK - WIN) + ((t - NITEM / 2 + rot) & (NITEM / 2 - 1)) * TILE_KEYS;
#pragma unroll 1
                    for (int i = 0; i < 2; i++) {
                        const uint32_t bar = bar_v + (2 * (t - (NITEM - 2)) + i) * 8;
                        mbar_expect_tx(bar, TILE_BYTES / 2);
                        tma2d_hint(sb + OFF_RING + s * TILE_BYTES + i * (TILE_BYTES / 2), &tm_v, 64 * i, row, bar, pol);
                    }
                }
                if (t >= PH_FIRST && (t & 7) == PH_LAG) {
                    const int now = (int)(gtime32() - t_start) - (t - PH_LAG) * PACE_TAU;
                    uint32_t ph;
                    asm volatile("atom.relaxed.gpu.global.add.u32 %0, [%1], 0;" : "=r"(ph) : "l"(g_phase + (t >> 3) * 32) : "memory");
                    phase = (int)min(((ph & 0xffffffu) * 4 + (NCTA - (ph >> 24)) * now) / NCTA, 65535u);
                    sched += (phase - LAT_T - sched) * 3 / 4;
                }
            }
        }
        __syncwarp();
    }

    if (warp == 9) {
        int side = 0;
        if (lane == 0) {
            uint32_t best[2] = {~0u, ~0u};
#pragma unroll
            for (int i = 0; i < 4; i++) stg_zero4(slot(SL_SIDE, i >> 1) + cta * 8 + (i & 1) * 4);
            uint32_t n = 0;
#pragma unroll 1
            for (int i = 0; (i & 1) || (n < NPROBE - 1 && (int)(gtime32() - t_start) < PROBE_END); i++) {
                uint32_t t0 = clock32(), t1;
                asm volatile("atom.relaxed.gpu.global.inc.u32 %0, [%1], %2;" : "=r"(n) : "l"(slot(SL_SIDE, i & 1) + cta * 8), "r"(0xffffu) : "memory");
                asm volatile("{\n.reg .pred p;\nsetp.ne.u32 p, %1, 0xffffffff;\nmov.u32 %0, 0;\n@p mov.u32 %0, %%clock;\n}" : "=r"(t1) : "r"(n) : "memory");
                if (i & 1) best[1] = min(best[1], t1 - t0); else best[0] = min(best[0], t1 - t0);
            }
            side = best[1] < best[0];
        }
        side = __shfl_sync(0xffffffffu, side, 0);
        HPROF(1);
        mbar_wait(bar_full + (NS - 1) * 8, 0);
        stg_zero4(slot(SL_O + (cta >> 4), lane >> 4) + (cta & 15) * 64 + (lane & 15) * 4);
        if (is_owner) {
#pragma unroll 1
            for (int i = lane; i < NH * 8; i += 32) stg_zero4(slot(SL_P1 + own, side) + i * 4);
#pragma unroll 1
            for (int i = lane; i < NF * 4; i += 32) stg_zero4(slot(SL_P2 + 2 * own + (i >> 7), side) + ((i >> 2) & 31) * 32 + (i & 3) * 4);
            if (lane < 8) stg_zero4(slot(SL_X1 + own / 30, lane >> 2) + (own % 30) * 32 + (lane & 3) * 4);
        }
        __threadfence();
        __syncwarp();
        if (lane == 0) stg_relaxed(g_clr + cta, 1u + side);
        HPROF(0);
        HPROF(2);
        while ((int)(gtime32() - t_start) < CLR_CHECK) __nanosleep(1000);
        mbar_wait(bar_xfree, 0);
        {
            uint4 v = make_uint4(1, 1, 1, 1), gv = v, mv[20];
#pragma unroll
            for (int i = 0; i < 20; i++) mv[i] = v;
#pragma unroll 1
            for (int it = 0;; it++) {
                v = ldg_relaxed(g_clr + lane * 4);

                ldg_relaxed_if(is_owner && lane < (gb_own ? 4 : 8), gv, mod_slot(lane < 4 ? 2 : 5, own, lane & 3));
#pragma unroll
                for (int i = 0; i < 20; i++) ldg_relaxed_if(is_f, mv[i], mod_slot(3, 8 * i + (lane >> 2), lane & 3));
                bool ok = ready(v) && ready(gv);
#pragma unroll
                for (int i = 0; i < 20; i++) ok = ok && ready(mv[i]);
                if (__all_sync(0xffffffffu, ok)) break;
                if (it > SPIN_LIMIT) __trap();
                __nanosleep(2000);
            }
            const uint32_t w[4] = {v.x, v.y, v.z, v.w};
#pragma unroll
            for (int i = 0; i < 4; i++) {
                const Roles r = roles(4 * lane + i);
                if (r.is_owner) {
                    sts32(sb + OFF_TAB1 + r.own * 4, (uint32_t)(size_t)(slot(SL_P1 + r.own, w[i] - 1) + head * 32));
                    sts32(sb + OFF_TAB2 + r.own * 4, (uint32_t)(size_t)(slot(SL_P2 + 2 * r.own + (f >> 5), w[i] - 1) + (f & 31) * 32));
                }
            }
            if (lane == 0) sts32(sb + OFF_SIDE, side);
            if (lane < 8) sts128(sb + OWN_GA + lane * 16, inv4(gv));
            const uint32_t dst = sb + OFF_VB + (lane & 3) * VEC_STRIDE + (lane >> 2) * 16;
#pragma unroll
            for (int i = 0; i < 10; i++) {
                const uint4 c = inv4(mv[10 + i]);
                sts128(dst + i * 128, make_uint4(bf2_add(c.x, 0x3f803f80u), bf2_add(c.y, 0x3f803f80u), bf2_add(c.z, 0x3f803f80u), bf2_add(c.w, 0x3f803f80u)));
                sts128(dst + (OFF_RED - OFF_VB) + i * 128, inv4(mv[i]));
            }
        }
        asm volatile("fence.acq_rel.gpu;" ::: "memory");
        __syncwarp();
        HPROF(3);
        if (lane == 0) mbar_arrive(bar_help);
        {
            const uint32_t* const src = pin(slot(SL_O + (cta >> 4), side) + (cta & 12) * 64 + lane * 4);
            const uint32_t dst = pin(sb + OFF_O + (lane >> 4) * O_STRIDE + (lane & 15) * 16);
            mbar_wait(bar_v + 16, 0);
            mbar_wait(bar_v + 24, 0);
            uint4 v[2];
            const uint32_t* const ptr[2] = {src, src + 128};
            const bool on[2] = {true, true};
            poll_n<2>(v, ptr, on);
            sts128(dst, v[0]);
            sts128(dst + 2 * O_STRIDE, v[1]);
#pragma unroll
            for (int w = 0; w < 8; w++) asm volatile("bar.arrive %0, 64;" ::"r"(NB_O + w) : "memory");
        }
        HPROF(4);
    }
    if (warp >= 8) {
        if (gb_own && warp == 9) {
            uint32_t a[20][4];
#pragma unroll
            for (int i = 0; i < 20; i++) ldsm4(a[i], sb + OFF_VA + (lane & 3) * VEC_STRIDE + (4 * i + (lane >> 3)) * 16);
            float c[4][4];
#pragma unroll
            for (int i = 0; i < 4; i++) c[i][0] = c[i][1] = c[i][2] = c[i][3] = 0.f;
#pragma unroll
            for (int bx = 0; bx < 4; bx++) {
                mbar_wait(bar_gb + bx * 8, 0);
#pragma unroll
                for (int i = 5 * bx; i < 5 * bx + 5; i++) {
                    uint32_t w[4];
                    ldsm4t(w, sb + X_GB + (32 * i + lane) * 16);
                    const uint32_t a0[4] = {a[i][0], 0u, a[i][1], 0u}, a1[4] = {a[i][2], 0u, a[i][3], 0u};
                    mma16816(c[(2 * i) & 3], a0, w[0], w[1]);
                    mma16816(c[(2 * i + 1) & 3], a1, w[2], w[3]);
                }
            }
            if (lane < 16) sts32(sb + OWN_GB + lane * 4, pack_bf((c[0][0] + c[1][0]) + (c[2][0] + c[3][0]), (c[0][1] + c[1][1]) + (c[2][1] + c[3][1])));
            HPROF(6);
        }
        if (is_owner && warp == 9) nbar_arrive<NB_E6, 288>();
        if (is_f) gelu_stage(sb, warp - 8, lane);
        return;
    }

    const int g = lane >> 2, t4 = lane & 3;
    const int mi = lane >> 3, r8 = lane & 7;

    {
        auto silu4 = [&](const uint4& cv) {
            uint32_t w4[4] = {cv.x, cv.y, cv.z, cv.w};
#pragma unroll
            for (int e = 0; e < 4; e++) {
                float c0 = bf_lo(w4[e]), c1 = bf_hi(w4[e]);
                w4[e] = pack_bf(c0 * rcp_fast(1.f + ex2(-1.4426950408889634f * c0)), c1 * rcp_fast(1.f + ex2(-1.4426950408889634f * c1)));
            }
            return make_uint4(w4[0], w4[1], w4[2], w4[3]);
        };
        {
            uint4 v = silu4(ca0);
            sts128(sb + OFF_VA + (tid / 80) * VEC_STRIDE + (tid % 80) * 16, v);
            if (tid < 64) { v = silu4(ca1); sts128(sb + OFF_VA + 3 * VEC_STRIDE + (16 + tid) * 16, v); }
        }
        if (warp < 4) {
            float s = 0.f, q = 0.f;
            const float pv = __shfl_sync(0xffffffffu, bf_lo(xs[0].x), 0);
#pragma unroll
            for (int i = 0; i < 3; i++) if (i < 2 || lane < 16) acc_stats(xs[i], pv, s, q);
#pragma unroll
            for (int of = 16; of > 0; of >>= 1) { s += __shfl_xor_sync(0xffffffffu, s, of); q += __shfl_xor_sync(0xffffffffu, q, of); }
            uint32_t m2; float rden;
            ln_finish(pv, s, q, m2, rden);
            if (lane == 0) { sts32(sb + OFF_STAT + warp * 8, m2); sts_f32(sb + OFF_STAT + warp * 8 + 4, rden); }
        } else if (warp == 4) {
            sts32(sb + OWN_X + lane * 4, bf2_add(own0, 0u));
            sts_f32(sb + OWN_B1 + lane * 4, bf2f(own2));
        }
    }
    bar_cons();
    PROF(24);
    uint32_t qf[8][2];
    float o[8][4];
#pragma unroll
    for (int c = 0; c < 8; c++) { o[c][0] = o[c][1] = o[c][2] = o[c][3] = 0.f; }
    float m_run = -INFINITY, l_run = 0.f;
    const bool diag = (t4 == (g >> 1));
    const bool odd = g & 1;
    const uint32_t koff = (warp & 3) * 4096 + (r8 + 8 * (mi & 1)) * 256 + (mi >> 1) * 128 + (r8 << 4);
    const uint32_t voff = TILE_BYTES + (warp & 3) * 4096 + (r8 + 8 * (mi >> 1)) * 256 + (mi & 1) * 128 + (r8 << 4);
    const int src0 = (2 * t4) * 4 + t4, src1 = (2 * t4 + 1) * 4 + t4;
#pragma unroll 1
    for (int step = crit ? 0 : 1; step < 3; step++) {
        if (step < 2 || late) {
            if (step == 1) {
                if (!crit) mbar_wait(bar_wq, 0);
                const uint32_t m2 = lds32(sb + OFF_STAT + (tid & 3) * 8);
                const float rden = lds_f32(sb + OFF_STAT + (tid & 3) * 8 + 4);
                uint4 v[4];
                v[2] = v[3] = make_uint4(1, 1, 1, 1);
                const uint32_t* const p0 = mod_slot(0, tid >> 2, tid & 3);
                while ((int)(gtime32() - t_start) < MOD_T) { }
                PROF(2);
#pragma unroll 1
                for (int it = 0;; it++) {
                    ldg_relaxed_if(tid < 64, v[2], p0 + 16 * 64);
                    ldg_relaxed_if(tid < 64, v[3], p0 + 36 * 64);
                    v[0] = ldg_relaxed(p0);
                    v[1] = ldg_relaxed(p0 + 20 * 64);
                    if (__all_sync(0xffffffffu, min(min(min4(v[0]), min4(v[1])), min(min4(v[2]), min4(v[3]))) != 0u)) break;
                    if (it > SPIN_LIMIT) __trap();
                }
#pragma unroll
                for (int i = 0; i < 4; i++) v[i] = inv4(v[i]);
                PROF(3);
                uint4 h0 = ln_mod4(xa, v[1], v[0], m2, rden);
                sts128(sb + OFF_VB + (tid & 3) * VEC_STRIDE + (tid >> 2) * 16, h0);
                if (tid < 64) {
                    h0 = ln_mod4(xb, v[3], v[2], m2, rden);
                    sts128(sb + OFF_VB + (tid & 3) * VEC_STRIDE + (64 + (tid >> 2)) * 16, h0);
                }
            }
            mbar_wait(step == 1 ? bar_wq : bar_wm, 0);
            bar_cons();
            const uint32_t strip = sb + (step == 1 ? X_WQ : X_WM), vec = sb + (step == 1 ? OFF_VB : OFF_VA);
            float acc[2][4];
#pragma unroll
            for (int m = 0; m < 2; m++) { acc[m][0] = acc[m][1] = acc[m][2] = acc[m][3] = 0.f; }
#pragma unroll
            for (int i = 0; i < 5; i++) {
                int k0 = (warp * 5 + i) * 16;
                uint32_t b0, b1;
                load_bfrag(vec, VEC_STRIDE, k0, g, t4, b0, b1);
                int krow = k0 + r8 + 8 * (mi >> 1);
#pragma unroll
                for (int m = 0; m < 2; m++) {
                    uint32_t a[4];
                    int ch = 2 * m + (mi & 1);
                    ldsm4t(a, strip + krow * 64 + ((ch ^ ((krow >> 1) & 3)) << 4));
                    mma16816(acc[m], a, b0, b1);
                }
            }
            if (t4 < 2) {
#pragma unroll
                for (int m = 0; m < 2; m++) {
                    sts_f32x2(sb + OFF_RED + ((warp * 32 + m * 16 + g) * 4 + 2 * t4) * 4, acc[m][0], acc[m][1]);
                    sts_f32x2(sb + OFF_RED + ((warp * 32 + m * 16 + g + 8) * 4 + 2 * t4) * 4, acc[m][2], acc[m][3]);
                }
            }
            bar_cons();
            if (tid < 64) {
                float v0 = 0.f, v1 = 0.f;
#pragma unroll
                for (int w = 0; w < 8; w++) {
                    v0 += lds_f32(sb + OFF_RED + (w * 128 + (tid & 15) * 8 + (tid >> 4)) * 4);
                    v1 += lds_f32(sb + OFF_RED + (w * 128 + (tid & 15) * 8 + 4 + (tid >> 4)) * 4);
                }
                stg_relaxed(step == 1 ? g_q + (((cta & ~3) + (tid >> 4)) * 4 + bown) * 32 + (tid & 15) : g_mod + mc * 64 + tid, ~pack_bf(v0, v1));
            }
        }
        if (step == 0) continue;
        if (step == 1) {
            if (warp == 0) {
                { const uint32_t c0 = clock32(); while (clock32() - c0 < Q_PAUSE) { } }
                uint4 v = poll1(g_q + (cta * 4 + ((lane >> 2) & 3)) * 32 + (lane & 3) * 4, lane < 16);
                if (lane < 16) {
                    sts128(sb + OFF_Q + lane * 16, v);
                    stg_zero4(g_q + (cta * 4 + (lane >> 2)) * 32 + (lane & 3) * 4);
                }
            }
            bar_cons();
            PROF(4);

#pragma unroll
            for (int c = 0; c < 8; c++) {
                qf[c][0] = lds32(sb + OFF_Q + (((c ^ g) * 4 + t4) << 2));
                qf[c][1] = lds32(sb + OFF_Q + 128 + (((c ^ g) * 4 + t4) << 2));
            }
        } else {
            bar_cons();
            if (tid == 0) mbar_arrive(bar_xfree);
        }
#pragma unroll 1
        for (int j = (step == 1 ? 0 : SEG_J) + (warp >> 2); j < (step == 1 ? SEG_J : NITEM / 2 - 2); j += 2) {
            const int s = (2 * j) & (NS - 1);
            const uint32_t par = (j >> 2) & 1;
            mbar_wait(bar_full + s * 8, par);
            if (tid == 0 && 2 * j >= PH_FIRST && (j & 3) == 0) {
                const int x = min(max((int)(gtime32() - t_start) - 2 * j * PACE_TAU, 0), 65535);
                asm volatile("red.relaxed.gpu.global.add.u32 [%0], %1;" ::"l"(g_phase + (j >> 2) * 32), "r"((1u << 24) + (x >> 2)) : "memory");
            }
            const uint32_t base = sb + OFF_RING + s * TILE_BYTES;
            float sa[4] = {0.f, 0.f, 0.f, 0.f}, sb2[4] = {0.f, 0.f, 0.f, 0.f};
#pragma unroll
            for (int c = 0; c < 8; c += 2) {
                uint32_t a[4], a2[4];
                ldsm4(a, (base + koff) ^ (c << 4));
                ldsm4(a2, (base + koff) ^ ((c + 1) << 4));
                mma16816(sa, a, qf[c][0], qf[c][1]);
                mma16816(sb2, a2, qf[c + 1][0], qf[c + 1][1]);
            }
            const uint32_t sw = pack_bf(odd ? sa[1] + sb2[1] : sa[0] + sb2[0], odd ? sa[3] + sb2[3] : sa[2] + sb2[2]);
            const uint32_t sv = pack_bf(bf_lo(sw) * 0.08838834764831845f, bf_hi(sw) * 0.08838834764831845f);
            const float s0 = bf_lo(sv) * 1.4426950408889634f, s1 = bf_hi(sv) * 1.4426950408889634f;
            float m_new = fmaxf(m_run, fmaxf(s0, s1));
            const bool grow = __any_sync(0xffffffffu, (diag && (m_new > m_run)));
            if (lane == 0) mbar_arrive(bar_empty + s * 8);
            if (grow) {
                float al = ex2(m_run - m_new);
                float a0 = __shfl_sync(0xffffffffu, al, src0), a1 = __shfl_sync(0xffffffffu, al, src1);
#pragma unroll
                for (int c = 0; c < 8; c++) { o[c][0] *= a0; o[c][1] *= a1; o[c][2] *= a0; o[c][3] *= a1; }
                l_run *= al;
                m_run = m_new;
            }
            uint32_t pw = pack_bf(ex2(s0 - m_run), ex2(s1 - m_run));
            l_run += bf_lo(pw) + bf_hi(pw);
            uint32_t b0 = odd ? (pw << 16) : (pw & 0xffffu);
            uint32_t b1 = odd ? (pw & 0xffff0000u) : (pw >> 16);
            if (!diag) { b0 = 0u; b1 = 0u; }
            mbar_wait(bar_full + (s + 1) * 8, par);
#pragma unroll
            for (int c = 0; c < 8; c++) {
                uint32_t a[4];
                ldsm4t(a, (base + voff) ^ (c << 4));
                mma16816(o[c], a, b0, b1);
            }
            __syncwarp();
            if (lane == 0) mbar_arrive(bar_empty + (s + 1) * 8);
        }
    }
    PROF(5);
    float acc[4][4];
    uint32_t pa[8][2];
    float rinv;
    {
        const int s = 4 + (warp >> 2);
        mbar_wait(bar_full + s * 8, 1);
        const uint32_t base = sb + OFF_RING + s * TILE_BYTES;
        float sa[4] = {0.f, 0.f, 0.f, 0.f}, sb2[4] = {0.f, 0.f, 0.f, 0.f};
#pragma unroll
        for (int c = 0; c < 8; c += 2) {
            uint32_t a[4], a2[4];
            ldsm4(a, (base + koff) ^ (c << 4));
            ldsm4(a2, (base + koff) ^ ((c + 1) << 4));
            mma16816(sa, a, qf[c][0], qf[c][1]);
            mma16816(sb2, a2, qf[c + 1][0], qf[c + 1][1]);
        }
        const uint32_t sw = pack_bf(odd ? sa[1] + sb2[1] : sa[0] + sb2[0], odd ? sa[3] + sb2[3] : sa[2] + sb2[2]);
        const uint32_t sv = pack_bf(bf_lo(sw) * 0.08838834764831845f, bf_hi(sw) * 0.08838834764831845f);
        const float s0 = bf_lo(sv) * 1.4426950408889634f, s1 = bf_hi(sv) * 1.4426950408889634f;
        int mi_ = __float_as_int(diag ? fmaxf(m_run, fmaxf(s0, s1)) : -INFINITY);
        mi_ ^= (mi_ >> 31) & 0x7fffffff;
        mi_ = __reduce_max_sync(0xffffffffu, mi_);
        mi_ ^= (mi_ >> 31) & 0x7fffffff;
        if (lane == 0) sts32(sb + OFF_ML + warp * 4, mi_);
        bar_cons();
        const float4 m0 = lds_f32x4(sb + OFF_ML), m1 = lds_f32x4(sb + OFF_ML + 16);
        const float mx = fmaxf(fmaxf(fmaxf(m0.x, m0.y), fmaxf(m0.z, m0.w)), fmaxf(fmaxf(m1.x, m1.y), fmaxf(m1.z, m1.w)));
        const float scl = ex2(m_run - mx);
        const uint32_t pw = pack_bf(ex2(s0 - mx), ex2(s1 - mx));
        if (diag) { sts16(sb + SC_P + (warp * 16 + g) * 2, pw); sts16(sb + SC_P + (warp * 16 + g + 8) * 2, pw >> 16); }
        const float lw = warp_sum(diag ? fmaf(l_run, scl, bf_lo(pw) + bf_hi(pw)) : 0.f);
        const float a0 = __shfl_sync(0xffffffffu, scl, src0), a1 = __shfl_sync(0xffffffffu, scl, src1);
        float v[8], u[8];
#pragma unroll
        for (int c = 0; c < 8; c++) {
            v[c] = a0 * o[c][0] + a1 * o[c ^ 1][1];
            u[c] = a0 * o[c][2] + a1 * o[c ^ 1][3];
        }
#pragma unroll
        for (int c = 0; c < 8; c++) {
            if (!(c & 2)) {
                v[c] += __shfl_xor_sync(0xffffffffu, v[c ^ 2], 1);
                u[c] += __shfl_xor_sync(0xffffffffu, u[c ^ 2], 1);
            }
        }
#pragma unroll
        for (int c = 0; c < 2; c++) {
            v[c] += __shfl_xor_sync(0xffffffffu, v[c ^ 4], 2);
            u[c] += __shfl_xor_sync(0xffffffffu, u[c ^ 4], 2);
        }
        const uint32_t dst = sb + SC_OP + (warp * 128 + 16 * t4 + g) * 4;
        sts_f32(dst, v[0]); sts_f32(dst + 32, v[1]); sts_f32(dst + 256, u[0]); sts_f32(dst + 288, u[1]);
        if (lane == 0) sts_f32(sb + OFF_ML + 32 + warp * 4, lw);
        mbar_wait(bar_help, 0);
        bar_cons();
        const float4 l0 = lds_f32x4(sb + OFF_ML + 32), l1 = lds_f32x4(sb + OFF_ML + 48);
        rinv = rcp_fast(((l0.x + l0.y) + (l0.z + l0.w)) + ((l1.x + l1.y) + (l1.z + l1.w)));
#pragma unroll
        for (int i = 0; i < 4; i++) acc[i][0] = acc[i][1] = acc[i][2] = acc[i][3] = 0.f;
#pragma unroll
        for (int w = 0; w < 8; w++) {
            const float2 x0 = lds_f32x2(sb + SC_OP + (w * 128 + 16 * warp + 2 * t4) * 4), x1 = lds_f32x2(sb + SC_OP + (w * 128 + 16 * warp + 8 + 2 * t4) * 4);
            acc[2 * (w & 1)][0] += x0.x; acc[2 * (w & 1)][1] += x0.y;
            acc[2 * (w & 1) + 1][0] += x1.x; acc[2 * (w & 1) + 1][1] += x1.y;
        }
#pragma unroll
        for (int ks = 0; ks < 8; ks++) { pa[ks][0] = lds32(sb + SC_P + (8 * ks + t4) * 4); pa[ks][1] = lds32(sb + SC_P + (8 * ks + 4 + t4) * 4); }
    }
    PROF(20);
    const int mt = warp < 2 ? warp : warp + 2;
    {
        const uint32_t va = pin(sb + OFF_RING + 6 * TILE_BYTES + (warp >> 2) * (TILE_BYTES / 2) + (8 * (mi & 1) + r8) * 128 + (((2 * (warp & 3) + (mi >> 1)) ^ r8) << 4));
        const uint32_t vbar = pin(bar_v + (warp >> 2) * 8);
        uint32_t* const o_dst = pin(slot(SL_O + (cta >> 4), g) + (cta & 15) * 64 + warp * 8 + 2 * t4);
#pragma unroll
        for (int tl = 0; tl < 2; tl++) {
            mbar_wait(vbar + tl * 16, 0);
            uint32_t r[4][4];
#pragma unroll
            for (int ks = 0; ks < 4; ks++) ldsm4t(r[ks], va + tl * TILE_BYTES + ks * 2048);
#pragma unroll
            for (int ks = 0; ks < 4; ks++) {
                const uint32_t a[4] = {pa[4 * tl + ks][0], 0u, pa[4 * tl + ks][1], 0u};
                mma16816(acc[2 * (ks & 1)], a, r[ks][0], r[ks][1]);
                mma16816(acc[2 * (ks & 1) + 1], a, r[ks][2], r[ks][3]);
            }
        }
        stg_relaxed2_if(g < 2, o_dst, ~pack_bf((acc[0][0] + acc[2][0]) * rinv, (acc[0][1] + acc[2][1]) * rinv),
                        ~pack_bf((acc[1][0] + acc[3][0]) * rinv, (acc[1][1] + acc[3][1]) * rinv));
    }
    PROF(7);
    const int side = lds32(sb + OFF_SIDE);
    const uint32_t red_st = pin(sb + SC_E4 + ((warp * 4 + 2 * ((lane >> 3) & 1) + (lane >> 4)) * 8 + (lane & 7)) * 4);
    const uint32_t red_ld = pin(sb + SC_E4 + (lane & 15) * 8);
    const uint32_t* const in1 = pin(slot(SL_P1 + own, side) + tid * 4);
    const uint32_t* const in2a = pin(slot(SL_P2 + 2 * own, side) + (tid >> 3) * 32 + (tid & 7) * 2);
    const uint32_t* const in2b = pin(slot(SL_P2 + 2 * own + 1, side) + (tid >> 3) * 32 + (tid & 7) * 2);
    uint32_t* const out_dst = pin((uint32_t*)(p.out + ((lane >> 2) & 3) * D + 8 * own) + t4);
    uint32_t* const x1_dst = pin(slot(SL_X1 + own / 30, lane >> 4) + (own % 30) * 32 + (lane & 15));
    uint32_t* const rst = pin(tid >= 32 && tid < 56 ? mod_slot(lane >> 2, own, lane & 3) : own < 32 && tid == 64 ? g_clr + own * 4 : own < 8 && tid == 96 ? g_phase + own * 32 : nullptr);
    const uint32_t xw = lds32(sb + OWN_X + (lane & 15) * 4), ga_w = lds32(sb + OWN_GA + (lane & 15) * 4);
    uint32_t cs[15];
    uint32_t* dst2[5];
    uint32_t w2a[5];
#pragma unroll
    for (int j = 0; j < 10; j++) cs[j] = lds32(sb + OFF_VB + ((g & 1) * 4 + (g >> 1)) * VEC_STRIDE + warp * 160 + t4 * 4 + j * 16);
#pragma unroll
    for (int i = 0; i < 5; i++) {
        cs[10 + i] = lds32(sb + OFF_VB + (g >> 1) * VEC_STRIDE + warp * 160 + (g & 1) * 16 + t4 * 4 + i * 32);
        const uint2 t = lds64(sb + OFF_TAB2 + warp * 40 + i * 8);
        dst2[i] = slot_ptr((t4 < 2 ? t.x : t.y) + g * 8 + (t4 & 1) * 4);
        const int cc = 2 * (warp * 5 + i) + (mi & 1);
        w2a[i] = pin(sb + X_W2 + (cc >> 3) * 4096 + (r8 + 8 * (mi >> 1)) * 128 + (((cc & 7) ^ r8) << 4));
    }
    const uint32_t piv = lds32(sb + OFF_STAT + (g >> 1) * 8);
    const uint32_t* const xin = pin(slot(SL_X1 + warp / 3, side) + ((warp % 3) * 10 + (g & 1)) * 32 + (g >> 1) * 4 + t4);
    const uint32_t w1a = pin(sb + X_W1 + (warp * 80 + r8 + 8 * (mi >> 1)) * 64 + (((mi & 1) ^ ((r8 >> 1) & 3)) << 4));
    const uint32_t w1bar = pin(bar_w1 + (warp >> 1) * 8), w2bar = pin(bar_w2 + (warp + (warp >> 2)) * 8);
    const uint32_t obar = pin(NB_O + warp), hbar = pin((NB_H1 + (warp >> 1)) & 15);
    const uint32_t ab_st = pin(sb + SC_AB + warp * 1024 + lane * 16), y_st = pin(sb + SC_Y + warp * 512 + lane * 8), s_st = pin(sb + SC_ST + (t4 * 8 + warp) * 8);
    const uint32_t h_ld = pin(sb + SC_H1 + ((g & 3) ^ (2 * (f & 1) + ((f >> 1) & 1))) * 64 + t4 * 16);
    {
        const int kap = 2 * (head & 1) + ((head >> 1) & 1);
        const uint32_t wa = pin(sb + X_WO + (mt >> 1) * (DH * 64) + (r8 + 8 * (mi >> 1)) * 64 + ((((mt & 1) * 2 + (mi & 1)) ^ ((r8 >> 1) & 3)) << 4));
        const uint32_t oa = pin(sb + OFF_O + ((g & 3) ^ kap) * O_STRIDE + t4 * 8);
        uint32_t* dst[4];
#pragma unroll
        for (int i = 0; i < 2; i++) {
            const uint2 t = lds64(sb + OFF_TAB1 + (bown * 20 + 2 * mt + (warp < 2 ? 4 * i : 0)) * 4);
            dst[2 * i] = slot_ptr(t.x + g * 16 + t4 * 8);
            dst[2 * i + 1] = slot_ptr(t.y + g * 16 + t4 * 8);
        }
        PROF(6);
        const uint32_t wobar = pin(bar_wo + (mt >> 1) * 8);
        asm volatile("bar.sync %0, 64;" ::"r"(obar) : "memory");
        uint2 ob[8];
#pragma unroll
        for (int ks = 0; ks < 8; ks++) ob[ks] = lds64(oa + ks * 32);
#pragma unroll
        for (int m = 0; m < 2; m++) {
            if (m == 0 || warp < 2) {
                mbar_wait(wobar + m * 8, 0);
                PROF(8);
                uint32_t wf[8][4];
#pragma unroll
                for (int ks = 0; ks < 8; ks++) ldsm4t(wf[ks], wa + m * (DH * 64) + ks * 1024);
                float c[4][4];
#pragma unroll
                for (int ks = 0; ks < 8; ks++) {
                    if (ks < 4) c[ks][0] = c[ks][1] = c[ks][2] = c[ks][3] = 0.f;
                    mma16816(c[ks & 3], wf[ks], ob[ks].x, ob[ks].y);
                }
                stg_relaxed2_if(t4 < 2, dst[2 * m], flag((c[0][0] + c[1][0]) + (c[2][0] + c[3][0])), flag((c[0][1] + c[1][1]) + (c[2][1] + c[3][1])));
                stg_relaxed2_if(t4 < 2, dst[2 * m + 1], flag((c[0][2] + c[1][2]) + (c[2][2] + c[3][2])), flag((c[0][3] + c[1][3]) + (c[2][3] + c[3][3])));
            }
        }
    }
    PROF(9);
    uint32_t x1w = 0;
    if (is_owner) {
        uint4 v;
        for (int it = 0;; it++) {
            v = ldg_relaxed(in1);
            if (__all_sync(0xffffffffu, and3(and3(v.x, v.y, v.z), v.w, 1u))) break;
            if (it > SPIN_LIMIT) __trap();
        }
        PROF(11);
        const float s0 = __uint_as_float(v.x) + __shfl_xor_sync(0xffffffffu, __uint_as_float(v.z), 8);
        const float s1 = __uint_as_float(v.y) + __shfl_xor_sync(0xffffffffu, __uint_as_float(v.w), 8);
        sts_f32(red_st, s0 + __shfl_xor_sync(0xffffffffu, s1, 16));
        nbar_sync<NB_E4, 256>();
        if (warp == 0) {
            float2 a[8];
#pragma unroll
            for (int w = 0; w < 8; w++) a[w] = lds_f32x2(red_ld + w * 128);
            const uint32_t aw = pack_bf(((a[0].x + a[1].x) + (a[2].x + a[3].x)) + ((a[4].x + a[5].x) + (a[6].x + a[7].x)),
                                        ((a[0].y + a[1].y) + (a[2].y + a[3].y)) + ((a[4].y + a[5].y) + (a[6].y + a[7].y)));
            x1w = bf2_add(xw, bf2_mul(ga_w, aw));
            stg_relaxed(x1_dst, x1w ^ 0x80008000u);
            if (lane == 0) mbar_arrive(bar_x1);
        }
        if (rst) stg_zero4(rst);
    }
    PROF(12);
    if (is_f) {
        uint32_t f1[5][2][4], f2[5][2][4];
        uint32_t d[6];
        auto load_x1 = [&] {
#pragma unroll
            for (int i = 0; i < 5; i++) d[i] = ldg_relaxed32(xin + i * 64);
        };
        auto have_x1 = [&] { return __all_sync(0xffffffffu, __vimin3_u32(__vimin3_u32(d[0], d[1], d[2]), d[3], d[4]) != 0u); };
        mbar_wait(w1bar, 0);
        load_x1();
        {
#pragma unroll
            for (int i = 0; i < 5; i++) { ldsm4t(f1[i][0], w1a + i * 1024); ldsm4t(f1[i][1], (w1a ^ 32) + i * 1024); }
            float c[2][4];
#pragma unroll
            for (int m = 0; m < 2; m++) c[m][0] = c[m][1] = c[m][2] = c[m][3] = 0.f;
#pragma unroll
            for (int i = 0; i < 5; i++) { mma16816(c[0], f1[i][0], cs[2 * i], cs[2 * i + 1]); mma16816(c[1], f1[i][1], cs[2 * i], cs[2 * i + 1]); }
#pragma unroll
            for (int i = 0; i < 5; i++) { cs[2 * i] = pin(odd ? 0u : cs[10 + i]); cs[2 * i + 1] = pin(odd ? cs[10 + i] : 0u); }
#pragma unroll
            for (int m = 0; m < 2; m++) sts128(ab_st + m * 512, make_uint4(__float_as_uint(c[m][0]), __float_as_uint(c[m][1]), __float_as_uint(c[m][2]), __float_as_uint(c[m][3])));
            nbar_arrive<NB_AB, 320>();
            d[0] |= __float_as_uint(c[1][3]) & (side >> 1);
        }
        PROF(10);
#pragma unroll 1
        for (int it = 0; !have_x1(); it++) {
            load_x1();
            if (it > SPIN_LIMIT) __trap();
        }
        PROF(13);
        {
            float y[2][4], st[4] = {0.f, 0.f, 0.f, 0.f};
            float z[2][4] = {};
#pragma unroll
            for (int m = 0; m < 2; m++) y[m][0] = y[m][1] = y[m][2] = y[m][3] = 0.f;
#pragma unroll
            for (int i = 0; i < 5; i++) d[i] = bf2_add(d[i], piv);
            d[5] = 0u;
#pragma unroll
            for (int i = 0; i < 5; i++) {
                if (i < 3) {
                    const uint32_t a[4] = {d[2 * i], 0x3f803f80u, d[2 * i + 1], 0x3f803f80u};
                    mma16816(st, a, d[2 * i], d[2 * i + 1]);
                }
                const uint32_t y0 = bf2_mul(d[i], cs[2 * i]), y1 = bf2_mul(d[i], cs[2 * i + 1]);
                if (i & 1) { mma16816(z[0], f1[i][0], y0, y1); mma16816(z[1], f1[i][1], y0, y1); }
                else { mma16816(y[0], f1[i][0], y0, y1); mma16816(y[1], f1[i][1], y0, y1); }
            }
            const float q = odd ? st[1] : st[0];
            const float q2 = q + __shfl_xor_sync(0xffffffffu, q, 4);
            if (diag && !odd) sts_f32x2(s_st, q2, st[2] + st[3]);
#pragma unroll
            for (int m = 0; m < 2; m++) sts_f32x2(y_st + m * 256, (z[m][0] + z[m][1]) + (y[m][0] + y[m][1]), (z[m][2] + z[m][3]) + (y[m][2] + y[m][3]));
        }
        nbar_arrive<NB_Y, 320>();
        PROF(14);
        mbar_wait(w2bar, 0);
        mbar_wait(w2bar + 8, 0);
#pragma unroll
        for (int i = 0; i < 5; i++) { ldsm4t(f2[i][0], w2a[i]); ldsm4t(f2[i][1], w2a[i] + 2048); }
        asm volatile("bar.sync %0, 128;" ::"r"(hbar) : "memory");
        PROF(15);
        {
            const uint4 hb = lds128(h_ld);
            float c[5][4];
#pragma unroll
            for (int i = 0; i < 5; i++) { c[i][0] = c[i][1] = c[i][2] = c[i][3] = 0.f; mma16816(c[i], f2[i][0], hb.x, hb.y); }
#pragma unroll
            for (int i = 0; i < 5; i++) {
                mma16816(c[i], f2[i][1], hb.z, hb.w);
                stg_relaxed(dst2[i], ~pack_bf(t4 < 2 ? c[i][0] : c[i][2], t4 < 2 ? c[i][1] : c[i][3]));
            }
        }
    }
    PROF(16);
    if (is_owner) {
        const uint32_t b2w = lds32(sb + OWN_B2 + (lane & 15) * 4), gb_ld = pin(sb + OWN_GB + (lane & 15) * 4);
        const bool two = tid < NF * 8 - 256;
        uint32_t v0, v1, w0 = ~0u, w1 = ~0u;
        for (int it = 0;; it++) {
            asm volatile("{\n.reg .pred q;\nsetp.ne.u32 q, %3, 0;\n@q ld.relaxed.gpu.global.v2.u32 {%0,%1}, [%2];\n}" : "+r"(w0), "+r"(w1) : "l"(in2b), "r"((uint32_t)two) : "memory");
            asm volatile("ld.relaxed.gpu.global.v2.u32 {%0,%1}, [%2];" : "=r"(v0), "=r"(v1) : "l"(in2a) : "memory");
            if (__all_sync(0xffffffffu, min(__vimin3_u32(v0, v1, w0), w1) != 0u)) break;
            if (it > SPIN_LIMIT) __trap();
        }
        PROF(17);
        const float s0 = (bf_lo(~v0) + bf_lo(~w0)) + __shfl_xor_sync(0xffffffffu, bf_lo(~v1) + bf_lo(~w1), 8);
        const float s1 = (bf_hi(~v0) + bf_hi(~w0)) + __shfl_xor_sync(0xffffffffu, bf_hi(~v1) + bf_hi(~w1), 8);
        sts_f32(red_st + (SC_E6 - SC_E4), s0 + __shfl_xor_sync(0xffffffffu, s1, 16));
        if (warp != 0) {
            nbar_arrive<NB_E6, 288>();
        } else {
            nbar_sync<NB_E6, 288>();
            float2 a[8];
#pragma unroll
            for (int i = 0; i < 8; i++) a[i] = lds_f32x2(red_ld + (SC_E6 - SC_E4) + i * 128);
            const uint32_t gb_w = lds32(gb_ld);
            const uint32_t aw = pack_bf(((a[0].x + a[1].x) + (a[2].x + a[3].x)) + ((a[4].x + a[5].x) + (a[6].x + a[7].x)),
                                        ((a[0].y + a[1].y) + (a[2].y + a[3].y)) + ((a[4].y + a[5].y) + (a[6].y + a[7].y)));
            x1w = bf2_add(x1w, bf2_mul(gb_w, bf2_add(aw, b2w)));
            if (lane < 16) asm volatile("st.global.u32 [%0], %1;" ::"l"(out_dst), "r"(x1w) : "memory");
        }
    }
    PROF(18);
    PROF_DUMP;
}

typedef CUresult (*EncodeFn)(CUtensorMap*, CUtensorMapDataType, cuuint32_t, void*, const cuuint64_t*, const cuuint64_t*, const cuuint32_t*,
                             const cuuint32_t*, CUtensorMapInterleave, CUtensorMapSwizzle, CUtensorMapL2promotion, CUtensorMapFloatOOBfill);

static CUtensorMap make_map(EncodeFn enc, const void* ptr, int cols, int rows, int box_cols, int box_rows, CUtensorMapSwizzle sw,
                            CUtensorMapL2promotion promo = CU_TENSOR_MAP_L2_PROMOTION_NONE) {
    CUtensorMap m;
    cuuint64_t dims[2] = {(cuuint64_t)cols, (cuuint64_t)rows};
    cuuint64_t strides[1] = {(cuuint64_t)cols * 2};
    cuuint32_t box[2] = {(cuuint32_t)box_cols, (cuuint32_t)box_rows};
    cuuint32_t es[2] = {1, 1};
    enc(&m, CU_TENSOR_MAP_DATA_TYPE_BFLOAT16, 2, const_cast<void*>(ptr), dims, strides, box, es, CU_TENSOR_MAP_INTERLEAVE_NONE, sw,
        promo, CU_TENSOR_MAP_FLOAT_OOB_FILL_NONE);
    return m;
}

}

extern "C" void kernel_launch(void* const* d_in, const int* in_sizes, int n_in, void* d_out, int out_size) {
    (void)in_sizes; (void)n_in; (void)out_size;
    static EncodeFn enc = nullptr;
    if (!enc) {
        void* fn = nullptr;
        cudaDriverEntryPointQueryResult qr;
        cudaGetDriverEntryPoint("cuTensorMapEncodeTiled", &fn, cudaEnableDefault, &qr);
        enc = (EncodeFn)fn;
        cudaFuncSetAttribute(fused_kernel, cudaFuncAttributeMaxDynamicSharedMemorySize, SMEM_BYTES);
    }
    Params p;
    p.x = (const __nv_bfloat16*)d_in[0];
    p.kc = (const __nv_bfloat16*)d_in[1];
    p.vc = (const __nv_bfloat16*)d_in[2];
    p.b1 = (const __nv_bfloat16*)d_in[7];
    p.b2 = (const __nv_bfloat16*)d_in[9];
    p.c = (const __nv_bfloat16*)d_in[10];
    p.out = (__nv_bfloat16*)d_out;
    CUtensorMap tm_wmod = make_map(enc, d_in[11], NMOD, D, 32, 160, CU_TENSOR_MAP_SWIZZLE_64B, CU_TENSOR_MAP_L2_PROMOTION_L2_128B);
    CUtensorMap tm_wq = make_map(enc, d_in[3], NH * DH, D, 32, 160, CU_TENSOR_MAP_SWIZZLE_64B, CU_TENSOR_MAP_L2_PROMOTION_L2_128B);
    CUtensorMap tm_wo = make_map(enc, d_in[4], D, NH * DH, 32, 128, CU_TENSOR_MAP_SWIZZLE_64B);
    CUtensorMap tm_w1 = make_map(enc, d_in[6], FF, D, 32, 160, CU_TENSOR_MAP_SWIZZLE_64B);
    CUtensorMap tm_w2 = make_map(enc, d_in[8], D, FF, 64, 32, CU_TENSOR_MAP_SWIZZLE_128B);
    CUtensorMap tm_v = make_map(enc, d_in[2], DH, NB * NH * SK, 64, TILE_KEYS, CU_TENSOR_MAP_SWIZZLE_128B);
    CUtensorMap tm_gb = make_map(enc, d_in[11], NMOD, D, 8, 160, CU_TENSOR_MAP_SWIZZLE_NONE, CU_TENSOR_MAP_L2_PROMOTION_L2_128B);
    fused_kernel<<<NCTA, NTHREADS, SMEM_BYTES>>>(p, tm_wmod, tm_wq, tm_wo, tm_w1, tm_w2, tm_v, tm_gb);
}
```

```cpp
#include <cuda_runtime.h>
#include <cuda.h>
#include <cuda_bf16.h>
#include <stdint.h>
#include <stdlib.h>

namespace {

constexpr int NB = 4, D = 640, NH = 32, DH = 128, SK = 8192, WIN = 2048, FF = 1728, NMOD = 6 * D;
constexpr int NCTA = 128;
constexpr int NOWN = 80;
constexpr int NF = 54;
constexpr int NTHREADS = 320;
constexpr int TILE_KEYS = 64;
constexpr int TILE_BYTES = TILE_KEYS * DH * 2;
constexpr int NITEM = 2 * WIN / TILE_KEYS;
constexpr int NS = 8;
constexpr int NMODC = 120;
constexpr int SPIN_LIMIT = 1 << 18;
#define INFLIGHT 3
#define WQ_DELAY 500
#define MOD_T 4200
#define Q_PAUSE 1100
#define PACE_A 7500
#define PACE_TAU 635
#define ROT(c) 0
#define PF_END 16
#define PH_FIRST 24
#define PH_LAG 5
#define LAT_T 2300
#define WO_T -1050
#define WO_S 250
#define W1_T 900
#define W2_T 1600
#define GB_T 2300
#define GB_EV 600
#define CLR_CHECK 28000
constexpr int NPROBE = 8, PROBE_END = 10000;
constexpr int SEG_J = 8;

constexpr int OFF_RING = 0;
constexpr int OFF_X = OFF_RING + NS * TILE_BYTES;
constexpr int X_WM = OFF_X;
constexpr int X_WQ = OFF_X + D * 64;
constexpr int X_WO = OFF_X;
constexpr int X_W1 = X_WO + 5 * DH * 64;
constexpr int X_END = X_W1 + D * 64;
constexpr int X_W2 = OFF_RING;
constexpr int X_GB = OFF_RING + 3 * TILE_BYTES;
static_assert(X_WQ + D * 64 <= X_END, "prologue weights must fit");
constexpr int VEC_STRIDE = 1296;
constexpr int OFF_VA = X_END;
constexpr int OFF_VB = OFF_VA + 4 * VEC_STRIDE;
constexpr int OFF_RED = OFF_VB + 4 * VEC_STRIDE;
constexpr int OFF_ML = OFF_RED + 4 * VEC_STRIDE;
constexpr int O_STRIDE = 288;
constexpr int OFF_O = OFF_ML + 64;
constexpr int OFF_Q = OFF_O + 4 * O_STRIDE;
constexpr int OFF_OWN = OFF_Q + 256;
constexpr int OWN_X = OFF_OWN, OWN_B2 = OWN_X + 64, OWN_GA = OWN_B2 + 64, OWN_GB = OWN_GA + 64, OWN_B1 = OWN_GB + 64;
constexpr int OFF_STAT = OWN_B1 + 128;
constexpr int OFF_TAB1 = OFF_STAT + 32;
constexpr int OFF_TAB2 = OFF_TAB1 + NOWN * 4;
constexpr int OFF_SIDE = OFF_TAB2 + NOWN * 4;
constexpr int OFF_BAR = OFF_SIDE + 8;
constexpr int NBAR = 2 * NS + 32;
constexpr int SMEM_BYTES = OFF_BAR + NBAR * 8;
constexpr int SC_OP = OFF_RING + 4 * TILE_BYTES;
constexpr int SC_AB = SC_OP + 4096;
constexpr int SC_Y = SC_AB + 8192;
constexpr int SC_ST = SC_Y + 4096;
constexpr int SC_E4 = SC_ST + 256;
constexpr int SC_E6 = SC_E4 + 1024;
constexpr int SC_P = SC_E6 + 1024;
constexpr int SC_H1 = SC_P + 256;
static_assert(SMEM_BYTES <= 232448, "smem");
static_assert(OFF_BAR % 8 == 0 && OFF_X % 1024 == 0 && X_WQ % 512 == 0 && X_W1 % 512 == 0 && OFF_VA % 16 == 0 && OFF_RED % 16 == 0 && OFF_ML % 16 == 0 && OFF_O % 16 == 0 && OFF_Q % 16 == 0, "align");
constexpr int NB_O = 2  , NB_E4 = 10, NB_E6 = 11, NB_AB = 12, NB_Y = 13, NB_H1 = 14  ;

__device__ __align__(128) uint32_t g_mod[NMODC * 64];
__device__ __align__(128) uint32_t g_q[NCTA * 128];
__device__ uint32_t g_clr[NCTA];
__device__ __align__(128) uint32_t g_phase[8 * 32];
constexpr int SL_P1 = 0;
constexpr int SL_P2 = SL_P1 + NOWN;
constexpr int SL_O = SL_P2 + 2 * NOWN;
constexpr int SL_X1 = SL_O + 8;
constexpr int SL_SIDE = SL_X1 + 3;
static_assert(SL_SIDE < 256, "one 2 MB page");
__device__ uint32_t g_slots[2 * 256 * 2048];
__device__ __forceinline__ uint32_t* slot(int i, int side) {
    const size_t base = ((size_t)g_slots + 0x1fffff) & ~(size_t)0x1fffff;
    return (uint32_t*)base + i * 2048 + (((__popc(i & 0x59) ^ side) & 1) << 10);
}
#define PROF_DECL
#define HPROF(i) do { } while (0)
#define PROF(i) do { } while (0)
#define PROF_DUMP do { } while (0)

__device__ __forceinline__ uint32_t smem_u32(const void* p) { return (uint32_t)__cvta_generic_to_shared(p); }
__device__ __forceinline__ void mbar_init(uint32_t bar, uint32_t cnt) { asm volatile("mbarrier.init.shared::cta.b64 [%0], %1;" ::"r"(bar), "r"(cnt) : "memory"); }
__device__ __forceinline__ void mbar_expect_tx(uint32_t bar, uint32_t bytes) { asm volatile("mbarrier.arrive.expect_tx.shared::cta.b64 _, [%0], %1;" ::"r"(bar), "r"(bytes) : "memory"); }
__device__ __forceinline__ void mbar_arrive(uint32_t bar) { asm volatile("mbarrier.arrive.shared::cta.b64 _, [%0];" ::"r"(bar) : "memory"); }
__device__ __forceinline__ void mbar_wait(uint32_t bar, uint32_t parity) {
    uint32_t ok;
    int it = 0;
    while (true) {
        asm volatile("{\n.reg .pred p;\nmbarrier.try_wait.parity.shared::cta.b64 p, [%1], %2;\nselp.u32 %0, 1, 0, p;\n}" : "=r"(ok) : "r"(bar), "r"(parity) : "memory");
        if (ok) break;
        if (++it > SPIN_LIMIT) __trap();
    }
}
__device__ __forceinline__ void bulk_load(uint32_t dst, const void* src, uint32_t bytes, uint32_t bar, uint64_t pol) {
    asm volatile("cp.async.bulk.shared::cluster.global.mbarrier::complete_tx::bytes.L2::cache_hint [%0], [%1], %2, [%3], %4;"
                 ::"r"(dst), "l"(src), "r"(bytes), "r"(bar), "l"(pol) : "memory");
}
__device__ __forceinline__ void bar_cons() { asm volatile("bar.sync 1, 256;" ::: "memory"); }
template <int ID, int N> __device__ __forceinline__ void nbar_sync() { asm volatile("bar.sync %0, %1;" ::"n"(ID), "n"(N) : "memory"); }
template <int ID, int N> __device__ __forceinline__ void nbar_arrive() { asm volatile("bar.arrive %0, %1;" ::"n"(ID), "n"(N) : "memory"); }
__device__ __forceinline__ bool mbar_test(uint32_t bar, uint32_t parity) {
    uint32_t ok;
    asm volatile("{\n.reg .pred p;\nmbarrier.test_wait.parity.shared::cta.b64 p, [%1], %2;\nselp.u32 %0, 1, 0, p;\n}" : "=r"(ok) : "r"(bar), "r"(parity) : "memory");
    return ok;
}
__device__ __forceinline__ uint32_t pin(uint32_t v) { asm volatile("" : "+r"(v)); return v; }
template <class T> __device__ __forceinline__ T pin_hard(T v) { return __shfl_sync(0xffffffffu, v, threadIdx.x & 31); }
template <class T> __device__ __forceinline__ T* pin(T* v) { asm volatile("" : "+l"(v)); return v; }
__device__ __forceinline__ void ldsm4(uint32_t (&a)[4], uint32_t addr) {
    asm volatile("ldmatrix.sync.aligned.m8n8.x4.shared.b16 {%0,%1,%2,%3}, [%4];" : "=r"(a[0]), "=r"(a[1]), "=r"(a[2]), "=r"(a[3]) : "r"(addr) : "memory");
}
__device__ __forceinline__ void ldsm4t(uint32_t (&a)[4], uint32_t addr) {
    asm volatile("ldmatrix.sync.aligned.m8n8.x4.trans.shared.b16 {%0,%1,%2,%3}, [%4];" : "=r"(a[0]), "=r"(a[1]), "=r"(a[2]), "=r"(a[3]) : "r"(addr) : "memory");
}
__device__ __forceinline__ void mma16816(float (&c)[4], const uint32_t (&a)[4], uint32_t b0, uint32_t b1) {
    asm volatile("mma.sync.aligned.m16n8k16.row.col.f32.bf16.bf16.f32 {%0,%1,%2,%3}, {%4,%5,%6,%7}, {%8,%9}, {%0,%1,%2,%3};"
                 : "+f"(c[0]), "+f"(c[1]), "+f"(c[2]), "+f"(c[3]) : "r"(a[0]), "r"(a[1]), "r"(a[2]), "r"(a[3]), "r"(b0), "r"(b1));
}
__device__ __forceinline__ uint32_t lds32(uint32_t addr) { uint32_t v; asm volatile("ld.shared.u32 %0, [%1];" : "=r"(v) : "r"(addr) : "memory"); return v; }
__device__ __forceinline__ float lds_f32(uint32_t addr) { float v; asm volatile("ld.shared.f32 %0, [%1];" : "=f"(v) : "r"(addr) : "memory"); return v; }
__device__ __forceinline__ float2 lds_f32x2(uint32_t addr) { float2 v; asm volatile("ld.shared.v2.f32 {%0,%1}, [%2];" : "=f"(v.x), "=f"(v.y) : "r"(addr) : "memory"); return v; }
__device__ __forceinline__ float4 lds_f32x4(uint32_t addr) { float4 v; asm volatile("ld.shared.v4.f32 {%0,%1,%2,%3}, [%4];" : "=f"(v.x), "=f"(v.y), "=f"(v.z), "=f"(v.w) : "r"(addr) : "memory"); return v; }
__device__ __forceinline__ uint2 lds64(uint32_t addr) { uint2 v; asm volatile("ld.shared.v2.u32 {%0,%1}, [%2];" : "=r"(v.x), "=r"(v.y) : "r"(addr) : "memory"); return v; }
__device__ __forceinline__ uint4 lds128(uint32_t addr) { uint4 v; asm volatile("ld.shared.v4.u32 {%0,%1,%2,%3}, [%4];" : "=r"(v.x), "=r"(v.y), "=r"(v.z), "=r"(v.w) : "r"(addr) : "memory"); return v; }
__device__ __forceinline__ void sts16(uint32_t addr, uint32_t v) { asm volatile("st.shared.b16 [%0], %1;" ::"r"(addr), "h"((unsigned short)v) : "memory"); }
__device__ __forceinline__ void sts32(uint32_t addr, uint32_t v) { asm volatile("st.shared.u32 [%0], %1;" ::"r"(addr), "r"(v) : "memory"); }
__device__ __forceinline__ void sts_f32(uint32_t addr, float v) { asm volatile("st.shared.f32 [%0], %1;" ::"r"(addr), "f"(v) : "memory"); }
__device__ __forceinline__ void sts_f32x2(uint32_t addr, float a, float b) { asm volatile("st.shared.v2.f32 [%0], {%1,%2};" ::"r"(addr), "f"(a), "f"(b) : "memory"); }
__device__ __forceinline__ void sts128(uint32_t addr, uint4 v) { asm volatile("st.shared.v4.u32 [%0], {%1,%2,%3,%4};" ::"r"(addr), "r"(v.x), "r"(v.y), "r"(v.z), "r"(v.w) : "memory"); }
__device__ __forceinline__ uint4 ldg_relaxed(const uint32_t* p) {
    uint4 v;
    asm volatile("ld.relaxed.gpu.global.v4.u32 {%0,%1,%2,%3}, [%4];" : "=r"(v.x), "=r"(v.y), "=r"(v.z), "=r"(v.w) : "l"(p) : "memory");
    return v;
}
__device__ __forceinline__ void ldg_relaxed_if(bool on, uint4& v, const uint32_t* p) {
    asm volatile("{\n.reg .pred q;\nsetp.ne.u32 q, %5, 0;\n@q ld.relaxed.gpu.global.v4.u32 {%0,%1,%2,%3}, [%4];\n}"
                 : "+r"(v.x), "+r"(v.y), "+r"(v.z), "+r"(v.w) : "l"(p), "r"((uint32_t)on) : "memory");
}
__device__ __forceinline__ void stg_relaxed2_if(bool on, uint32_t* p, uint32_t a, uint32_t b) {
    asm volatile("{\n.reg .pred q;\nsetp.ne.u32 q, %3, 0;\n@q st.relaxed.gpu.global.v2.u32 [%0], {%1,%2};\n}" ::"l"(p), "r"(a), "r"(b), "r"((uint32_t)on) : "memory");
}
__device__ __forceinline__ uint32_t ldg_relaxed32(const uint32_t* p) { uint32_t v; asm volatile("ld.relaxed.gpu.global.u32 %0, [%1];" : "=r"(v) : "l"(p) : "memory"); return v; }
__device__ __forceinline__ void stg_relaxed(uint32_t* p, uint32_t v) { asm volatile("st.relaxed.gpu.global.u32 [%0], %1;" ::"l"(p), "r"(v) : "memory"); }
__device__ __forceinline__ void stg_zero4(uint32_t* p) { asm volatile("st.relaxed.gpu.global.v4.u32 [%0], {%1,%1,%1,%1};" ::"l"(p), "r"(0u) : "memory"); }
__device__ __forceinline__ bool ready(const uint4& v) { return (v.x != 0u) & (v.y != 0u) & (v.z != 0u) & (v.w != 0u); }
__device__ __forceinline__ uint32_t min4(const uint4& v) { return min(__vimin3_u32(v.x, v.y, v.z), v.w); }
__device__ __forceinline__ uint4 inv4(const uint4& v) { return make_uint4(~v.x, ~v.y, ~v.z, ~v.w); }
__device__ __forceinline__ uint32_t pack_bf(float lo, float hi) {
    uint32_t r;
    asm("cvt.rn.bf16x2.f32 %0, %1, %2;" : "=r"(r) : "f"(hi), "f"(lo));
    return r;
}
__device__ __forceinline__ float bfr(float x) { return __uint_as_float(pack_bf(0.f, x) & 0xffff0000u); }
__device__ __forceinline__ float bf_lo(uint32_t w) { return __uint_as_float(w << 16); }
__device__ __forceinline__ float bf_hi(uint32_t w) { return __uint_as_float(w & 0xffff0000u); }
__device__ __forceinline__ float bf2f(__nv_bfloat16 v) { return __bfloat162float(v); }
__device__ __forceinline__ float ex2(float x) { float y; asm("ex2.approx.ftz.f32 %0, %1;" : "=f"(y) : "f"(x)); return y; }
__device__ __forceinline__ float rcp_fast(float x) { float y; asm("rcp.approx.ftz.f32 %0, %1;" : "=f"(y) : "f"(x)); return y; }
__device__ __forceinline__ float rsqrt_fast(float x) { float y; asm("rsqrt.approx.ftz.f32 %0, %1;" : "=f"(y) : "f"(x)); return y; }
__device__ __forceinline__ float sqrt_fast(float x) { float y; asm("sqrt.approx.f32 %0, %1;" : "=f"(y) : "f"(x)); return y; }
__device__ __forceinline__ uint32_t bf2_add(uint32_t a, uint32_t b) { uint32_t r; asm("add.rn.bf16x2 %0, %1, %2;" : "=r"(r) : "r"(a), "r"(b)); return r; }
__device__ __forceinline__ uint32_t bf2_sub(uint32_t a, uint32_t b) { uint32_t r; asm("sub.rn.bf16x2 %0, %1, %2;" : "=r"(r) : "r"(a), "r"(b)); return r; }
__device__ __forceinline__ uint32_t bf2_mul(uint32_t a, uint32_t b) { uint32_t r; asm("mul.rn.bf16x2 %0, %1, %2;" : "=r"(r) : "r"(a), "r"(b)); return r; }
__device__ __forceinline__ uint32_t gtime32() { uint32_t c; asm volatile("mov.u32 %0, %%globaltimer_lo;" : "=r"(c)); return c; }
__device__ __forceinline__ uint32_t clock32() { uint32_t c; asm volatile("mov.u32 %0, %%clock;" : "=r"(c)); return c; }

__device__ __forceinline__ float warp_sum(float v) {
#pragma unroll
    for (int o = 16; o > 0; o >>= 1) v += __shfl_xor_sync(0xffffffffu, v, o);
    return v;
}

struct Params {
    const __nv_bfloat16 *x, *kc, *vc, *b1, *b2, *c;
    __nv_bfloat16* out;
};

__device__ __forceinline__ void tma2d(uint32_t dst, const CUtensorMap* tm, int x, int y, uint32_t bar) {
    asm volatile("cp.async.bulk.tensor.2d.shared::cluster.global.mbarrier::complete_tx::bytes [%0], [%1, {%2, %3}], [%4];"
                 ::"r"(dst), "l"(tm), "r"(x), "r"(y), "r"(bar) : "memory");
}

__device__ __forceinline__ void tma2d_hint(uint32_t dst, const CUtensorMap* tm, int x, int y, uint32_t bar, uint64_t pol) {
    asm volatile("cp.async.bulk.tensor.2d.shared::cluster.global.mbarrier::complete_tx::bytes.L2::cache_hint [%0], [%1, {%2, %3}], [%4], %5;"
                 ::"r"(dst), "l"(tm), "r"(x), "r"(y), "r"(bar), "l"(pol) : "memory");
}
__device__ __forceinline__ uint32_t flag(float v) { return __float_as_uint(v) | 1u; }
__device__ __forceinline__ uint32_t* slot_ptr(uint32_t lo) {
    uint32_t* r;
    asm volatile("mov.b64 %0, {%1, %2};" : "=l"(r) : "r"(lo), "r"((uint32_t)((size_t)slot(0, 0) >> 32)));
    return r;
}

__device__ __forceinline__ void load_bfrag(uint32_t vec, int stride, int k0, int g, int t, uint32_t& b0, uint32_t& b1) {
    uint32_t a = vec + (g & 3) * stride + (k0 + 2 * t) * 2;
    b0 = lds32(a);
    b1 = lds32(a + 16);
}

__device__ __forceinline__ void ln_finish(float pivot, float sum, float sumsq, uint32_t& m2, float& rden) {
    float dm = sum * (1.f / D);
    float var = fmaxf(sumsq * (1.f / D) - dm * dm, 0.f);
    float mean = pivot + dm;
    m2 = pack_bf(mean, mean);
    rden = rcp_fast(bfr(sqrt_fast(bfr(bfr(var) + 1e-5f))));
}
__device__ __forceinline__ uint32_t ln_mod_pair(uint32_t xw, uint32_t cw, uint32_t sw, uint32_t m2, float rden) {
    uint32_t d = bf2_sub(xw, m2);
    uint32_t ln = pack_bf(bf_lo(d) * rden, bf_hi(d) * rden);
    return bf2_add(bf2_mul(ln, bf2_add(cw, 0x3f803f80u)), sw);
}
__device__ __forceinline__ uint4 ln_mod4(const uint4& x, const uint4& c, const uint4& s, uint32_t m2, float rden) {
    return make_uint4(ln_mod_pair(x.x, c.x, s.x, m2, rden), ln_mod_pair(x.y, c.y, s.y, m2, rden),
                      ln_mod_pair(x.z, c.z, s.z, m2, rden), ln_mod_pair(x.w, c.w, s.w, m2, rden));
}
__device__ __forceinline__ void acc_stats(const uint4& v, float pv, float& s, float& q) {
    const float a0 = bf_lo(v.x) - pv, a1 = bf_hi(v.x) - pv, a2 = bf_lo(v.y) - pv, a3 = bf_hi(v.y) - pv;
    const float a4 = bf_lo(v.z) - pv, a5 = bf_hi(v.z) - pv, a6 = bf_lo(v.w) - pv, a7 = bf_hi(v.w) - pv;
    s += ((a0 + a1) + (a2 + a3)) + ((a4 + a5) + (a6 + a7));
    q += (fmaf(a0, a0, a1 * a1) + fmaf(a2, a2, a3 * a3)) + (fmaf(a4, a4, a5 * a5) + fmaf(a6, a6, a7 * a7));
}
__device__ __forceinline__ uint32_t* mod_slot(int kind, int j, int b) { return g_mod + (kind * 20 + (j >> 2)) * 64 + b * 16 + (j & 3) * 4; }

template <int N>
__device__ __forceinline__ void poll_n(uint4 (&v)[N], const uint32_t* const* ptr, const bool* on) {
    bool pend[N];
#pragma unroll
    for (int i = 0; i < N; i++) pend[i] = on[i];
    int it = 0;
    while (true) {
#pragma unroll
        for (int i = 0; i < N; i++) if (pend[i]) v[i] = ldg_relaxed(ptr[i]);
        bool any = false;
#pragma unroll
        for (int i = 0; i < N; i++) { pend[i] = pend[i] && !ready(v[i]); any |= pend[i]; }
        if (!__any_sync(0xffffffffu, any)) break;
        if (++it > SPIN_LIMIT) __trap();
    }
#pragma unroll
    for (int i = 0; i < N; i++) v[i] = inv4(v[i]);
}
__device__ __forceinline__ uint4 poll1(const uint32_t* p, bool on) {
    uint4 v[1] = {make_uint4(0, 0, 0, 0)};
    const uint32_t* const ptr[1] = {p};
    const bool o[1] = {on};
    poll_n<1>(v, ptr, o);
    return v[0];
}

#define OWNER_EXCHANGE_AND_VOTE \
    "shfl.sync.bfly.b32 a, z, 8, 31, 0xffffffff;\nshfl.sync.bfly.b32 b, y, 16, 31, 0xffffffff;\nshfl.sync.bfly.b32 c, w, 24, 31, 0xffffffff;\n" \
    "setp.ne.u32 q, t, 0;\nvote.sync.all.pred q, q, 0xffffffff;\n@!q bra.uni L_%=;\nadd.f32 a, a, x;\nadd.f32 b, b, c;\nadd.f32 %0, a, b;\n}"
__device__ __forceinline__ float poll_e4(const uint32_t* p) {
    float s;
    asm volatile("{\n.reg .pred q;\n.reg .b32 t, n, x, y, z, w, a, b, c;\nmov.u32 n, 0;\n"
                 "L_%=:\nld.relaxed.gpu.global.v4.u32 {x, y, z, w}, [%1];\nadd.u32 n, n, 1;\nsetp.gt.u32 q, n, %2;\n@q trap;\nbar.warp.sync 0xffffffff;\n"
                 "lop3.b32 t, x, y, z, 0x80;\nlop3.b32 t, t, w, 1, 0x80;\n" OWNER_EXCHANGE_AND_VOTE
                 : "=f"(s) : "l"(p), "n"(SPIN_LIMIT) : "memory");
    return s;
}
__device__ __forceinline__ float poll_e6(const uint32_t* pa, const uint32_t* pb, bool two) {
    float s;
    asm volatile("{\n.reg .pred q, r;\n.reg .b32 t, n, x, y, z, w, a, b, c, u0, u1, v0, v1;\nmov.u32 n, 0;\nsetp.ne.u32 r, %4, 0;\nmov.b32 v0, 0xffffffff;\nmov.b32 v1, 0xffffffff;\n"
                 "L_%=:\n@r ld.relaxed.gpu.global.v2.u32 {v0, v1}, [%3];\nld.relaxed.gpu.global.v2.u32 {u0, u1}, [%1];\nadd.u32 n, n, 1;\nsetp.gt.u32 q, n, %2;\n@q trap;\nbar.warp.sync 0xffffffff;\n"
                 "lop3.b32 a, u0, 0xffff0000, 0, 0x0c;\nlop3.b32 b, v0, 0xffff0000, 0, 0x0c;\nadd.f32 y, a, b;\n"
                 "lop3.b32 a, u1, 0xffff0000, 0, 0x0c;\nlop3.b32 b, v1, 0xffff0000, 0, 0x0c;\nadd.f32 w, a, b;\n"
                 "shl.b32 a, u1, 16;\nshl.b32 b, v1, 16;\nxor.b32 a, a, 0xffff0000;\nxor.b32 b, b, 0xffff0000;\nadd.f32 z, a, b;\n"
                 "shl.b32 a, u0, 16;\nshl.b32 b, v0, 16;\nxor.b32 a, a, 0xffff0000;\nxor.b32 b, b, 0xffff0000;\nadd.f32 x, a, b;\n"
                 "min.u32 t, u0, u1;\nmin.u32 t, t, v0;\nmin.u32 t, t, v1;\n" OWNER_EXCHANGE_AND_VOTE
                 : "=f"(s) : "l"(pa), "n"(SPIN_LIMIT), "l"(pb), "r"((uint32_t)two) : "memory");
    return s;
}

__device__ __forceinline__ void gelu_stage(uint32_t sb, int m, int lane) {
    const int g = lane >> 2, b = lane & 3;
    const uint32_t y_ld = pin_hard(sb + SC_Y + m * 256 + lane * 8), s_ld = pin_hard(sb + SC_ST + b * 64);
    const uint32_t h_st = pin_hard(sb + SC_H1 + b * 64 + (g >> 1) * 16 + m * 8 + (g & 1) * 2);
    float a0 = 0.f, b0 = lds_f32(sb + OWN_B1 + (16 * m + g) * 4), a1 = 0.f, b1 = lds_f32(sb + OWN_B1 + (16 * m + g + 8) * 4);
    const float piv = bf_hi(lds32(sb + OFF_STAT + b * 8));
    nbar_sync<NB_AB, 320>();
#pragma unroll
    for (int w = 0; w < 8; w++) {
        const float4 t = lds_f32x4(sb + SC_AB + w * 1024 + m * 512 + lane * 16);
        a0 += t.x; b0 += t.y; a1 += t.z; b1 += t.w;
    }
    sts128(sb + SC_AB + m * 512 + lane * 16, make_uint4(__float_as_uint(a0), __float_as_uint(b0), __float_as_uint(a1), __float_as_uint(b1)));
    nbar_sync<NB_Y, 320>();
    float4 q[4];
    float2 y[8];
#pragma unroll
    for (int i = 0; i < 4; i++) q[i] = lds_f32x4(s_ld + i * 16);
#pragma unroll
    for (int w = 0; w < 8; w++) y[w] = lds_f32x2(y_ld + w * 512);
    const float dm = (((q[0].y + q[0].w) + (q[1].y + q[1].w)) + ((q[2].y + q[2].w) + (q[3].y + q[3].w))) * (1.f / D);
    const float sq = ((q[0].x + q[0].z) + (q[1].x + q[1].z)) + ((q[2].x + q[2].z) + (q[3].x + q[3].z));
    const float r = rsqrt_fast(fmaxf(fmaf(-dm, dm, fmaf(sq, 1.f / D, 1e-5f)), 1e-5f));
    const float y0 = ((y[0].x + y[1].x) + (y[2].x + y[3].x)) + ((y[4].x + y[5].x) + (y[6].x + y[7].x));
    const float y1 = ((y[0].y + y[1].y) + (y[2].y + y[3].y)) + ((y[4].y + y[5].y) + (y[6].y + y[7].y));
    const float dmr = piv - bfr(piv - dm);
    const float u0 = fmaf(r, fmaf(dmr, a0, -y0), b0), u1 = fmaf(r, fmaf(dmr, a1, -y1), b1);
    const float e0 = ex2(u0 * fmaf(u0 * u0, -0.044715f * 2.302208198144325f, -2.302208198144325f));
    const float e1 = ex2(u1 * fmaf(u1 * u1, -0.044715f * 2.302208198144325f, -2.302208198144325f));
    sts16(h_st, pack_bf(u0 * rcp_fast(1.f + e0), 0.f));
    sts16(h_st + 4, pack_bf(u1 * rcp_fast(1.f + e1), 0.f));
#pragma unroll
    for (int w = 0; w < 4; w++) asm volatile("bar.arrive %0, 128;" ::"r"((NB_H1 + w) & 15) : "memory");
}

struct Roles { bool is_f, is_owner; int f, own; };
__device__ __forceinline__ Roles roles(int cta) {
    Roles r;
    r.f = (cta * 27) >> 6;
    r.is_f = (((cta + 1) * 27) >> 6) != r.f;
    r.is_owner = !r.is_f || r.f % 9 == 4;
    r.own = r.is_f ? 74 + r.f / 9 : cta - r.f;
    return r;
}

__global__ void __launch_bounds__(NTHREADS, 1)
fused_kernel(const Params p, const __grid_constant__ CUtensorMap tm_wmod, const __grid_constant__ CUtensorMap tm_wq,
             const __grid_constant__ CUtensorMap tm_wo, const __grid_constant__ CUtensorMap tm_w1, const __grid_constant__ CUtensorMap tm_w2,
             const __grid_constant__ CUtensorMap tm_v, const __grid_constant__ CUtensorMap tm_gb) {
    extern __shared__ __align__(1024) unsigned char smem[];
    const uint32_t t_start = gtime32();
    if (threadIdx.x == 0) {
        const uint32_t c_ = blockIdx.x;
        const uint32_t off = ((c_ & 3) << 26) + (c_ >> 2) * (1u << 21) + (ROT(c_) << 14) + (SK - WIN) * DH * 2;
        asm volatile("cp.async.bulk.prefetch.L2.global.L2::cache_hint [%0], %1, %2;" ::"l"((const char*)p.kc + off), "r"(TILE_BYTES), "l"(0x12f0000000000000ull  ) : "memory");
    }
    const uint32_t sb = smem_u32(smem);
    const int cta = blockIdx.x;
    const int head = cta >> 2, bown = cta & 3;
    const int rot = ROT(cta);
    const char* const kb = (const char*)(p.kc + ((size_t)(bown * NH + head) * SK + (SK - WIN)) * DH);
    uint64_t pol = 0;
    if (threadIdx.x == 256) {
        mbar_init(sb + OFF_BAR, 1);
        asm volatile("fence.mbarrier_init.release.cluster;" ::: "memory");
        asm volatile("createpolicy.fractional.L2::evict_first.b64 %0, 1.0;" : "=l"(pol));
        mbar_expect_tx(sb + OFF_BAR, TILE_BYTES);
        bulk_load(sb + OFF_RING, kb + (size_t)rot * TILE_BYTES, TILE_BYTES, sb + OFF_BAR, pol);
        if ((((head + 1) * 5) >> 4) != ((head * 5) >> 4)) {
            const uint32_t bar = sb + OFF_BAR + 2 * NS * 8;
            mbar_init(bar, 1);
            asm volatile("fence.mbarrier_init.release.cluster;" ::: "memory");
            mbar_expect_tx(bar, D * 64);
#pragma unroll 1
            for (int r = 0; r < D; r += 160) tma2d(sb + X_WM + r * 64, &tm_wmod, 32 * (((head * 5) >> 4) * 4 + bown), r, bar);
        }
    }
    const uint32_t bar_full = sb + OFF_BAR, bar_empty = bar_full + NS * 8;
    const uint32_t bar_wm = bar_empty + NS * 8, bar_wq = bar_wm + 8, bar_xfree = bar_wq + 8, bar_wo = bar_xfree + 8  ;
    const uint32_t bar_w1 = bar_wo + 40  , bar_w2 = bar_w1 + 32  , bar_help = bar_w2 + 80, bar_v = bar_help + 8  ;
    const uint32_t bar_gb = bar_v + 32  , bar_x1 = bar_gb + 32;
    const int tid = threadIdx.x, warp = tid >> 5, lane = tid & 31;
    const Roles role = roles(cta);
    const bool is_f = role.is_f, is_owner = role.is_owner;
    const int f = role.f, own = role.own;
    const bool crit = (((head + 1) * 5) >> 4) != ((head * 5) >> 4);
    const int mr = cta - ((head * 5) >> 4) * 4, mq = ((head * 5) >> 4) * 4 + bown;
    const int ml = mr * 31 / 44;
    const bool late = !crit && (mr + 1) * 31 / 44 != ml;
    const int mc = crit ? mq : ml < 60 ? 40 + ml : 58 + ml;
    const bool gb_own = is_owner && own < 72;

    PROF_DECL
    PROF(0);
    uint4 xa = make_uint4(0, 0, 0, 0), xb = xa, ca0 = xa, ca1 = xa, xs[3] = {xa, xa, xa};
    uint32_t own0 = 0;
    __nv_bfloat16 own2 = __float2bfloat16(0.f);
    if (warp < 8) {
        xa = *(const uint4*)(p.x + (tid & 3) * D + (tid >> 2) * 8);
        ca0 = ((const uint4*)p.c)[tid];
        if (tid < 64) { xb = *(const uint4*)(p.x + (tid & 3) * D + (64 + (tid >> 2)) * 8); ca1 = ((const uint4*)p.c)[256 + tid]; }
        if (warp < 4) {
#pragma unroll
            for (int i = 0; i < 3; i++) if (lane + 32 * i < 80) xs[i] = ((const uint4*)p.x)[warp * 80 + lane + 32 * i];
        } else if (warp == 4) {
            if (is_owner) own0 = *(const uint32_t*)((lane < 16 ? p.x + (lane >> 2) * D : p.b2) + 8 * own + 2 * (lane & 3));
            if (is_f) own2 = p.b1[32 * f + lane];
        }
    }
    const char* const vb = (const char*)(p.vc + ((size_t)(bown * NH + head) * SK + (SK - WIN)) * DH);
    const uint32_t bar_first = crit ? bar_wm : bar_wq;
    if (threadIdx.x == 256) {
        if (!crit) {
            mbar_init(bar_wq, 1);
            asm volatile("fence.mbarrier_init.release.cluster;" ::: "memory");
            mbar_expect_tx(bar_wq, D * 64);
            const uint32_t c0 = clock32();
            while (clock32() - c0 < WQ_DELAY) { }
#pragma unroll
            for (int r = 0; r < D; r += 160) tma2d(sb + X_WQ + r * 64, &tm_wq, 32 * cta, r, bar_wq);
        }
    } else if (threadIdx.x == 0) {
#pragma unroll
        for (int s = 0; s < NS; s++) { if (s) mbar_init(bar_full + s * 8, 1); mbar_init(bar_empty + s * 8, 4); }
        mbar_init(crit ? bar_wq : bar_wm, 1);
        mbar_init(bar_xfree, 1);
#pragma unroll
        for (int i = 0; i < 5; i++) { mbar_init(bar_wo + i * 8, 1); mbar_init(bar_w2 + i * 16, 1); mbar_init(bar_w2 + i * 16 + 8, 1); }
        mbar_init(bar_help, 1); mbar_init(bar_x1, 1);
#pragma unroll
        for (int i = 0; i < 4; i++) { mbar_init(bar_v + i * 8, 1); mbar_init(bar_w1 + i * 8, 1); mbar_init(bar_gb + i * 8, 1); }
        asm volatile("fence.mbarrier_init.release.cluster;" ::: "memory");
    }
    __syncthreads();

    if (warp == 8) {
        if (lane == 0) {
            int tp = NS;
            int sched = PACE_A - NS * PACE_TAU;
            int phase = 0;
#pragma unroll 1
            for (int t = 1; t <= NITEM; t++) {
                if (t == 1) mbar_wait(bar_full, 0);
                if (t == 2) {
                    mbar_wait(bar_first, 0);
                    if (crit) {
                        mbar_expect_tx(bar_wq, D * 64);
#pragma unroll 1
                        for (int r = 0; r < D; r += 160) tma2d(sb + X_WQ + r * 64, &tm_wq, 32 * cta, r, bar_wq);
                    }
                }
                if (t == 3) {
                    asm volatile("prefetch.tensormap [%0];" ::"l"(&tm_v) : "memory");
                    asm volatile("prefetch.tensormap [%0];" ::"l"(&tm_wo) : "memory");
                    asm volatile("prefetch.tensormap [%0];" ::"l"(&tm_w1) : "memory");
                    asm volatile("prefetch.tensormap [%0];" ::"l"(&tm_w2) : "memory");
                    asm volatile("prefetch.tensormap [%0];" ::"l"(&tm_gb) : "memory");
                }
                if (t == NS && late) {
                    mbar_wait(bar_full + (NS - INFLIGHT) * 8, 0);
                    mbar_expect_tx(bar_wm, D * 64);
#pragma unroll 1
                    for (int r = 0; r < D; r += 160) tma2d(sb + X_WM + r * 64, &tm_wmod, 32 * mc, r, bar_wm);
                }
                if (t >= NS && t < PF_END) {
                    int it = 0;
                    while (!mbar_test(bar_empty + (t & (NS - 1)) * 8, ((t >> 3) - 1) & 1)) {
                        if (tp < PF_END && (int)(gtime32() - t_start) >= PACE_A + (tp - NS) * PACE_TAU) {
                            asm volatile("cp.async.bulk.prefetch.L2.global.L2::cache_hint [%0], %1, %2;"
                                         ::"l"(((tp & 1) ? vb : kb) + (size_t)(((tp >> 1) + rot) & (NITEM / 2 - 1)) * TILE_BYTES), "r"(TILE_BYTES), "l"(pol) : "memory");
                            tp++;
                        }
                        if (++it > 16 * SPIN_LIMIT) __trap();
                    }
                    if (tp <= t) tp = t + 1;
                }
                if (t == NITEM) {
                    mbar_wait(bar_xfree, 0);
                    const uint32_t t_ref = t_start + phase + (NITEM - 1) * PACE_TAU;
#pragma unroll 1
                    for (int i = 0; i < 5; i++) {
                        while ((int)(gtime32() - t_ref) < WO_T + i * WO_S) { }
                        mbar_expect_tx(bar_wo + i * 8, DH * 64);
                        tma2d(sb + X_WO + i * (DH * 64), &tm_wo, bown * 160 + i * 32, head * DH, bar_wo + i * 8);
                    }
                    if (gb_own) {
                        mbar_wait(bar_empty + 3 * 8, ((NITEM >> 3) - 1) & 1);
                        mbar_wait(bar_x1, 0);
                        { const uint32_t c0 = clock32(); while (clock32() - c0 < GB_EV) { } }
                        while ((int)(gtime32() - t_ref) < GB_T) { }
#pragma unroll 1
                        for (int i = 0; i < 4; i++) {
                            mbar_expect_tx(bar_gb + i * 8, 160 * 16);
                            tma2d(sb + X_GB + i * (160 * 16), &tm_gb, 5 * D + 8 * own, 160 * i, bar_gb + i * 8);
                        }
                    }
                    if (is_f) {
#pragma unroll 1
                        for (int i = 0; i < 3; i++) mbar_wait(bar_empty + i * 8, ((NITEM >> 3) - 1) & 1);
                        while ((int)(gtime32() - t_ref) < W1_T) { }
#pragma unroll 1
                        for (int i = 0; i < 4; i++) {
                            mbar_expect_tx(bar_w1 + i * 8, 160 * 64);
                            tma2d(sb + X_W1 + i * (160 * 64), &tm_w1, 32 * f, 160 * i, bar_w1 + i * 8);
                        }
                        while ((int)(gtime32() - t_ref) < W2_T) { }
#pragma unroll 1
                        for (int i = 0; i < 10; i++) {
                            mbar_expect_tx(bar_w2 + i * 8, 4096);
                            tma2d(sb + X_W2 + i * 4096, &tm_w2, 64 * i, 32 * f, bar_w2 + i * 8);
                        }
                    }
                    break;
                }
                const int s = t & (NS - 1);
                if (t >= NS) {
                    mbar_wait(bar_empty + s * 8, ((t >> 3) - 1) & 1);
                    while ((int)(gtime32() - t_start) < sched + t * PACE_TAU) { }
                } else if (t >= INFLIGHT) {
                    mbar_wait(bar_full + (t - INFLIGHT) * 8, 0);
                }
                if (t < NITEM - 2) {
                    const int pair = t == NITEM - 3 ? NITEM / 2 - 1 : t >> 1;
                    mbar_expect_tx(bar_full + s * 8, TILE_BYTES);
                    bulk_load(sb + OFF_RING + s * TILE_BYTES, ((t & 1) && t != NITEM - 3 ? vb : kb) + (size_t)((pair + rot) & (NITEM / 2 - 1)) * TILE_BYTES, TILE_BYTES, bar_full + s * 8, pol);
                } else {
                    const int row = (bown * NH + head) * SK + (SK - WIN) + ((t - NITEM / 2 + rot) & (NITEM / 2 - 1)) * TILE_KEYS;
#pragma unroll 1
                    for (int i = 0; i < 2; i++) {
                        const uint32_t bar = bar_v + (2 * (t - (NITEM - 2)) + i) * 8;
                        mbar_expect_tx(bar, TILE_BYTES / 2);
                        tma2d_hint(sb + OFF_RING + s * TILE_BYTES + i * (TILE_BYTES / 2), &tm_v, 64 * i, row, bar, pol);
                    }
                }
                if (t >= PH_FIRST && (t & 7) == PH_LAG) {
                    const int now = (int)(gtime32() - t_start) - (t - PH_LAG) * PACE_TAU;
                    uint32_t ph;
                    asm volatile("atom.relaxed.gpu.global.add.u32 %0, [%1], 0;" : "=r"(ph) : "l"(g_phase + (t >> 3) * 32) : "memory");
                    phase = (int)min(((ph & 0xffffffu) * 4 + (NCTA - (ph >> 24)) * now) / NCTA, 65535u);
                    sched += (phase - LAT_T - sched) * 3 / 4;
                }
            }
        }
        __syncwarp();
    }

    if (warp == 9) {
        int side = 0;
        if (lane == 0) {
            uint32_t best[2] = {~0u, ~0u};
#pragma unroll
            for (int i = 0; i < 4; i++) stg_zero4(slot(SL_SIDE, i >> 1) + cta * 8 + (i & 1) * 4);
            uint32_t n = 0;
#pragma unroll 1
            for (int i = 0; (i & 1) || (n < NPROBE - 1 && (int)(gtime32() - t_start) < PROBE_END); i++) {
                uint32_t t0 = clock32(), t1;
                asm volatile("atom.relaxed.gpu.global.inc.u32 %0, [%1], %2;" : "=r"(n) : "l"(slot(SL_SIDE, i & 1) + cta * 8), "r"(0xffffu) : "memory");
                asm volatile("{\n.reg .pred p;\nsetp.ne.u32 p, %1, 0xffffffff;\nmov.u32 %0, 0;\n@p mov.u32 %0, %%clock;\n}" : "=r"(t1) : "r"(n) : "memory");
                if (i & 1) best[1] = min(best[1], t1 - t0); else best[0] = min(best[0], t1 - t0);
            }
            side = best[1] < best[0];
        }
        side = __shfl_sync(0xffffffffu, side, 0);
        HPROF(1);
        mbar_wait(bar_full + (NS - 1) * 8, 0);
        stg_zero4(slot(SL_O + (cta >> 4), lane >> 4) + (cta & 15) * 64 + (lane & 15) * 4);
        if (is_owner) {
#pragma unroll 1
            for (int i = lane; i < NH * 8; i += 32) stg_zero4(slot(SL_P1 + own, side) + i * 4);
#pragma unroll 1
            for (int i = lane; i < NF * 4; i += 32) stg_zero4(slot(SL_P2 + 2 * own + (i >> 7), side) + ((i >> 2) & 31) * 32 + (i & 3) * 4);
            if (lane < 8) stg_zero4(slot(SL_X1 + own / 30, lane >> 2) + (own % 30) * 32 + (lane & 3) * 4);
        }
        __threadfence();
        __syncwarp();
        if (lane == 0) stg_relaxed(g_clr + cta, 1u + side);
        HPROF(0);
        while ((int)(gtime32() - t_start) < CLR_CHECK) __nanosleep(1000);
        mbar_wait(bar_xfree, 0);
        {
            uint4 v = make_uint4(1, 1, 1, 1), gv = v, mv[20];
#pragma unroll
            for (int i = 0; i < 20; i++) mv[i] = v;
#pragma unroll 1
            for (int it = 0;; it++) {
                v = ldg_relaxed(g_clr + lane * 4);

                ldg_relaxed_if(is_owner && lane < (gb_own ? 4 : 8), gv, mod_slot(lane < 4 ? 2 : 5, own, lane & 3));
#pragma unroll
                for (int i = 0; i < 20; i++) ldg_relaxed_if(is_f, mv[i], mod_slot(3, 8 * i + (lane >> 2), lane & 3));
                bool ok = ready(v) && ready(gv);
#pragma unroll
                for (int i = 0; i < 20; i++) ok = ok && ready(mv[i]);
                if (__all_sync(0xffffffffu, ok)) break;
                if (it > SPIN_LIMIT) __trap();
                __nanosleep(2000);
            }
            const uint32_t w[4] = {v.x, v.y, v.z, v.w};
#pragma unroll
            for (int i = 0; i < 4; i++) {
                const Roles r = roles(4 * lane + i);
                if (r.is_owner) {
                    sts32(sb + OFF_TAB1 + r.own * 4, (uint32_t)(size_t)(slot(SL_P1 + r.own, w[i] - 1) + head * 32));
                    sts32(sb + OFF_TAB2 + r.own * 4, (uint32_t)(size_t)(slot(SL_P2 + 2 * r.own + (f >> 5), w[i] - 1) + (f & 31) * 32));
                }
            }
            if (lane == 0) sts32(sb + OFF_SIDE, side);
            if (lane < 8) sts128(sb + OWN_GA + lane * 16, inv4(gv));
            const uint32_t dst = sb + OFF_VB + (lane & 3) * VEC_STRIDE + (lane >> 2) * 16;
#pragma unroll
            for (int i = 0; i < 10; i++) {
                const uint4 c = inv4(mv[10 + i]);
                sts128(dst + i * 128, make_uint4(bf2_add(c.x, 0x3f803f80u), bf2_add(c.y, 0x3f803f80u), bf2_add(c.z, 0x3f803f80u), bf2_add(c.w, 0x3f803f80u)));
                sts128(dst + (OFF_RED - OFF_VB) + i * 128, inv4(mv[i]));
            }
        }
        asm volatile("fence.acq_rel.gpu;" ::: "memory");
        __syncwarp();
        HPROF(3);
        if (lane == 0) mbar_arrive(bar_help);
        {
            const uint32_t* const src = pin(slot(SL_O + (cta >> 4), side) + (cta & 12) * 64 + lane * 4);
            const uint32_t dst = pin(sb + OFF_O + (lane >> 4) * O_STRIDE + (lane & 15) * 16);
            mbar_wait(bar_v + 16, 0);
            mbar_wait(bar_v + 24, 0);
            uint4 v[2];
            const uint32_t* const ptr[2] = {src, src + 128};
            const bool on[2] = {true, true};
            poll_n<2>(v, ptr, on);
            sts128(dst, v[0]);
            sts128(dst + 2 * O_STRIDE, v[1]);
#pragma unroll
            for (int w = 0; w < 8; w++) asm volatile("bar.arrive %0, 64;" ::"r"(NB_O + w) : "memory");
        }
        HPROF(4);
    }
    if (warp >= 8) {
        if (gb_own && warp == 9) {
            uint32_t a[20][4];
#pragma unroll
            for (int i = 0; i < 20; i++) ldsm4(a[i], sb + OFF_VA + (lane & 3) * VEC_STRIDE + (4 * i + (lane >> 3)) * 16);
            float c[4][4];
#pragma unroll
            for (int i = 0; i < 4; i++) c[i][0] = c[i][1] = c[i][2] = c[i][3] = 0.f;
#pragma unroll
            for (int bx = 0; bx < 4; bx++) {
                mbar_wait(bar_gb + bx * 8, 0);
#pragma unroll
                for (int i = 5 * bx; i < 5 * bx + 5; i++) {
                    uint32_t w[4];
                    ldsm4t(w, sb + X_GB + (32 * i + lane) * 16);
                    const uint32_t a0[4] = {a[i][0], 0u, a[i][1], 0u}, a1[4] = {a[i][2], 0u, a[i][3], 0u};
                    mma16816(c[(2 * i) & 3], a0, w[0], w[1]);
                    mma16816(c[(2 * i + 1) & 3], a1, w[2], w[3]);
                }
            }
            if (lane < 16) sts32(sb + OWN_GB + lane * 4, pack_bf((c[0][0] + c[1][0]) + (c[2][0] + c[3][0]), (c[0][1] + c[1][1]) + (c[2][1] + c[3][1])));
            HPROF(6);
        }
        if (is_owner && warp == 9) nbar_arrive<NB_E6, 288>();
        if (is_f) gelu_stage(sb, warp - 8, lane);
        return;
    }

    const int g = lane >> 2, t4 = lane & 3;
    const int mi = lane >> 3, r8 = lane & 7;

    {
        auto silu4 = [&](const uint4& cv) {
            uint32_t w4[4] = {cv.x, cv.y, cv.z, cv.w};
#pragma unroll
            for (int e = 0; e < 4; e++) {
                float c0 = bf_lo(w4[e]), c1 = bf_hi(w4[e]);
                w4[e] = pack_bf(c0 * rcp_fast(1.f + ex2(-1.4426950408889634f * c0)), c1 * rcp_fast(1.f + ex2(-1.4426950408889634f * c1)));
            }
            return make_uint4(w4[0], w4[1], w4[2], w4[3]);
        };
        {
            uint4 v = silu4(ca0);
            sts128(sb + OFF_VA + (tid / 80) * VEC_STRIDE + (tid % 80) * 16, v);
            if (tid < 64) { v = silu4(ca1); sts128(sb + OFF_VA + 3 * VEC_STRIDE + (16 + tid) * 16, v); }
        }
        if (warp < 4) {
            float s = 0.f, q = 0.f;
            const float pv = __shfl_sync(0xffffffffu, bf_lo(xs[0].x), 0);
#pragma unroll
            for (int i = 0; i < 3; i++) if (i < 2 || lane < 16) acc_stats(xs[i], pv, s, q);
#pragma unroll
            for (int of = 16; of > 0; of >>= 1) { s += __shfl_xor_sync(0xffffffffu, s, of); q += __shfl_xor_sync(0xffffffffu, q, of); }
            uint32_t m2; float rden;
            ln_finish(pv, s, q, m2, rden);
            if (lane == 0) { sts32(sb + OFF_STAT + warp * 8, m2); sts_f32(sb + OFF_STAT + warp * 8 + 4, rden); }
        } else if (warp == 4) {
            sts32(sb + OWN_X + lane * 4, bf2_add(own0, 0u));
            sts_f32(sb + OWN_B1 + lane * 4, bf2f(own2));
        }
    }
    bar_cons();
    PROF(24);
    uint32_t qf[8][2];
    float o[8][4];
#pragma unroll
    for (int c = 0; c < 8; c++) { o[c][0] = o[c][1] = o[c][2] = o[c][3] = 0.f; }
    float m_run = -INFINITY, l_run = 0.f;
    const bool diag = (t4 == (g >> 1));
    const bool odd = g & 1;
    const uint32_t koff = (warp & 3) * 4096 + (r8 + 8 * (mi & 1)) * 256 + (mi >> 1) * 128 + (r8 << 4);
    const uint32_t voff = TILE_BYTES + (warp & 3) * 4096 + (r8 + 8 * (mi >> 1)) * 256 + (mi & 1) * 128 + (r8 << 4);
    const int src0 = (2 * t4) * 4 + t4, src1 = (2 * t4 + 1) * 4 + t4;
#pragma unroll 1
    for (int step = crit ? 0 : 1; step < 3; step++) {
        if (step < 2 || late) {
            if (step == 1) {
                if (!crit) mbar_wait(bar_wq, 0);
                const uint32_t m2 = lds32(sb + OFF_STAT + (tid & 3) * 8);
                const float rden = lds_f32(sb + OFF_STAT + (tid & 3) * 8 + 4);
                uint4 v[4];
                v[2] = v[3] = make_uint4(1, 1, 1, 1);
                const uint32_t* const p0 = mod_slot(0, tid >> 2, tid & 3);
                while ((int)(gtime32() - t_start) < MOD_T) { }
                PROF(2);
#pragma unroll 1
                for (int it = 0;; it++) {
                    ldg_relaxed_if(tid < 64, v[2], p0 + 16 * 64);
                    ldg_relaxed_if(tid < 64, v[3], p0 + 36 * 64);
                    v[0] = ldg_relaxed(p0);
                    v[1] = ldg_relaxed(p0 + 20 * 64);
                    if (__all_sync(0xffffffffu, min(min(min4(v[0]), min4(v[1])), min(min4(v[2]), min4(v[3]))) != 0u)) break;
                    if (it > SPIN_LIMIT) __trap();
                }
#pragma unroll
                for (int i = 0; i < 4; i++) v[i] = inv4(v[i]);
                PROF(3);
                uint4 h0 = ln_mod4(xa, v[1], v[0], m2, rden);
                sts128(sb + OFF_VB + (tid & 3) * VEC_STRIDE + (tid >> 2) * 16, h0);
                if (tid < 64) {
                    h0 = ln_mod4(xb, v[3], v[2], m2, rden);
                    sts128(sb + OFF_VB + (tid & 3) * VEC_STRIDE + (64 + (tid >> 2)) * 16, h0);
                }
            }
            mbar_wait(step == 1 ? bar_wq : bar_wm, 0);
            bar_cons();
            const uint32_t strip = sb + (step == 1 ? X_WQ : X_WM), vec = sb + (step == 1 ? OFF_VB : OFF_VA);
            float acc[2][4];
#pragma unroll
            for (int m = 0; m < 2; m++) { acc[m][0] = acc[m][1] = acc[m][2] = acc[m][3] = 0.f; }
#pragma unroll
            for (int i = 0; i < 5; i++) {
                int k0 = (warp * 5 + i) * 16;
                uint32_t b0, b1;
                load_bfrag(vec, VEC_STRIDE, k0, g, t4, b0, b1);
                int krow = k0 + r8 + 8 * (mi >> 1);
#pragma unroll
                for (int m = 0; m < 2; m++) {
                    uint32_t a[4];
                    int ch = 2 * m + (mi & 1);
                    ldsm4t(a, strip + krow * 64 + ((ch ^ ((krow >> 1) & 3)) << 4));
                    mma16816(acc[m], a, b0, b1);
                }
            }
            if (t4 < 2) {
#pragma unroll
                for (int m = 0; m < 2; m++) {
                    sts_f32x2(sb + OFF_RED + ((warp * 32 + m * 16 + g) * 4 + 2 * t4) * 4, acc[m][0], acc[m][1]);
                    sts_f32x2(sb + OFF_RED + ((warp * 32 + m * 16 + g + 8) * 4 + 2 * t4) * 4, acc[m][2], acc[m][3]);
                }
            }
            bar_cons();
            if (tid < 64) {
                float v0 = 0.f, v1 = 0.f;
#pragma unroll
                for (int w = 0; w < 8; w++) {
                    v0 += lds_f32(sb + OFF_RED + (w * 128 + (tid & 15) * 8 + (tid >> 4)) * 4);
                    v1 += lds_f32(sb + OFF_RED + (w * 128 + (tid & 15) * 8 + 4 + (tid >> 4)) * 4);
                }
                stg_relaxed(step == 1 ? g_q + (((cta & ~3) + (tid >> 4)) * 4 + bown) * 32 + (tid & 15) : g_mod + mc * 64 + tid, ~pack_bf(v0, v1));
            }
        }
        if (step == 0) continue;
        if (step == 1) {
            if (warp == 0) {
                { const uint32_t c0 = clock32(); while (clock32() - c0 < Q_PAUSE) { } }
                uint4 v = poll1(g_q + (cta * 4 + ((lane >> 2) & 3)) * 32 + (lane & 3) * 4, lane < 16);
                if (lane < 16) {
                    sts128(sb + OFF_Q + lane * 16, v);
                    stg_zero4(g_q + (cta * 4 + (lane >> 2)) * 32 + (lane & 3) * 4);
                }
            }
            bar_cons();
            PROF(4);

#pragma unroll
            for (int c = 0; c < 8; c++) {
                qf[c][0] = lds32(sb + OFF_Q + (((c ^ g) * 4 + t4) << 2));
                qf[c][1] = lds32(sb + OFF_Q + 128 + (((c ^ g) * 4 + t4) << 2));
            }
        } else {
            bar_cons();
            if (tid == 0) mbar_arrive(bar_xfree);
        }
#pragma unroll 1
        for (int j = (step == 1 ? 0 : SEG_J) + (warp >> 2); j < (step == 1 ? SEG_J : NITEM / 2 - 2); j += 2) {
            const int s = (2 * j) & (NS - 1);
            const uint32_t par = (j >> 2) & 1;
            mbar_wait(bar_full + s * 8, par);
            if (tid == 0 && 2 * j >= PH_FIRST && (j & 3) == 0) {
                const int x = min(max((int)(gtime32() - t_start) - 2 * j * PACE_TAU, 0), 65535);
                asm volatile("red.relaxed.gpu.global.add.u32 [%0], %1;" ::"l"(g_phase + (j >> 2) * 32), "r"((1u << 24) + (x >> 2)) : "memory");
            }
            const uint32_t base = sb + OFF_RING + s * TILE_BYTES;
            float sa[4] = {0.f, 0.f, 0.f, 0.f}, sb2[4] = {0.f, 0.f, 0.f, 0.f};
#pragma unroll
            for (int c = 0; c < 8; c += 2) {
                uint32_t a[4], a2[4];
                ldsm4(a, (base + koff) ^ (c << 4));
                ldsm4(a2, (base + koff) ^ ((c + 1) << 4));
                mma16816(sa, a, qf[c][0], qf[c][1]);
                mma16816(sb2, a2, qf[c + 1][0], qf[c + 1][1]);
            }
            const uint32_t sw = pack_bf(odd ? sa[1] + sb2[1] : sa[0] + sb2[0], odd ? sa[3] + sb2[3] : sa[2] + sb2[2]);
            const uint32_t sv = pack_bf(bf_lo(sw) * 0.08838834764831845f, bf_hi(sw) * 0.08838834764831845f);
            const float s0 = bf_lo(sv) * 1.4426950408889634f, s1 = bf_hi(sv) * 1.4426950408889634f;
            float m_new = fmaxf(m_run, fmaxf(s0, s1));
            const bool grow = __any_sync(0xffffffffu, (diag && (m_new > m_run)));
            if (lane == 0) mbar_arrive(bar_empty + s * 8);
            if (grow) {
                float al = ex2(m_run - m_new);
                float a0 = __shfl_sync(0xffffffffu, al, src0), a1 = __shfl_sync(0xffffffffu, al, src1);
#pragma unroll
                for (int c = 0; c < 8; c++) { o[c][0] *= a0; o[c][1] *= a1; o[c][2] *= a0; o[c][3] *= a1; }
                l_run *= al;
                m_run = m_new;
            }
            uint32_t pw = pack_bf(ex2(s0 - m_run), ex2(s1 - m_run));
            l_run += bf_lo(pw) + bf_hi(pw);
            uint32_t b0 = odd ? (pw << 16) : (pw & 0xffffu);
            uint32_t b1 = odd ? (pw & 0xffff0000u) : (pw >> 16);
            if (!diag) { b0 = 0u; b1 = 0u; }
            mbar_wait(bar_full + (s + 1) * 8, par);
#pragma unroll
            for (int c = 0; c < 8; c++) {
                uint32_t a[4];
                ldsm4t(a, (base + voff) ^ (c << 4));
                mma16816(o[c], a, b0, b1);
            }
            __syncwarp();
            if (lane == 0) mbar_arrive(bar_empty + (s + 1) * 8);
        }
    }
    PROF(5);
    float acc[4][4];
    uint32_t pa[8][2];
    float rinv;
    {
        const int s = 4 + (warp >> 2);
        mbar_wait(bar_full + s * 8, 1);
        const uint32_t base = sb + OFF_RING + s * TILE_BYTES;
        float sa[4] = {0.f, 0.f, 0.f, 0.f}, sb2[4] = {0.f, 0.f, 0.f, 0.f};
#pragma unroll
        for (int c = 0; c < 8; c += 2) {
            uint32_t a[4], a2[4];
            ldsm4(a, (base + koff) ^ (c << 4));
            ldsm4(a2, (base + koff) ^ ((c + 1) << 4));
            mma16816(sa, a, qf[c][0], qf[c][1]);
            mma16816(sb2, a2, qf[c + 1][0], qf[c + 1][1]);
        }
        const uint32_t sw = pack_bf(odd ? sa[1] + sb2[1] : sa[0] + sb2[0], odd ? sa[3] + sb2[3] : sa[2] + sb2[2]);
        const uint32_t sv = pack_bf(bf_lo(sw) * 0.08838834764831845f, bf_hi(sw) * 0.08838834764831845f);
        const float s0 = bf_lo(sv) * 1.4426950408889634f, s1 = bf_hi(sv) * 1.4426950408889634f;
        int mi_ = __float_as_int(diag ? fmaxf(m_run, fmaxf(s0, s1)) : -INFINITY);
        mi_ ^= (mi_ >> 31) & 0x7fffffff;
        mi_ = __reduce_max_sync(0xffffffffu, mi_);
        mi_ ^= (mi_ >> 31) & 0x7fffffff;
        if (lane == 0) sts32(sb + OFF_ML + warp * 4, mi_);
        bar_cons();
        const float4 m0 = lds_f32x4(sb + OFF_ML), m1 = lds_f32x4(sb + OFF_ML + 16);
        const float mx = fmaxf(fmaxf(fmaxf(m0.x, m0.y), fmaxf(m0.z, m0.w)), fmaxf(fmaxf(m1.x, m1.y), fmaxf(m1.z, m1.w)));
        const float scl = ex2(m_run - mx);
        const uint32_t pw = pack_bf(ex2(s0 - mx), ex2(s1 - mx));
        if (diag) { sts16(sb + SC_P + (warp * 16 + g) * 2, pw); sts16(sb + SC_P + (warp * 16 + g + 8) * 2, pw >> 16); }
        const float lw = warp_sum(diag ? fmaf(l_run, scl, bf_lo(pw) + bf_hi(pw)) : 0.f);
        const float a0 = __shfl_sync(0xffffffffu, scl, src0), a1 = __shfl_sync(0xffffffffu, scl, src1);
        float v[8], u[8];
#pragma unroll
        for (int c = 0; c < 8; c++) {
            v[c] = a0 * o[c][0] + a1 * o[c ^ 1][1];
            u[c] = a0 * o[c][2] + a1 * o[c ^ 1][3];
        }
#pragma unroll
        for (int c = 0; c < 8; c++) {
            if (!(c & 2)) {
                v[c] += __shfl_xor_sync(0xffffffffu, v[c ^ 2], 1);
                u[c] += __shfl_xor_sync(0xffffffffu, u[c ^ 2], 1);
            }
        }
#pragma unroll
        for (int c = 0; c < 2; c++) {
            v[c] += __shfl_xor_sync(0xffffffffu, v[c ^ 4], 2);
            u[c] += __shfl_xor_sync(0xffffffffu, u[c ^ 4], 2);
        }
        const uint32_t dst = sb + SC_OP + (warp * 128 + 16 * t4 + g) * 4;
        sts_f32(dst, v[0]); sts_f32(dst + 32, v[1]); sts_f32(dst + 256, u[0]); sts_f32(dst + 288, u[1]);
        if (lane == 0) sts_f32(sb + OFF_ML + 32 + warp * 4, lw);
        mbar_wait(bar_help, 0);
        bar_cons();
        const float4 l0 = lds_f32x4(sb + OFF_ML + 32), l1 = lds_f32x4(sb + OFF_ML + 48);
        rinv = rcp_fast(((l0.x + l0.y) + (l0.z + l0.w)) + ((l1.x + l1.y) + (l1.z + l1.w)));
#pragma unroll
        for (int i = 0; i < 4; i++) acc[i][0] = acc[i][1] = acc[i][2] = acc[i][3] = 0.f;
#pragma unroll
        for (int w = 0; w < 8; w++) {
            const float2 x0 = lds_f32x2(sb + SC_OP + (w * 128 + 16 * warp + 2 * t4) * 4), x1 = lds_f32x2(sb + SC_OP + (w * 128 + 16 * warp + 8 + 2 * t4) * 4);
            acc[2 * (w & 1)][0] += x0.x; acc[2 * (w & 1)][1] += x0.y;
            acc[2 * (w & 1) + 1][0] += x1.x; acc[2 * (w & 1) + 1][1] += x1.y;
        }
#pragma unroll
        for (int ks = 0; ks < 8; ks++) { pa[ks][0] = lds32(sb + SC_P + (8 * ks + t4) * 4); pa[ks][1] = lds32(sb + SC_P + (8 * ks + 4 + t4) * 4); }
    }
    PROF(20);
    const int mt = warp < 2 ? warp : warp + 2;
    {
        const uint32_t va = pin(sb + OFF_RING + 6 * TILE_BYTES + (warp >> 2) * (TILE_BYTES / 2) + (8 * (mi & 1) + r8) * 128 + (((2 * (warp & 3) + (mi >> 1)) ^ r8) << 4));
        const uint32_t vbar = pin(bar_v + (warp >> 2) * 8);
        uint32_t* const o_dst = pin(slot(SL_O + (cta >> 4), g) + (cta & 15) * 64 + warp * 8 + 2 * t4);
#pragma unroll
        for (int tl = 0; tl < 2; tl++) {
            mbar_wait(vbar + tl * 16, 0);
            uint32_t r[4][4];
#pragma unroll
            for (int ks = 0; ks < 4; ks++) ldsm4t(r[ks], va + tl * TILE_BYTES + ks * 2048);
#pragma unroll
            for (int ks = 0; ks < 4; ks++) {
                const uint32_t a[4] = {pa[4 * tl + ks][0], 0u, pa[4 * tl + ks][1], 0u};
                mma16816(acc[2 * (ks & 1)], a, r[ks][0], r[ks][1]);
                mma16816(acc[2 * (ks & 1) + 1], a, r[ks][2], r[ks][3]);
            }
        }
        stg_relaxed2_if(g < 2, o_dst, ~pack_bf((acc[0][0] + acc[2][0]) * rinv, (acc[0][1] + acc[2][1]) * rinv),
                        ~pack_bf((acc[1][0] + acc[3][0]) * rinv, (acc[1][1] + acc[3][1]) * rinv));
    }
    PROF(7);
    const int side = lds32(sb + OFF_SIDE);
    const uint32_t red_st = pin(sb + SC_E4 + ((warp * 4 + 2 * ((lane >> 3) & 1) + (lane >> 4)) * 8 + (lane & 7)) * 4);
    const uint32_t red_ld = pin(sb + SC_E4 + (lane & 15) * 8);
    const uint32_t* const in1 = pin(slot(SL_P1 + own, side) + tid * 4);
    const uint32_t* const in2a = pin(slot(SL_P2 + 2 * own, side) + (tid >> 3) * 32 + (tid & 7) * 2);
    const uint32_t* const in2b = pin(slot(SL_P2 + 2 * own + 1, side) + (tid >> 3) * 32 + (tid & 7) * 2);
    uint32_t* const out_dst = pin((uint32_t*)(p.out + ((lane >> 2) & 3) * D + 8 * own) + t4);
    uint32_t* const x1_dst = pin(slot(SL_X1 + own / 30, lane >> 4) + (own % 30) * 32 + (lane & 15));
    uint32_t* const rst = pin(tid >= 32 && tid < 56 ? mod_slot(lane >> 2, own, lane & 3) : own < 32 && tid == 64 ? g_clr + own * 4 : own < 8 && tid == 96 ? g_phase + own * 32 : nullptr);
    const uint32_t xw = lds32(sb + OWN_X + (lane & 15) * 4), ga_w = lds32(sb + OWN_GA + (lane & 15) * 4);
    uint32_t cs[15];
    uint32_t* dst2[5];
    uint32_t w2a[5];
#pragma unroll
    for (int j = 0; j < 10; j++) cs[j] = lds32(sb + OFF_VB + ((g & 1) * 4 + (g >> 1)) * VEC_STRIDE + warp * 160 + t4 * 4 + j * 16);
#pragma unroll
    for (int i = 0; i < 5; i++) {
        cs[10 + i] = lds32(sb + OFF_VB + (g >> 1) * VEC_STRIDE + warp * 160 + (g & 1) * 16 + t4 * 4 + i * 32);
        const uint2 t = lds64(sb + OFF_TAB2 + warp * 40 + i * 8);
        dst2[i] = slot_ptr((t4 < 2 ? t.x : t.y) + g * 8 + (t4 & 1) * 4);
        const int cc = 2 * (warp * 5 + i) + (mi & 1);
        w2a[i] = pin(sb + X_W2 + (cc >> 3) * 4096 + (r8 + 8 * (mi >> 1)) * 128 + (((cc & 7) ^ r8) << 4));
    }
    const uint32_t piv = lds32(sb + OFF_STAT + (g >> 1) * 8);
    const uint32_t* const xin = pin(slot(SL_X1 + warp / 3, side) + ((warp % 3) * 10 + (g & 1)) * 32 + (g >> 1) * 4 + t4);
    const uint32_t w1a = pin(sb + X_W1 + (warp * 80 + r8 + 8 * (mi >> 1)) * 64 + (((mi & 1) ^ ((r8 >> 1) & 3)) << 4));
    const uint32_t w1bar = pin(bar_w1 + (warp >> 1) * 8), w2bar = pin(bar_w2 + (warp + (warp >> 2)) * 8);
    const uint32_t obar = pin(NB_O + warp), hbar = pin((NB_H1 + (warp >> 1)) & 15);
    const uint32_t ab_st = pin(sb + SC_AB + warp * 1024 + lane * 16), y_st = pin(sb + SC_Y + warp * 512 + lane * 8), s_st = pin(sb + SC_ST + (t4 * 8 + warp) * 8);
    const uint32_t h_ld = pin(sb + SC_H1 + ((g & 3) ^ (2 * (f & 1) + ((f >> 1) & 1))) * 64 + t4 * 16);
    {
        const int kap = 2 * (head & 1) + ((head >> 1) & 1);
        const uint32_t wa = pin(sb + X_WO + (mt >> 1) * (DH * 64) + (r8 + 8 * (mi >> 1)) * 64 + ((((mt & 1) * 2 + (mi & 1)) ^ ((r8 >> 1) & 3)) << 4));
        const uint32_t oa = pin(sb + OFF_O + ((g & 3) ^ kap) * O_STRIDE + t4 * 8);
        uint32_t* dst[4];
#pragma unroll
        for (int i = 0; i < 2; i++) {
            const uint2 t = lds64(sb + OFF_TAB1 + (bown * 20 + 2 * mt + (warp < 2 ? 4 * i : 0)) * 4);
            dst[2 * i] = slot_ptr(t.x + g * 16 + t4 * 8);
            dst[2 * i + 1] = slot_ptr(t.y + g * 16 + t4 * 8);
        }
        PROF(6);
        const uint32_t wobar = pin(bar_wo + (mt >> 1) * 8);
        asm volatile("bar.sync %0, 64;" ::"r"(obar) : "memory");
        uint2 ob[8];
#pragma unroll
        for (int ks = 0; ks < 8; ks++) ob[ks] = lds64(oa + ks * 32);
#pragma unroll
        for (int m = 0; m < 2; m++) {
            if (m == 0 || warp < 2) {
                mbar_wait(wobar + m * 8, 0);
                PROF(8);
                uint32_t wf[8][4];
#pragma unroll
                for (int ks = 0; ks < 8; ks++) ldsm4t(wf[ks], wa + m * (DH * 64) + ks * 1024);
                float c[4][4];
#pragma unroll
                for (int ks = 0; ks < 8; ks++) {
                    if (ks < 4) c[ks][0] = c[ks][1] = c[ks][2] = c[ks][3] = 0.f;
                    mma16816(c[ks & 3], wf[ks], ob[ks].x, ob[ks].y);
                }
                stg_relaxed2_if(t4 < 2, dst[2 * m], flag((c[0][0] + c[1][0]) + (c[2][0] + c[3][0])), flag((c[0][1] + c[1][1]) + (c[2][1] + c[3][1])));
                stg_relaxed2_if(t4 < 2, dst[2 * m + 1], flag((c[0][2] + c[1][2]) + (c[2][2] + c[3][2])), flag((c[0][3] + c[1][3]) + (c[2][3] + c[3][3])));
            }
        }
    }
    PROF(9);
    uint32_t x1w = 0;
    if (is_owner) {
        sts_f32(red_st, poll_e4(in1));
        PROF(11);
        nbar_sync<NB_E4, 256>();
        if (warp == 0) {
            float2 a[8];
#pragma unroll
            for (int w = 0; w < 8; w++) a[w] = lds_f32x2(red_ld + w * 128);
            const uint32_t aw = pack_bf(((a[0].x + a[1].x) + (a[2].x + a[3].x)) + ((a[4].x + a[5].x) + (a[6].x + a[7].x)),
                                        ((a[0].y + a[1].y) + (a[2].y + a[3].y)) + ((a[4].y + a[5].y) + (a[6].y + a[7].y)));
            x1w = bf2_add(xw, bf2_mul(ga_w, aw));
            stg_relaxed(x1_dst, x1w ^ 0x80008000u);
            if (lane == 0) mbar_arrive(bar_x1);
        }
        if (rst) stg_zero4(rst);
    }
    PROF(12);
    if (is_f) {
        uint32_t f1[5][2][4], f2[5][2][4];
        uint32_t d[6];
        auto load_x1 = [&] {
#pragma unroll
            for (int i = 0; i < 5; i++) d[i] = ldg_relaxed32(xin + i * 64);
        };
        auto have_x1 = [&] { return __all_sync(0xffffffffu, __vimin3_u32(__vimin3_u32(d[0], d[1], d[2]), d[3], d[4]) != 0u); };
        mbar_wait(w1bar, 0);
        load_x1();
        {
#pragma unroll
            for (int i = 0; i < 5; i++) { ldsm4t(f1[i][0], w1a + i * 1024); ldsm4t(f1[i][1], (w1a ^ 32) + i * 1024); }
            float c[2][4];
#pragma unroll
            for (int m = 0; m < 2; m++) c[m][0] = c[m][1] = c[m][2] = c[m][3] = 0.f;
#pragma unroll
            for (int i = 0; i < 5; i++) { mma16816(c[0], f1[i][0], cs[2 * i], cs[2 * i + 1]); mma16816(c[1], f1[i][1], cs[2 * i], cs[2 * i + 1]); }
#pragma unroll
            for (int i = 0; i < 5; i++) { cs[2 * i] = pin(odd ? 0u : cs[10 + i]); cs[2 * i + 1] = pin(odd ? cs[10 + i] : 0u); }
#pragma unroll
            for (int m = 0; m < 2; m++) sts128(ab_st + m * 512, make_uint4(__float_as_uint(c[m][0]), __float_as_uint(c[m][1]), __float_as_uint(c[m][2]), __float_as_uint(c[m][3])));
            nbar_arrive<NB_AB, 320>();
            d[0] |= __float_as_uint(c[1][3]) & (side >> 1);
        }
        PROF(10);
        if (!have_x1()) {
            asm volatile("{\n.reg .pred q;\n.reg .b32 t, n;\nmov.u32 n, 0;\n"
                         "L_%=:\nld.relaxed.gpu.global.u32 %0, [%5];\nld.relaxed.gpu.global.u32 %1, [%5 + 256];\nld.relaxed.gpu.global.u32 %2, [%5 + 512];\n"
                         "ld.relaxed.gpu.global.u32 %3, [%5 + 768];\nld.relaxed.gpu.global.u32 %4, [%5 + 1024];\n"
                         "add.u32 n, n, 1;\nsetp.gt.u32 q, n, %6;\n@q trap;\nbar.warp.sync 0xffffffff;\n"
                         "min.u32 t, %0, %1;\nmin.u32 t, t, %2;\nmin.u32 t, t, %3;\nmin.u32 t, t, %4;\n"
                         "setp.ne.u32 q, t, 0;\nvote.sync.all.pred q, q, 0xffffffff;\n@!q bra.uni L_%=;\n}"
                         : "=&r"(d[0]), "=&r"(d[1]), "=&r"(d[2]), "=&r"(d[3]), "=&r"(d[4]) : "l"(xin), "n"(SPIN_LIMIT) : "memory");
        }
        PROF(13);
        {
            float y[2][4], st[4] = {0.f, 0.f, 0.f, 0.f};
            float z[2][4] = {};
#pragma unroll
            for (int m = 0; m < 2; m++) y[m][0] = y[m][1] = y[m][2] = y[m][3] = 0.f;
#pragma unroll
            for (int i = 0; i < 5; i++) d[i] = bf2_add(d[i], piv);
            d[5] = 0u;
#pragma unroll
            for (int i = 0; i < 5; i++) {
                if (i < 3) {
                    const uint32_t a[4] = {d[2 * i], 0x3f803f80u, d[2 * i + 1], 0x3f803f80u};
                    mma16816(st, a, d[2 * i], d[2 * i + 1]);
                }
                const uint32_t y0 = bf2_mul(d[i], cs[2 * i]), y1 = bf2_mul(d[i], cs[2 * i + 1]);
                if (i & 1) { mma16816(z[0], f1[i][0], y0, y1); mma16816(z[1], f1[i][1], y0, y1); }
                else { mma16816(y[0], f1[i][0], y0, y1); mma16816(y[1], f1[i][1], y0, y1); }
            }
            const float q = odd ? st[1] : st[0];
            const float q2 = q + __shfl_xor_sync(0xffffffffu, q, 4);
            if (diag && !odd) sts_f32x2(s_st, q2, st[2] + st[3]);
#pragma unroll
            for (int m = 0; m < 2; m++) sts_f32x2(y_st + m * 256, (z[m][0] + z[m][1]) + (y[m][0] + y[m][1]), (z[m][2] + z[m][3]) + (y[m][2] + y[m][3]));
        }
        nbar_arrive<NB_Y, 320>();
        PROF(14);
        mbar_wait(w2bar, 0);
        mbar_wait(w2bar + 8, 0);
#pragma unroll
        for (int i = 0; i < 5; i++) { ldsm4t(f2[i][0], w2a[i]); ldsm4t(f2[i][1], w2a[i] + 2048); }
        asm volatile("bar.sync %0, 128;" ::"r"(hbar) : "memory");
        PROF(15);
        {
            const uint4 hb = lds128(h_ld);
            float c[5][4];
#pragma unroll
            for (int i = 0; i < 5; i++) { c[i][0] = c[i][1] = c[i][2] = c[i][3] = 0.f; mma16816(c[i], f2[i][0], hb.x, hb.y); }
#pragma unroll
            for (int i = 0; i < 5; i++) {
                mma16816(c[i], f2[i][1], hb.z, hb.w);
                stg_relaxed(dst2[i], ~pack_bf(t4 < 2 ? c[i][0] : c[i][2], t4 < 2 ? c[i][1] : c[i][3]));
            }
        }
    }
    PROF(16);
    if (is_owner) {
        const uint32_t b2w = lds32(sb + OWN_B2 + (lane & 15) * 4), gb_ld = pin(sb + OWN_GB + (lane & 15) * 4);
        sts_f32(red_st + (SC_E6 - SC_E4), poll_e6(in2a, in2b, tid < NF * 8 - 256));
        PROF(17);
        if (warp != 0) {
            nbar_arrive<NB_E6, 288>();
        } else {
            nbar_sync<NB_E6, 288>();
            float2 a[8];
#pragma unroll
            for (int i = 0; i < 8; i++) a[i] = lds_f32x2(red_ld + (SC_E6 - SC_E4) + i * 128);
            const uint32_t gb_w = lds32(gb_ld);
            const uint32_t aw = pack_bf(((a[0].x + a[1].x) + (a[2].x + a[3].x)) + ((a[4].x + a[5].x) + (a[6].x + a[7].x)),
                                        ((a[0].y + a[1].y) + (a[2].y + a[3].y)) + ((a[4].y + a[5].y) + (a[6].y + a[7].y)));
            x1w = bf2_add(x1w, bf2_mul(gb_w, bf2_add(aw, b2w)));
            if (lane < 16) asm volatile("st.global.u32 [%0], %1;" ::"l"(out_dst), "r"(x1w) : "memory");
        }
    }
    PROF(18);
    PROF_DUMP;
}

typedef CUresult (*EncodeFn)(CUtensorMap*, CUtensorMapDataType, cuuint32_t, void*, const cuuint64_t*, const cuuint64_t*, const cuuint32_t*,
                             const cuuint32_t*, CUtensorMapInterleave, CUtensorMapSwizzle, CUtensorMapL2promotion, CUtensorMapFloatOOBfill);

static CUtensorMap make_map(EncodeFn enc, const void* ptr, int cols, int rows, int box_cols, int box_rows, CUtensorMapSwizzle sw,
                            CUtensorMapL2promotion promo = CU_TENSOR_MAP_L2_PROMOTION_NONE) {
    CUtensorMap m;
    cuuint64_t dims[2] = {(cuuint64_t)cols, (cuuint64_t)rows};
    cuuint64_t strides[1] = {(cuuint64_t)cols * 2};
    cuuint32_t box[2] = {(cuuint32_t)box_cols, (cuuint32_t)box_rows};
    cuuint32_t es[2] = {1, 1};
    enc(&m, CU_TENSOR_MAP_DATA_TYPE_BFLOAT16, 2, const_cast<void*>(ptr), dims, strides, box, es, CU_TENSOR_MAP_INTERLEAVE_NONE, sw,
        promo, CU_TENSOR_MAP_FLOAT_OOB_FILL_NONE);
    return m;
}

}

extern "C" void kernel_launch(void* const* d_in, const int* in_sizes, int n_in, void* d_out, int out_size) {
    (void)in_sizes; (void)n_in; (void)out_size;
    static EncodeFn enc = nullptr;
    if (!enc) {
        void* fn = nullptr;
        cudaDriverEntryPointQueryResult qr;
        cudaGetDriverEntryPoint("cuTensorMapEncodeTiled", &fn, cudaEnableDefault, &qr);
        enc = (EncodeFn)fn;
        cudaFuncSetAttribute(fused_kernel, cudaFuncAttributeMaxDynamicSharedMemorySize, SMEM_BYTES);
    }
    Params p;
    p.x = (const __nv_bfloat16*)d_in[0];
    p.kc = (const __nv_bfloat16*)d_in[1];
    p.vc = (const __nv_bfloat16*)d_in[2];
    p.b1 = (const __nv_bfloat16*)d_in[7];
    p.b2 = (const __nv_bfloat16*)d_in[9];
    p.c = (const __nv_bfloat16*)d_in[10];
    p.out = (__nv_bfloat16*)d_out;
    CUtensorMap tm_wmod = make_map(enc, d_in[11], NMOD, D, 32, 160, CU_TENSOR_MAP_SWIZZLE_64B, CU_TENSOR_MAP_L2_PROMOTION_L2_128B);
    CUtensorMap tm_wq = make_map(enc, d_in[3], NH * DH, D, 32, 160, CU_TENSOR_MAP_SWIZZLE_64B, CU_TENSOR_MAP_L2_PROMOTION_L2_128B);
    CUtensorMap tm_wo = make_map(enc, d_in[4], D, NH * DH, 32, 128, CU_TENSOR_MAP_SWIZZLE_64B);
    CUtensorMap tm_w1 = make_map(enc, d_in[6], FF, D, 32, 160, CU_TENSOR_MAP_SWIZZLE_64B);
    CUtensorMap tm_w2 = make_map(enc, d_in[8], D, FF, 64, 32, CU_TENSOR_MAP_SWIZZLE_128B);
    CUtensorMap tm_v = make_map(enc, d_in[2], DH, NB * NH * SK, 64, TILE_KEYS, CU_TENSOR_MAP_SWIZZLE_128B);
    CUtensorMap tm_gb = make_map(enc, d_in[11], NMOD, D, 8, 160, CU_TENSOR_MAP_SWIZZLE_NONE, CU_TENSOR_MAP_L2_PROMOTION_L2_128B);
    fused_kernel<<<NCTA, NTHREADS, SMEM_BYTES>>>(p, tm_wmod, tm_wq, tm_wo, tm_w1, tm_w2, tm_v, tm_gb);
}
```

```cpp
#include <cuda_runtime.h>
#include <cuda.h>
#include <cuda_bf16.h>
#include <stdint.h>
#include <stdlib.h>

namespace {

constexpr int NB = 4, D = 640, NH = 32, DH = 128, SK = 8192, WIN = 2048, FF = 1728, NMOD = 6 * D;
constexpr int NCTA = 128;
constexpr int NOWN = 80;
constexpr int NF = 54;
constexpr int NTHREADS = 320;
constexpr int TILE_KEYS = 64;
constexpr int TILE_BYTES = TILE_KEYS * DH * 2;
constexpr int NITEM = 2 * WIN / TILE_KEYS;
constexpr int NS = 8;
constexpr int NMODC = 120;
constexpr int SPIN_LIMIT = 1 << 18;
#define INFLIGHT 3
#define WQ_DELAY 500
#define MOD_T 4200
#define Q_PAUSE 1100
#define PACE_A 7500
#define PACE_TAU 635
#define ROT(c) 0
#define PF_END 16
#define PH_FIRST 24
#define PH_LAG 5
#define LAT_T 2300
#define WO_T -1050
#define WO_S 250
#define W1_T 860
#define W2_T 1560
#define GB_T 2350
#define GB_EV 700
#define CLR_CHECK 28000
constexpr int NPROBE = 8, PROBE_END = 10000;
constexpr int SEG_J = 8;

constexpr int OFF_RING = 0;
constexpr int OFF_X = OFF_RING + NS * TILE_BYTES;
constexpr int X_WM = OFF_X;
constexpr int X_WQ = OFF_X + D * 64;
constexpr int X_WO = OFF_X;
constexpr int X_W1 = X_WO + 5 * DH * 64;
constexpr int X_END = X_W1 + D * 64;
constexpr int X_W2 = OFF_RING;
constexpr int X_GB = OFF_RING + 3 * TILE_BYTES;
static_assert(X_WQ + D * 64 <= X_END, "prologue weights must fit");
constexpr int VEC_STRIDE = 1296;
constexpr int OFF_VA = X_END;
constexpr int OFF_VB = OFF_VA + 4 * VEC_STRIDE;
constexpr int OFF_RED = OFF_VB + 4 * VEC_STRIDE;
constexpr int OFF_ML = OFF_RED + 4 * VEC_STRIDE;
constexpr int O_STRIDE = 288;
constexpr int OFF_O = OFF_ML + 64;
constexpr int OFF_Q = OFF_O + 4 * O_STRIDE;
constexpr int OFF_OWN = OFF_Q + 256;
constexpr int OWN_X = OFF_OWN, OWN_B2 = OWN_X + 64, OWN_GA = OWN_B2 + 64, OWN_GB = OWN_GA + 64, OWN_B1 = OWN_GB + 256;
constexpr int OFF_STAT = OWN_B1 + 128;
constexpr int OFF_TAB1 = OFF_STAT + 32;
constexpr int OFF_TAB2 = OFF_TAB1 + NOWN * 4;
constexpr int OFF_SIDE = OFF_TAB2 + NOWN * 4;
constexpr int OFF_BAR = OFF_SIDE + 8;
constexpr int NBAR = 2 * NS + 32;
constexpr int SMEM_BYTES = OFF_BAR + NBAR * 8;
constexpr int SC_OP = OFF_RING + 4 * TILE_BYTES;
constexpr int SC_AB = SC_OP + 4096;
constexpr int SC_Y = SC_AB + 8192;
constexpr int SC_ST = SC_Y + 4096;
constexpr int SC_E4 = SC_ST + 256;
constexpr int SC_E6 = SC_E4 + 1024;
constexpr int SC_P = SC_E6 + 1024;
constexpr int SC_H1 = SC_P + 256;
static_assert(SMEM_BYTES <= 232448, "smem");
static_assert(OFF_BAR % 8 == 0 && OFF_X % 1024 == 0 && X_WQ % 512 == 0 && X_W1 % 512 == 0 && OFF_VA % 16 == 0 && OFF_RED % 16 == 0 && OFF_ML % 16 == 0 && OFF_O % 16 == 0 && OFF_Q % 16 == 0, "align");
constexpr int NB_O = 2  , NB_E4 = 10, NB_E6 = 11, NB_AB = 12, NB_Y = 13, NB_H1 = 14  ;

__device__ __align__(128) uint32_t g_mod[NMODC * 64];
__device__ __align__(128) uint32_t g_q[NCTA * 128];
__device__ uint32_t g_clr[NCTA];
__device__ __align__(128) uint32_t g_phase[8 * 32];
constexpr int SL_P1 = 0;
constexpr int SL_P2 = SL_P1 + NOWN;
constexpr int SL_O = SL_P2 + 2 * NOWN;
constexpr int SL_X1 = SL_O + 8;
constexpr int SL_SIDE = SL_X1 + 3;
static_assert(SL_SIDE < 256, "one 2 MB page");
__device__ uint32_t g_slots[2 * 256 * 2048];
__device__ __forceinline__ uint32_t* slot(int i, int side) {
    const size_t base = ((size_t)g_slots + 0x1fffff) & ~(size_t)0x1fffff;
    return (uint32_t*)base + i * 2048 + (((__popc(i & 0x59) ^ side) & 1) << 10);
}
#define PROF_DECL
#define HPROF(i) do { } while (0)
#define PROF(i) do { } while (0)
#define PROF_DUMP do { } while (0)

__device__ __forceinline__ uint32_t smem_u32(const void* p) { return (uint32_t)__cvta_generic_to_shared(p); }
__device__ __forceinline__ void mbar_init(uint32_t bar, uint32_t cnt) { asm volatile("mbarrier.init.shared::cta.b64 [%0], %1;" ::"r"(bar), "r"(cnt) : "memory"); }
__device__ __forceinline__ void mbar_expect_tx(uint32_t bar, uint32_t bytes) { asm volatile("mbarrier.arrive.expect_tx.shared::cta.b64 _, [%0], %1;" ::"r"(bar), "r"(bytes) : "memory"); }
__device__ __forceinline__ void mbar_arrive(uint32_t bar) { asm volatile("mbarrier.arrive.shared::cta.b64 _, [%0];" ::"r"(bar) : "memory"); }
__device__ __forceinline__ void mbar_wait(uint32_t bar, uint32_t parity) {
    uint32_t ok;
    int it = 0;
    while (true) {
        asm volatile("{\n.reg .pred p;\nmbarrier.try_wait.parity.shared::cta.b64 p, [%1], %2;\nselp.u32 %0, 1, 0, p;\n}" : "=r"(ok) : "r"(bar), "r"(parity) : "memory");
        if (ok) break;
        if (++it > SPIN_LIMIT) __trap();
    }
}
__device__ __forceinline__ void bulk_load(uint32_t dst, const void* src, uint32_t bytes, uint32_t bar, uint64_t pol) {
    asm volatile("cp.async.bulk.shared::cluster.global.mbarrier::complete_tx::bytes.L2::cache_hint [%0], [%1], %2, [%3], %4;"
                 ::"r"(dst), "l"(src), "r"(bytes), "r"(bar), "l"(pol) : "memory");
}
__device__ __forceinline__ void bar_cons() { asm volatile("bar.sync 1, 256;" ::: "memory"); }
template <int ID, int N> __device__ __forceinline__ void nbar_sync() { asm volatile("bar.sync %0, %1;" ::"n"(ID), "n"(N) : "memory"); }
template <int ID, int N> __device__ __forceinline__ void nbar_arrive() { asm volatile("bar.arrive %0, %1;" ::"n"(ID), "n"(N) : "memory"); }
__device__ __forceinline__ bool mbar_test(uint32_t bar, uint32_t parity) {
    uint32_t ok;
    asm volatile("{\n.reg .pred p;\nmbarrier.test_wait.parity.shared::cta.b64 p, [%1], %2;\nselp.u32 %0, 1, 0, p;\n}" : "=r"(ok) : "r"(bar), "r"(parity) : "memory");
    return ok;
}
__device__ __forceinline__ uint32_t pin(uint32_t v) { asm volatile("" : "+r"(v)); return v; }
template <class T> __device__ __forceinline__ T pin_hard(T v) { return __shfl_sync(0xffffffffu, v, threadIdx.x & 31); }
template <class T> __device__ __forceinline__ T* pin(T* v) { asm volatile("" : "+l"(v)); return v; }
__device__ __forceinline__ void ldsm4(uint32_t (&a)[4], uint32_t addr) {
    asm volatile("ldmatrix.sync.aligned.m8n8.x4.shared.b16 {%0,%1,%2,%3}, [%4];" : "=r"(a[0]), "=r"(a[1]), "=r"(a[2]), "=r"(a[3]) : "r"(addr) : "memory");
}
__device__ __forceinline__ void ldsm4t(uint32_t (&a)[4], uint32_t addr) {
    asm volatile("ldmatrix.sync.aligned.m8n8.x4.trans.shared.b16 {%0,%1,%2,%3}, [%4];" : "=r"(a[0]), "=r"(a[1]), "=r"(a[2]), "=r"(a[3]) : "r"(addr) : "memory");
}
__device__ __forceinline__ void mma16816(float (&c)[4], const uint32_t (&a)[4], uint32_t b0, uint32_t b1) {
    asm volatile("mma.sync.aligned.m16n8k16.row.col.f32.bf16.bf16.f32 {%0,%1,%2,%3}, {%4,%5,%6,%7}, {%8,%9}, {%0,%1,%2,%3};"
                 : "+f"(c[0]), "+f"(c[1]), "+f"(c[2]), "+f"(c[3]) : "r"(a[0]), "r"(a[1]), "r"(a[2]), "r"(a[3]), "r"(b0), "r"(b1));
}
__device__ __forceinline__ uint32_t lds32(uint32_t addr) { uint32_t v; asm volatile("ld.shared.u32 %0, [%1];" : "=r"(v) : "r"(addr) : "memory"); return v; }
__device__ __forceinline__ float lds_f32(uint32_t addr) { float v; asm volatile("ld.shared.f32 %0, [%1];" : "=f"(v) : "r"(addr) : "memory"); return v; }
__device__ __forceinline__ float2 lds_f32x2(uint32_t addr) { float2 v; asm volatile("ld.shared.v2.f32 {%0,%1}, [%2];" : "=f"(v.x), "=f"(v.y) : "r"(addr) : "memory"); return v; }
__device__ __forceinline__ float4 lds_f32x4(uint32_t addr) { float4 v; asm volatile("ld.shared.v4.f32 {%0,%1,%2,%3}, [%4];" : "=f"(v.x), "=f"(v.y), "=f"(v.z), "=f"(v.w) : "r"(addr) : "memory"); return v; }
__device__ __forceinline__ uint2 lds64(uint32_t addr) { uint2 v; asm volatile("ld.shared.v2.u32 {%0,%1}, [%2];" : "=r"(v.x), "=r"(v.y) : "r"(addr) : "memory"); return v; }
__device__ __forceinline__ uint4 lds128(uint32_t addr) { uint4 v; asm volatile("ld.shared.v4.u32 {%0,%1,%2,%3}, [%4];" : "=r"(v.x), "=r"(v.y), "=r"(v.z), "=r"(v.w) : "r"(addr) : "memory"); return v; }
__device__ __forceinline__ void sts16(uint32_t addr, uint32_t v) { asm volatile("st.shared.b16 [%0], %1;" ::"r"(addr), "h"((unsigned short)v) : "memory"); }
__device__ __forceinline__ void sts32(uint32_t addr, uint32_t v) { asm volatile("st.shared.u32 [%0], %1;" ::"r"(addr), "r"(v) : "memory"); }
__device__ __forceinline__ void sts_f32(uint32_t addr, float v) { asm volatile("st.shared.f32 [%0], %1;" ::"r"(addr), "f"(v) : "memory"); }
__device__ __forceinline__ void sts_f32x2(uint32_t addr, float a, float b) { asm volatile("st.shared.v2.f32 [%0], {%1,%2};" ::"r"(addr), "f"(a), "f"(b) : "memory"); }
__device__ __forceinline__ void sts128(uint32_t addr, uint4 v) { asm volatile("st.shared.v4.u32 [%0], {%1,%2,%3,%4};" ::"r"(addr), "r"(v.x), "r"(v.y), "r"(v.z), "r"(v.w) : "memory"); }
__device__ __forceinline__ uint4 ldg_relaxed(const uint32_t* p) {
    uint4 v;
    asm volatile("ld.relaxed.gpu.global.v4.u32 {%0,%1,%2,%3}, [%4];" : "=r"(v.x), "=r"(v.y), "=r"(v.z), "=r"(v.w) : "l"(p) : "memory");
    return v;
}
__device__ __forceinline__ void ldg_relaxed_if(bool on, uint4& v, const uint32_t* p) {
    asm volatile("{\n.reg .pred q;\nsetp.ne.u32 q, %5, 0;\n@q ld.relaxed.gpu.global.v4.u32 {%0,%1,%2,%3}, [%4];\n}"
                 : "+r"(v.x), "+r"(v.y), "+r"(v.z), "+r"(v.w) : "l"(p), "r"((uint32_t)on) : "memory");
}
__device__ __forceinline__ void stg_relaxed2_if(bool on, uint32_t* p, uint32_t a, uint32_t b) {
    asm volatile("{\n.reg .pred q;\nsetp.ne.u32 q, %3, 0;\n@q st.relaxed.gpu.global.v2.u32 [%0], {%1,%2};\n}" ::"l"(p), "r"(a), "r"(b), "r"((uint32_t)on) : "memory");
}
__device__ __forceinline__ uint32_t ldg_relaxed32(const uint32_t* p) { uint32_t v; asm volatile("ld.relaxed.gpu.global.u32 %0, [%1];" : "=r"(v) : "l"(p) : "memory"); return v; }
__device__ __forceinline__ void stg_relaxed(uint32_t* p, uint32_t v) { asm volatile("st.relaxed.gpu.global.u32 [%0], %1;" ::"l"(p), "r"(v) : "memory"); }
__device__ __forceinline__ void stg_zero4(uint32_t* p) { asm volatile("st.relaxed.gpu.global.v4.u32 [%0], {%1,%1,%1,%1};" ::"l"(p), "r"(0u) : "memory"); }
__device__ __forceinline__ bool ready(const uint4& v) { return (v.x != 0u) & (v.y != 0u) & (v.z != 0u) & (v.w != 0u); }
__device__ __forceinline__ uint32_t min4(const uint4& v) { return min(__vimin3_u32(v.x, v.y, v.z), v.w); }
__device__ __forceinline__ uint4 inv4(const uint4& v) { return make_uint4(~v.x, ~v.y, ~v.z, ~v.w); }
__device__ __forceinline__ uint32_t pack_bf(float lo, float hi) {
    uint32_t r;
    asm("cvt.rn.bf16x2.f32 %0, %1, %2;" : "=r"(r) : "f"(hi), "f"(lo));
    return r;
}
__device__ __forceinline__ float bfr(float x) { return __uint_as_float(pack_bf(0.f, x) & 0xffff0000u); }
__device__ __forceinline__ float bf_lo(uint32_t w) { return __uint_as_float(w << 16); }
__device__ __forceinline__ float bf_hi(uint32_t w) { return __uint_as_float(w & 0xffff0000u); }
__device__ __forceinline__ float bf2f(__nv_bfloat16 v) { return __bfloat162float(v); }
__device__ __forceinline__ float ex2(float x) { float y; asm("ex2.approx.ftz.f32 %0, %1;" : "=f"(y) : "f"(x)); return y; }
__device__ __forceinline__ float rcp_fast(float x) { float y; asm("rcp.approx.ftz.f32 %0, %1;" : "=f"(y) : "f"(x)); return y; }
__device__ __forceinline__ float rsqrt_fast(float x) { float y; asm("rsqrt.approx.ftz.f32 %0, %1;" : "=f"(y) : "f"(x)); return y; }
__device__ __forceinline__ float sqrt_fast(float x) { float y; asm("sqrt.approx.f32 %0, %1;" : "=f"(y) : "f"(x)); return y; }
__device__ __forceinline__ uint32_t bf2_add(uint32_t a, uint32_t b) { uint32_t r; asm("add.rn.bf16x2 %0, %1, %2;" : "=r"(r) : "r"(a), "r"(b)); return r; }
__device__ __forceinline__ uint32_t bf2_sub(uint32_t a, uint32_t b) { uint32_t r; asm("sub.rn.bf16x2 %0, %1, %2;" : "=r"(r) : "r"(a), "r"(b)); return r; }
__device__ __forceinline__ uint32_t bf2_mul(uint32_t a, uint32_t b) { uint32_t r; asm("mul.rn.bf16x2 %0, %1, %2;" : "=r"(r) : "r"(a), "r"(b)); return r; }
__device__ __forceinline__ uint32_t gtime32() { uint32_t c; asm volatile("mov.u32 %0, %%globaltimer_lo;" : "=r"(c)); return c; }
__device__ __forceinline__ uint32_t clock32() { uint32_t c; asm volatile("mov.u32 %0, %%clock;" : "=r"(c)); return c; }

__device__ __forceinline__ float warp_sum(float v) {
#pragma unroll
    for (int o = 16; o > 0; o >>= 1) v += __shfl_xor_sync(0xffffffffu, v, o);
    return v;
}

struct Params {
    const __nv_bfloat16 *x, *kc, *vc, *b1, *b2, *c;
    __nv_bfloat16* out;
};

__device__ __forceinline__ void tma2d(uint32_t dst, const CUtensorMap* tm, int x, int y, uint32_t bar) {
    asm volatile("cp.async.bulk.tensor.2d.shared::cluster.global.mbarrier::complete_tx::bytes [%0], [%1, {%2, %3}], [%4];"
                 ::"r"(dst), "l"(tm), "r"(x), "r"(y), "r"(bar) : "memory");
}

__device__ __forceinline__ void tma2d_hint(uint32_t dst, const CUtensorMap* tm, int x, int y, uint32_t bar, uint64_t pol) {
    asm volatile("cp.async.bulk.tensor.2d.shared::cluster.global.mbarrier::complete_tx::bytes.L2::cache_hint [%0], [%1, {%2, %3}], [%4], %5;"
                 ::"r"(dst), "l"(tm), "r"(x), "r"(y), "r"(bar), "l"(pol) : "memory");
}
__device__ __forceinline__ uint32_t flag(float v) { return __float_as_uint(v) | 1u; }
__device__ __forceinline__ uint32_t* slot_ptr(uint32_t lo) {
    uint32_t* r;
    asm volatile("mov.b64 %0, {%1, %2};" : "=l"(r) : "r"(lo), "r"((uint32_t)((size_t)slot(0, 0) >> 32)));
    return r;
}

__device__ __forceinline__ void load_bfrag(uint32_t vec, int stride, int k0, int g, int t, uint32_t& b0, uint32_t& b1) {
    uint32_t a = vec + (g & 3) * stride + (k0 + 2 * t) * 2;
    b0 = lds32(a);
    b1 = lds32(a + 16);
}

__device__ __forceinline__ void ln_finish(float pivot, float sum, float sumsq, uint32_t& m2, float& rden) {
    float dm = sum * (1.f / D);
    float var = fmaxf(sumsq * (1.f / D) - dm * dm, 0.f);
    float mean = pivot + dm;
    m2 = pack_bf(mean, mean);
    rden = rcp_fast(bfr(sqrt_fast(bfr(bfr(var) + 1e-5f))));
}
__device__ __forceinline__ uint32_t ln_mod_pair(uint32_t xw, uint32_t cw, uint32_t sw, uint32_t m2, float rden) {
    uint32_t d = bf2_sub(xw, m2);
    uint32_t ln = pack_bf(bf_lo(d) * rden, bf_hi(d) * rden);
    return bf2_add(bf2_mul(ln, bf2_add(cw, 0x3f803f80u)), sw);
}
__device__ __forceinline__ uint4 ln_mod4(const uint4& x, const uint4& c, const uint4& s, uint32_t m2, float rden) {
    return make_uint4(ln_mod_pair(x.x, c.x, s.x, m2, rden), ln_mod_pair(x.y, c.y, s.y, m2, rden),
                      ln_mod_pair(x.z, c.z, s.z, m2, rden), ln_mod_pair(x.w, c.w, s.w, m2, rden));
}
__device__ __forceinline__ void acc_stats(const uint4& v, float pv, float& s, float& q) {
    const float a0 = bf_lo(v.x) - pv, a1 = bf_hi(v.x) - pv, a2 = bf_lo(v.y) - pv, a3 = bf_hi(v.y) - pv;
    const float a4 = bf_lo(v.z) - pv, a5 = bf_hi(v.z) - pv, a6 = bf_lo(v.w) - pv, a7 = bf_hi(v.w) - pv;
    s += ((a0 + a1) + (a2 + a3)) + ((a4 + a5) + (a6 + a7));
    q += (fmaf(a0, a0, a1 * a1) + fmaf(a2, a2, a3 * a3)) + (fmaf(a4, a4, a5 * a5) + fmaf(a6, a6, a7 * a7));
}
__device__ __forceinline__ uint32_t* mod_slot(int kind, int j, int b) { return g_mod + (kind * 20 + (j >> 2)) * 64 + b * 16 + (j & 3) * 4; }

template <int N>
__device__ __forceinline__ void poll_n(uint4 (&v)[N], const uint32_t* const* ptr, const bool* on) {
    bool pend[N];
#pragma unroll
    for (int i = 0; i < N; i++) pend[i] = on[i];
    int it = 0;
    while (true) {
#pragma unroll
        for (int i = 0; i < N; i++) if (pend[i]) v[i] = ldg_relaxed(ptr[i]);
        bool any = false;
#pragma unroll
        for (int i = 0; i < N; i++) { pend[i] = pend[i] && !ready(v[i]); any |= pend[i]; }
        if (!__any_sync(0xffffffffu, any)) break;
        if (++it > SPIN_LIMIT) __trap();
    }
#pragma unroll
    for (int i = 0; i < N; i++) v[i] = inv4(v[i]);
}
__device__ __forceinline__ uint4 poll1(const uint32_t* p, bool on) {
    uint4 v[1] = {make_uint4(0, 0, 0, 0)};
    const uint32_t* const ptr[1] = {p};
    const bool o[1] = {on};
    poll_n<1>(v, ptr, o);
    return v[0];
}

#define OWNER_EXCHANGE_AND_VOTE \
    "shfl.sync.bfly.b32 a, z, 8, 31, 0xffffffff;\nshfl.sync.bfly.b32 b, y, 16, 31, 0xffffffff;\nshfl.sync.bfly.b32 c, w, 24, 31, 0xffffffff;\n" \
    "setp.ne.u32 q, t, 0;\nvote.sync.all.pred q, q, 0xffffffff;\n@!q bra.uni L_%=;\nadd.f32 a, a, x;\nadd.f32 b, b, c;\nadd.f32 %0, a, b;\n}"
__device__ __forceinline__ float poll_e4(const uint32_t* p) {
    float s;
    asm volatile("{\n.reg .pred q;\n.reg .b32 t, n, x, y, z, w, a, b, c;\nmov.u32 n, 0;\n"
                 "L_%=:\nld.relaxed.gpu.global.v4.u32 {x, y, z, w}, [%1];\nadd.u32 n, n, 1;\nsetp.gt.u32 q, n, %2;\n@q trap;\nbar.warp.sync 0xffffffff;\n"
                 "lop3.b32 t, x, y, z, 0x80;\nlop3.b32 t, t, w, 1, 0x80;\n" OWNER_EXCHANGE_AND_VOTE
                 : "=f"(s) : "l"(p), "n"(SPIN_LIMIT) : "memory");
    return s;
}
__device__ __forceinline__ float poll_e6(const uint32_t* pa, const uint32_t* pb, bool two) {
    float s;
    asm volatile("{\n.reg .pred q, r;\n.reg .b32 t, n, x, y, z, w, a, b, c, u0, u1, v0, v1;\nmov.u32 n, 0;\nsetp.ne.u32 r, %4, 0;\nmov.b32 v0, 0xffffffff;\nmov.b32 v1, 0xffffffff;\n"
                 "L_%=:\n@r ld.relaxed.gpu.global.v2.u32 {v0, v1}, [%3];\nld.relaxed.gpu.global.v2.u32 {u0, u1}, [%1];\nadd.u32 n, n, 1;\nsetp.gt.u32 q, n, %2;\n@q trap;\nbar.warp.sync 0xffffffff;\n"
                 "lop3.b32 a, u0, 0xffff0000, 0, 0x0c;\nlop3.b32 b, v0, 0xffff0000, 0, 0x0c;\nadd.f32 y, a, b;\n"
                 "lop3.b32 a, u1, 0xffff0000, 0, 0x0c;\nlop3.b32 b, v1, 0xffff0000, 0, 0x0c;\nadd.f32 w, a, b;\n"
                 "shl.b32 a, u1, 16;\nshl.b32 b, v1, 16;\nxor.b32 a, a, 0xffff0000;\nxor.b32 b, b, 0xffff0000;\nadd.f32 z, a, b;\n"
                 "shl.b32 a, u0, 16;\nshl.b32 b, v0, 16;\nxor.b32 a, a, 0xffff0000;\nxor.b32 b, b, 0xffff0000;\nadd.f32 x, a, b;\n"
                 "min.u32 t, u0, u1;\nmin.u32 t, t, v0;\nmin.u32 t, t, v1;\n" OWNER_EXCHANGE_AND_VOTE
                 : "=f"(s) : "l"(pa), "n"(SPIN_LIMIT), "l"(pb), "r"((uint32_t)two) : "memory");
    return s;
}

__device__ __forceinline__ void gelu_stage(uint32_t sb, int m, int lane) {
    const int g = lane >> 2, b = lane & 3;
    const uint32_t y_ld = pin_hard(sb + SC_Y + m * 256 + lane * 8), s_ld = pin_hard(sb + SC_ST + b * 64);
    const uint32_t h_st = pin_hard(sb + SC_H1 + b * 64 + (g >> 1) * 16 + m * 8 + (g & 1) * 2);
    float a0 = 0.f, b0 = lds_f32(sb + OWN_B1 + (16 * m + g) * 4), a1 = 0.f, b1 = lds_f32(sb + OWN_B1 + (16 * m + g + 8) * 4);
    const float piv = bf_hi(lds32(sb + OFF_STAT + b * 8));
    nbar_sync<NB_AB, 320>();
#pragma unroll
    for (int w = 0; w < 8; w++) {
        const float4 t = lds_f32x4(sb + SC_AB + w * 1024 + m * 512 + lane * 16);
        a0 += t.x; b0 += t.y; a1 += t.z; b1 += t.w;
    }
    sts128(sb + SC_AB + m * 512 + lane * 16, make_uint4(__float_as_uint(a0), __float_as_uint(b0), __float_as_uint(a1), __float_as_uint(b1)));
    nbar_sync<NB_Y, 320>();
    float4 q[4];
    float2 y[8];
#pragma unroll
    for (int i = 0; i < 4; i++) q[i] = lds_f32x4(s_ld + i * 16);
#pragma unroll
    for (int w = 0; w < 8; w++) y[w] = lds_f32x2(y_ld + w * 512);
    const float dm = (((q[0].y + q[0].w) + (q[1].y + q[1].w)) + ((q[2].y + q[2].w) + (q[3].y + q[3].w))) * (1.f / D);
    const float sq = ((q[0].x + q[0].z) + (q[1].x + q[1].z)) + ((q[2].x + q[2].z) + (q[3].x + q[3].z));
    const float r = rsqrt_fast(fmaxf(fmaf(-dm, dm, fmaf(sq, 1.f / D, 1e-5f)), 1e-5f));
    const float y0 = ((y[0].x + y[1].x) + (y[2].x + y[3].x)) + ((y[4].x + y[5].x) + (y[6].x + y[7].x));
    const float y1 = ((y[0].y + y[1].y) + (y[2].y + y[3].y)) + ((y[4].y + y[5].y) + (y[6].y + y[7].y));
    const float dmr = piv - bfr(piv - dm);
    const float u0 = fmaf(r, fmaf(dmr, a0, -y0), b0), u1 = fmaf(r, fmaf(dmr, a1, -y1), b1);
    const float e0 = ex2(u0 * fmaf(u0 * u0, -0.044715f * 2.302208198144325f, -2.302208198144325f));
    const float e1 = ex2(u1 * fmaf(u1 * u1, -0.044715f * 2.302208198144325f, -2.302208198144325f));
    sts16(h_st, pack_bf(u0 * rcp_fast(1.f + e0), 0.f));
    sts16(h_st + 4, pack_bf(u1 * rcp_fast(1.f + e1), 0.f));
#pragma unroll
    for (int w = 0; w < 4; w++) asm volatile("bar.arrive %0, 128;" ::"r"((NB_H1 + w) & 15) : "memory");
}

struct Roles { bool is_f, is_owner; int f, own; };
__device__ __forceinline__ Roles roles(int cta) {
    Roles r;
    r.f = (cta * 27) >> 6;
    r.is_f = (((cta + 1) * 27) >> 6) != r.f;
    r.is_owner = !r.is_f || r.f % 9 == 4;
    r.own = r.is_f ? 74 + r.f / 9 : cta - r.f;
    return r;
}

__global__ void __launch_bounds__(NTHREADS, 1)
fused_kernel(const Params p, const __grid_constant__ CUtensorMap tm_wmod, const __grid_constant__ CUtensorMap tm_wq,
             const __grid_constant__ CUtensorMap tm_wo, const __grid_constant__ CUtensorMap tm_w1, const __grid_constant__ CUtensorMap tm_w2,
             const __grid_constant__ CUtensorMap tm_v, const __grid_constant__ CUtensorMap tm_gb) {
    extern __shared__ __align__(1024) unsigned char smem[];
    const uint32_t t_start = gtime32();
    if (threadIdx.x == 0) {
        const uint32_t c_ = blockIdx.x;
        const uint32_t off = ((c_ & 3) << 26) + (c_ >> 2) * (1u << 21) + (ROT(c_) << 14) + (SK - WIN) * DH * 2;
        asm volatile("cp.async.bulk.prefetch.L2.global.L2::cache_hint [%0], %1, %2;" ::"l"((const char*)p.kc + off), "r"(TILE_BYTES), "l"(0x12f0000000000000ull  ) : "memory");
    }
    const uint32_t sb = smem_u32(smem);
    const int cta = blockIdx.x;
    const int head = cta >> 2, bown = cta & 3;
    const int rot = ROT(cta);
    const char* const kb = (const char*)(p.kc + ((size_t)(bown * NH + head) * SK + (SK - WIN)) * DH);
    uint64_t pol = 0;
    if (threadIdx.x == 256) {
        mbar_init(sb + OFF_BAR, 1);
        asm volatile("fence.mbarrier_init.release.cluster;" ::: "memory");
        asm volatile("createpolicy.fractional.L2::evict_first.b64 %0, 1.0;" : "=l"(pol));
        mbar_expect_tx(sb + OFF_BAR, TILE_BYTES);
        bulk_load(sb + OFF_RING, kb + (size_t)rot * TILE_BYTES, TILE_BYTES, sb + OFF_BAR, pol);
        if ((((head + 1) * 5) >> 4) != ((head * 5) >> 4)) {
            const uint32_t bar = sb + OFF_BAR + 2 * NS * 8;
            mbar_init(bar, 1);
            asm volatile("fence.mbarrier_init.release.cluster;" ::: "memory");
            mbar_expect_tx(bar, D * 64);
#pragma unroll 1
            for (int r = 0; r < D; r += 160) tma2d(sb + X_WM + r * 64, &tm_wmod, 32 * (((head * 5) >> 4) * 4 + bown), r, bar);
        }
    }
    const uint32_t bar_full = sb + OFF_BAR, bar_empty = bar_full + NS * 8;
    const uint32_t bar_wm = bar_empty + NS * 8, bar_wq = bar_wm + 8, bar_xfree = bar_wq + 8, bar_wo = bar_xfree + 8  ;
    const uint32_t bar_w1 = bar_wo + 40  , bar_w2 = bar_w1 + 32  , bar_help = bar_w2 + 80, bar_v = bar_help + 8  ;
    const uint32_t bar_gb = bar_v + 32  , bar_x1 = bar_gb + 32;
    const int tid = threadIdx.x, warp = tid >> 5, lane = tid & 31;
    const Roles role = roles(cta);
    const bool is_f = role.is_f, is_owner = role.is_owner;
    const int f = role.f, own = role.own;
    const bool crit = (((head + 1) * 5) >> 4) != ((head * 5) >> 4);
    const int mr = cta - ((head * 5) >> 4) * 4, mq = ((head * 5) >> 4) * 4 + bown;
    const int ml = mr * 31 / 44;
    const bool late = !crit && (mr + 1) * 31 / 44 != ml;
    const int mc = crit ? mq : ml < 60 ? 40 + ml : 58 + ml;
    const bool gb_own = is_owner && own < 72;

    PROF_DECL
    PROF(0);
    uint4 xa = make_uint4(0, 0, 0, 0), xb = xa, ca0 = xa, ca1 = xa, xs[3] = {xa, xa, xa};
    uint32_t own0 = 0;
    __nv_bfloat16 own2 = __float2bfloat16(0.f);
    if (warp < 8) {
        xa = *(const uint4*)(p.x + (tid & 3) * D + (tid >> 2) * 8);
        ca0 = ((const uint4*)p.c)[tid];
        if (tid < 64) { xb = *(const uint4*)(p.x + (tid & 3) * D + (64 + (tid >> 2)) * 8); ca1 = ((const uint4*)p.c)[256 + tid]; }
        if (warp < 4) {
#pragma unroll
            for (int i = 0; i < 3; i++) if (lane + 32 * i < 80) xs[i] = ((const uint4*)p.x)[warp * 80 + lane + 32 * i];
        } else if (warp == 4) {
            if (is_owner) own0 = *(const uint32_t*)((lane < 16 ? p.x + (lane >> 2) * D : p.b2) + 8 * own + 2 * (lane & 3));
            if (is_f) own2 = p.b1[32 * f + lane];
        }
    }
    const char* const vb = (const char*)(p.vc + ((size_t)(bown * NH + head) * SK + (SK - WIN)) * DH);
    const uint32_t bar_first = crit ? bar_wm : bar_wq;
    if (threadIdx.x == 256) {
        if (!crit) {
            mbar_init(bar_wq, 1);
            asm volatile("fence.mbarrier_init.release.cluster;" ::: "memory");
            mbar_expect_tx(bar_wq, D * 64);
            const uint32_t c0 = clock32();
            while (clock32() - c0 < WQ_DELAY) { }
#pragma unroll
            for (int r = 0; r < D; r += 160) tma2d(sb + X_WQ + r * 64, &tm_wq, 32 * cta, r, bar_wq);
        }
    } else if (threadIdx.x == 0) {
#pragma unroll
        for (int s = 0; s < NS; s++) { if (s) mbar_init(bar_full + s * 8, 1); mbar_init(bar_empty + s * 8, 4); }
        mbar_init(crit ? bar_wq : bar_wm, 1);
        mbar_init(bar_xfree, 1);
#pragma unroll
        for (int i = 0; i < 5; i++) { mbar_init(bar_wo + i * 8, 1); mbar_init(bar_w2 + i * 16, 1); mbar_init(bar_w2 + i * 16 + 8, 1); }
        mbar_init(bar_help, 1); mbar_init(bar_x1, 1);
#pragma unroll
        for (int i = 0; i < 4; i++) { mbar_init(bar_v + i * 8, 1); mbar_init(bar_w1 + i * 8, 1); mbar_init(bar_gb + i * 8, 1); }
        asm volatile("fence.mbarrier_init.release.cluster;" ::: "memory");
    }
    __syncthreads();

    if (warp == 8) {
        if (lane == 0) {
            int tp = NS;
            int sched = PACE_A - NS * PACE_TAU;
            int phase = 0;
#pragma unroll 1
            for (int t = 1; t <= NITEM; t++) {
                if (t == 1) mbar_wait(bar_full, 0);
                if (t == 2) {
                    mbar_wait(bar_first, 0);
                    if (crit) {
                        mbar_expect_tx(bar_wq, D * 64);
#pragma unroll 1
                        for (int r = 0; r < D; r += 160) tma2d(sb + X_WQ + r * 64, &tm_wq, 32 * cta, r, bar_wq);
                    }
                }
                if (t == 3) {
                    asm volatile("prefetch.tensormap [%0];" ::"l"(&tm_v) : "memory");
                    asm volatile("prefetch.tensormap [%0];" ::"l"(&tm_wo) : "memory");
                    asm volatile("prefetch.tensormap [%0];" ::"l"(&tm_w1) : "memory");
                    asm volatile("prefetch.tensormap [%0];" ::"l"(&tm_w2) : "memory");
                    asm volatile("prefetch.tensormap [%0];" ::"l"(&tm_gb) : "memory");
                }
                if (t == NS && late) {
                    mbar_wait(bar_full + (NS - INFLIGHT) * 8, 0);
                    mbar_expect_tx(bar_wm, D * 64);
#pragma unroll 1
                    for (int r = 0; r < D; r += 160) tma2d(sb + X_WM + r * 64, &tm_wmod, 32 * mc, r, bar_wm);
                }
                if (t >= NS && t < PF_END) {
                    int it = 0;
                    while (!mbar_test(bar_empty + (t & (NS - 1)) * 8, ((t >> 3) - 1) & 1)) {
                        if (tp < PF_END && (int)(gtime32() - t_start) >= PACE_A + (tp - NS) * PACE_TAU) {
                            asm volatile("cp.async.bulk.prefetch.L2.global.L2::cache_hint [%0], %1, %2;"
                                         ::"l"(((tp & 1) ? vb : kb) + (size_t)(((tp >> 1) + rot) & (NITEM / 2 - 1)) * TILE_BYTES), "r"(TILE_BYTES), "l"(pol) : "memory");
                            tp++;
                        }
                        if (++it > 16 * SPIN_LIMIT) __trap();
                    }
                    if (tp <= t) tp = t + 1;
                }
                if (t == NITEM) {
                    mbar_wait(bar_xfree, 0);
                    const uint32_t t_ref = t_start + phase + (NITEM - 1) * PACE_TAU;
#pragma unroll 1
                    for (int i = 0; i < 5; i++) {
                        while ((int)(gtime32() - t_ref) < WO_T + i * WO_S) { }
                        mbar_expect_tx(bar_wo + i * 8, DH * 64);
                        tma2d(sb + X_WO + i * (DH * 64), &tm_wo, bown * 160 + i * 32, head * DH, bar_wo + i * 8);
                    }
                    if (gb_own) {
                        mbar_wait(bar_empty + 3 * 8, ((NITEM >> 3) - 1) & 1);
                        mbar_wait(bar_x1, 0);
                        { const uint32_t c0 = clock32(); while (clock32() - c0 < GB_EV) { } }
                        while ((int)(gtime32() - t_ref) < GB_T) { }
#pragma unroll 1
                        for (int i = 0; i < 4; i++) {
                            mbar_expect_tx(bar_gb + i * 8, 160 * 16);
                            tma2d(sb + X_GB + i * (160 * 16), &tm_gb, 5 * D + 8 * own, 160 * i, bar_gb + i * 8);
                        }
                    }
                    if (is_f) {
#pragma unroll 1
                        for (int i = 0; i < 3; i++) mbar_wait(bar_empty + i * 8, ((NITEM >> 3) - 1) & 1);
                        while ((int)(gtime32() - t_ref) < W1_T) { }
#pragma unroll 1
                        for (int i = 0; i < 4; i++) {
                            mbar_expect_tx(bar_w1 + i * 8, 160 * 64);
                            tma2d(sb + X_W1 + i * (160 * 64), &tm_w1, 32 * f, 160 * i, bar_w1 + i * 8);
                        }
                        while ((int)(gtime32() - t_ref) < W2_T) { }
#pragma unroll 1
                        for (int i = 0; i < 10; i++) {
                            mbar_expect_tx(bar_w2 + i * 8, 4096);
                            tma2d(sb + X_W2 + i * 4096, &tm_w2, 64 * i, 32 * f, bar_w2 + i * 8);
                        }
                    }
                    break;
                }
                const int s = t & (NS - 1);
                if (t >= NS) {
                    mbar_wait(bar_empty + s * 8, ((t >> 3) - 1) & 1);
                    while ((int)(gtime32() - t_start) < sched + t * PACE_TAU) { }
                } else if (t >= INFLIGHT) {
                    mbar_wait(bar_full + (t - INFLIGHT) * 8, 0);
                }
                if (t < NITEM - 2) {
                    const int pair = t == NITEM - 3 ? NITEM / 2 - 1 : t >> 1;
                    mbar_expect_tx(bar_full + s * 8, TILE_BYTES);
                    bulk_load(sb + OFF_RING + s * TILE_BYTES, ((t & 1) && t != NITEM - 3 ? vb : kb) + (size_t)((pair + rot) & (NITEM / 2 - 1)) * TILE_BYTES, TILE_BYTES, bar_full + s * 8, pol);
                } else {
                    const int row = (bown * NH + head) * SK + (SK - WIN) + ((t - NITEM / 2 + rot) & (NITEM / 2 - 1)) * TILE_KEYS;
#pragma unroll 1
                    for (int i = 0; i < 2; i++) {
                        const uint32_t bar = bar_v + (2 * (t - (NITEM - 2)) + i) * 8;
                        mbar_expect_tx(bar, TILE_BYTES / 2);
                        tma2d_hint(sb + OFF_RING + s * TILE_BYTES + i * (TILE_BYTES / 2), &tm_v, 64 * i, row, bar, pol);
                    }
                }
                if (t >= PH_FIRST && (t & 7) == PH_LAG) {
                    const int now = (int)(gtime32() - t_start) - (t - PH_LAG) * PACE_TAU;
                    uint32_t ph;
                    asm volatile("atom.relaxed.gpu.global.add.u32 %0, [%1], 0;" : "=r"(ph) : "l"(g_phase + (t >> 3) * 32) : "memory");
                    phase = (int)min(((ph & 0xffffffu) * 4 + (NCTA - (ph >> 24)) * now) / NCTA, 65535u);
                    sched += (phase - LAT_T - sched) * 3 / 4;
                }
            }
        }
        __syncwarp();
    }

    if (warp == 9) {
        int side = 0;
        if (lane == 0) {
            uint32_t best[2] = {~0u, ~0u};
#pragma unroll
            for (int i = 0; i < 4; i++) stg_zero4(slot(SL_SIDE, i >> 1) + cta * 8 + (i & 1) * 4);
            uint32_t n = 0;
#pragma unroll 1
            for (int i = 0; (i & 1) || (n < NPROBE - 1 && (int)(gtime32() - t_start) < PROBE_END); i++) {
                uint32_t t0 = clock32(), t1;
                asm volatile("atom.relaxed.gpu.global.inc.u32 %0, [%1], %2;" : "=r"(n) : "l"(slot(SL_SIDE, i & 1) + cta * 8), "r"(0xffffu) : "memory");
                asm volatile("{\n.reg .pred p;\nsetp.ne.u32 p, %1, 0xffffffff;\nmov.u32 %0, 0;\n@p mov.u32 %0, %%clock;\n}" : "=r"(t1) : "r"(n) : "memory");
                if (i & 1) best[1] = min(best[1], t1 - t0); else best[0] = min(best[0], t1 - t0);
            }
            side = best[1] < best[0];
        }
        side = __shfl_sync(0xffffffffu, side, 0);
        HPROF(1);
        mbar_wait(bar_full + (NS - 1) * 8, 0);
        stg_zero4(slot(SL_O + (cta >> 4), lane >> 4) + (cta & 15) * 64 + (lane & 15) * 4);
        if (is_owner) {
#pragma unroll 1
            for (int i = lane; i < NH * 8; i += 32) stg_zero4(slot(SL_P1 + own, side) + i * 4);
#pragma unroll 1
            for (int i = lane; i < NF * 4; i += 32) stg_zero4(slot(SL_P2 + 2 * own + (i >> 7), side) + ((i >> 2) & 31) * 32 + (i & 3) * 4);
            if (lane < 8) stg_zero4(slot(SL_X1 + own / 30, lane >> 2) + (own % 30) * 32 + (lane & 3) * 4);
        }
        __threadfence();
        __syncwarp();
        if (lane == 0) stg_relaxed(g_clr + cta, 1u + side);
        HPROF(0);
        while ((int)(gtime32() - t_start) < CLR_CHECK) __nanosleep(1000);
        mbar_wait(bar_xfree, 0);
        {
            uint4 v = make_uint4(1, 1, 1, 1), gv = v, mv[20];
#pragma unroll
            for (int i = 0; i < 20; i++) mv[i] = v;
#pragma unroll 1
            for (int it = 0;; it++) {
                v = ldg_relaxed(g_clr + lane * 4);

                ldg_relaxed_if(is_owner && lane < (gb_own ? 4 : 8), gv, mod_slot(lane < 4 ? 2 : 5, own, lane & 3));
#pragma unroll
                for (int i = 0; i < 20; i++) ldg_relaxed_if(is_f, mv[i], mod_slot(3, 8 * i + (lane >> 2), lane & 3));
                bool ok = ready(v) && ready(gv);
#pragma unroll
                for (int i = 0; i < 20; i++) ok = ok && ready(mv[i]);
                if (__all_sync(0xffffffffu, ok)) break;
                if (it > SPIN_LIMIT) __trap();
                __nanosleep(2000);
            }
            const uint32_t w[4] = {v.x, v.y, v.z, v.w};
#pragma unroll
            for (int i = 0; i < 4; i++) {
                const Roles r = roles(4 * lane + i);
                if (r.is_owner) {
                    sts32(sb + OFF_TAB1 + r.own * 4, (uint32_t)(size_t)(slot(SL_P1 + r.own, w[i] - 1) + head * 32));
                    sts32(sb + OFF_TAB2 + r.own * 4, (uint32_t)(size_t)(slot(SL_P2 + 2 * r.own + (f >> 5), w[i] - 1) + (f & 31) * 32));
                }
            }
            if (lane == 0) sts32(sb + OFF_SIDE, side);
            gv = inv4(gv);
            if (lane < 4) sts128(sb + OWN_GA + lane * 16, gv);
            else if (lane < 8) {
                sts128(sb + OWN_GB + (lane & 3) * 32, make_uint4(gv.x << 16, gv.x & 0xffff0000u, gv.y << 16, gv.y & 0xffff0000u));
                sts128(sb + OWN_GB + (lane & 3) * 32 + 16, make_uint4(gv.z << 16, gv.z & 0xffff0000u, gv.w << 16, gv.w & 0xffff0000u));
            } else if (lane < 16) sts128(sb + OWN_GB + lane * 16, make_uint4(0, 0, 0, 0));
            const uint32_t dst = sb + OFF_VB + (lane & 3) * VEC_STRIDE + (lane >> 2) * 16;
#pragma unroll
            for (int i = 0; i < 10; i++) {
                const uint4 c = inv4(mv[10 + i]);
                sts128(dst + i * 128, make_uint4(bf2_add(c.x, 0x3f803f80u), bf2_add(c.y, 0x3f803f80u), bf2_add(c.z, 0x3f803f80u), bf2_add(c.w, 0x3f803f80u)));
                sts128(dst + (OFF_RED - OFF_VB) + i * 128, inv4(mv[i]));
            }
        }
        asm volatile("fence.acq_rel.gpu;" ::: "memory");
        __syncwarp();
        HPROF(3);
        if (lane == 0) mbar_arrive(bar_help);
        {
            const uint32_t* const src = pin(slot(SL_O + (cta >> 4), side) + (cta & 12) * 64 + lane * 4);
            const uint32_t dst = pin(sb + OFF_O + (lane >> 4) * O_STRIDE + (lane & 15) * 16);
            mbar_wait(bar_v + 16, 0);
            mbar_wait(bar_v + 24, 0);
            uint4 v[2];
            const uint32_t* const ptr[2] = {src, src + 128};
            const bool on[2] = {true, true};
            poll_n<2>(v, ptr, on);
            sts128(dst, v[0]);
            sts128(dst + 2 * O_STRIDE, v[1]);
#pragma unroll
            for (int w = 0; w < 8; w++) asm volatile("bar.arrive %0, 64;" ::"r"(NB_O + w) : "memory");
        }
        HPROF(4);
    }
    if (warp >= 8) {
        if (gb_own) {
            uint32_t a[10][4];
#pragma unroll
            for (int k = 0; k < 10; k++) ldsm4(a[k], sb + OFF_VA + (lane & 3) * VEC_STRIDE + (8 * k + 4 * (warp - 8) + ((lane >> 2) & 2) + (lane >> 4)) * 16);
            float c[4][4];
#pragma unroll
            for (int i = 0; i < 4; i++) c[i][0] = c[i][1] = c[i][2] = c[i][3] = 0.f;
            mbar_wait(bar_help, 0);
#pragma unroll
            for (int k = 0; k < 10; k++) {
                if (k == 0 || k == 2 || k == 5 || k == 7) mbar_wait(bar_gb + (2 * k + 1) / 5 * 8, 0);
                uint32_t w[4];
                ldsm4t(w, sb + X_GB + (64 * k + 32 * (warp - 8) + lane) * 16);
                mma16816(c[2 * (k & 1)], a[k], w[0], w[1]);
                mma16816(c[2 * (k & 1) + 1], a[k], w[2], w[3]);
            }
            if (lane < 16) sts_f32x2(sb + OWN_GB + (warp - 8) * 128 + lane * 8, (c[0][0] + c[2][0]) + (c[1][2] + c[3][2]), (c[0][1] + c[2][1]) + (c[1][3] + c[3][3]));
        }
        if (is_owner) nbar_arrive<NB_E6, 320>();
        if (is_f) gelu_stage(sb, warp - 8, lane);
        return;
    }

    const int g = lane >> 2, t4 = lane & 3;
    const int mi = lane >> 3, r8 = lane & 7;

    {
        auto silu4 = [&](const uint4& cv) {
            uint32_t w4[4] = {cv.x, cv.y, cv.z, cv.w};
#pragma unroll
            for (int e = 0; e < 4; e++) {
                float c0 = bf_lo(w4[e]), c1 = bf_hi(w4[e]);
                w4[e] = pack_bf(c0 * rcp_fast(1.f + ex2(-1.4426950408889634f * c0)), c1 * rcp_fast(1.f + ex2(-1.4426950408889634f * c1)));
            }
            return make_uint4(w4[0], w4[1], w4[2], w4[3]);
        };
        {
            uint4 v = silu4(ca0);
            sts128(sb + OFF_VA + (tid / 80) * VEC_STRIDE + (tid % 80) * 16, v);
            if (tid < 64) { v = silu4(ca1); sts128(sb + OFF_VA + 3 * VEC_STRIDE + (16 + tid) * 16, v); }
        }
        if (warp < 4) {
            float s = 0.f, q = 0.f;
            const float pv = __shfl_sync(0xffffffffu, bf_lo(xs[0].x), 0);
#pragma unroll
            for (int i = 0; i < 3; i++) if (i < 2 || lane < 16) acc_stats(xs[i], pv, s, q);
#pragma unroll
            for (int of = 16; of > 0; of >>= 1) { s += __shfl_xor_sync(0xffffffffu, s, of); q += __shfl_xor_sync(0xffffffffu, q, of); }
            uint32_t m2; float rden;
            ln_finish(pv, s, q, m2, rden);
            if (lane == 0) { sts32(sb + OFF_STAT + warp * 8, m2); sts_f32(sb + OFF_STAT + warp * 8 + 4, rden); }
        } else if (warp == 4) {
            sts32(sb + OWN_X + lane * 4, bf2_add(own0, 0u));
            sts_f32(sb + OWN_B1 + lane * 4, bf2f(own2));
        }
    }
    bar_cons();
    PROF(24);
    uint32_t qf[8][2];
    float o[8][4];
#pragma unroll
    for (int c = 0; c < 8; c++) { o[c][0] = o[c][1] = o[c][2] = o[c][3] = 0.f; }
    float m_run = -INFINITY, l_run = 0.f;
    const bool diag = (t4 == (g >> 1));
    const bool odd = g & 1;
    const uint32_t koff = (warp & 3) * 4096 + (r8 + 8 * (mi & 1)) * 256 + (mi >> 1) * 128 + (r8 << 4);
    const uint32_t voff = TILE_BYTES + (warp & 3) * 4096 + (r8 + 8 * (mi >> 1)) * 256 + (mi & 1) * 128 + (r8 << 4);
    const int src0 = (2 * t4) * 4 + t4, src1 = (2 * t4 + 1) * 4 + t4;
#pragma unroll 1
    for (int step = crit ? 0 : 1; step < 3; step++) {
        if (step < 2 || late) {
            if (step == 1) {
                if (!crit) mbar_wait(bar_wq, 0);
                const uint32_t m2 = lds32(sb + OFF_STAT + (tid & 3) * 8);
                const float rden = lds_f32(sb + OFF_STAT + (tid & 3) * 8 + 4);
                uint4 v[4];
                v[2] = v[3] = make_uint4(1, 1, 1, 1);
                const uint32_t* const p0 = mod_slot(0, tid >> 2, tid & 3);
                while ((int)(gtime32() - t_start) < MOD_T) { }
                PROF(2);
#pragma unroll 1
                for (int it = 0;; it++) {
                    ldg_relaxed_if(tid < 64, v[2], p0 + 16 * 64);
                    ldg_relaxed_if(tid < 64, v[3], p0 + 36 * 64);
                    v[0] = ldg_relaxed(p0);
                    v[1] = ldg_relaxed(p0 + 20 * 64);
                    if (__all_sync(0xffffffffu, min(min(min4(v[0]), min4(v[1])), min(min4(v[2]), min4(v[3]))) != 0u)) break;
                    if (it > SPIN_LIMIT) __trap();
                }
#pragma unroll
                for (int i = 0; i < 4; i++) v[i] = inv4(v[i]);
                PROF(3);
                uint4 h0 = ln_mod4(xa, v[1], v[0], m2, rden);
                sts128(sb + OFF_VB + (tid & 3) * VEC_STRIDE + (tid >> 2) * 16, h0);
                if (tid < 64) {
                    h0 = ln_mod4(xb, v[3], v[2], m2, rden);
                    sts128(sb + OFF_VB + (tid & 3) * VEC_STRIDE + (64 + (tid >> 2)) * 16, h0);
                }
            }
            mbar_wait(step == 1 ? bar_wq : bar_wm, 0);
            bar_cons();
            const uint32_t strip = sb + (step == 1 ? X_WQ : X_WM), vec = sb + (step == 1 ? OFF_VB : OFF_VA);
            float acc[2][4];
#pragma unroll
            for (int m = 0; m < 2; m++) { acc[m][0] = acc[m][1] = acc[m][2] = acc[m][3] = 0.f; }
#pragma unroll
            for (int i = 0; i < 5; i++) {
                int k0 = (warp * 5 + i) * 16;
                uint32_t b0, b1;
                load_bfrag(vec, VEC_STRIDE, k0, g, t4, b0, b1);
                int krow = k0 + r8 + 8 * (mi >> 1);
#pragma unroll
                for (int m = 0; m < 2; m++) {
                    uint32_t a[4];
                    int ch = 2 * m + (mi & 1);
                    ldsm4t(a, strip + krow * 64 + ((ch ^ ((krow >> 1) & 3)) << 4));
                    mma16816(acc[m], a, b0, b1);
                }
            }
            if (t4 < 2) {
#pragma unroll
                for (int m = 0; m < 2; m++) {
                    sts_f32x2(sb + OFF_RED + ((warp * 32 + m * 16 + g) * 4 + 2 * t4) * 4, acc[m][0], acc[m][1]);
                    sts_f32x2(sb + OFF_RED + ((warp * 32 + m * 16 + g + 8) * 4 + 2 * t4) * 4, acc[m][2], acc[m][3]);
                }
            }
            bar_cons();
            if (tid < 64) {
                float v0 = 0.f, v1 = 0.f;
#pragma unroll
                for (int w = 0; w < 8; w++) {
                    v0 += lds_f32(sb + OFF_RED + (w * 128 + (tid & 15) * 8 + (tid >> 4)) * 4);
                    v1 += lds_f32(sb + OFF_RED + (w * 128 + (tid & 15) * 8 + 4 + (tid >> 4)) * 4);
                }
                stg_relaxed(step == 1 ? g_q + (((cta & ~3) + (tid >> 4)) * 4 + bown) * 32 + (tid & 15) : g_mod + mc * 64 + tid, ~pack_bf(v0, v1));
            }
        }
        if (step == 0) continue;
        if (step == 1) {
            if (warp == 0) {
                { const uint32_t c0 = clock32(); while (clock32() - c0 < Q_PAUSE) { } }
                uint4 v = poll1(g_q + (cta * 4 + ((lane >> 2) & 3)) * 32 + (lane & 3) * 4, lane < 16);
                if (lane < 16) {
                    sts128(sb + OFF_Q + lane * 16, v);
                    stg_zero4(g_q + (cta * 4 + (lane >> 2)) * 32 + (lane & 3) * 4);
                }
            }
            bar_cons();
            PROF(4);

#pragma unroll
            for (int c = 0; c < 8; c++) {
                qf[c][0] = lds32(sb + OFF_Q + (((c ^ g) * 4 + t4) << 2));
                qf[c][1] = lds32(sb + OFF_Q + 128 + (((c ^ g) * 4 + t4) << 2));
            }
        } else {
            bar_cons();
            if (tid == 0) mbar_arrive(bar_xfree);
        }
#pragma unroll 1
        for (int j = (step == 1 ? 0 : SEG_J) + (warp >> 2); j < (step == 1 ? SEG_J : NITEM / 2 - 2); j += 2) {
            const int s = (2 * j) & (NS - 1);
            const uint32_t par = (j >> 2) & 1;
            mbar_wait(bar_full + s * 8, par);
            if (tid == 0 && 2 * j >= PH_FIRST && (j & 3) == 0) {
                const int x = min(max((int)(gtime32() - t_start) - 2 * j * PACE_TAU, 0), 65535);
                asm volatile("red.relaxed.gpu.global.add.u32 [%0], %1;" ::"l"(g_phase + (j >> 2) * 32), "r"((1u << 24) + (x >> 2)) : "memory");
            }
            const uint32_t base = sb + OFF_RING + s * TILE_BYTES;
            float sa[4] = {0.f, 0.f, 0.f, 0.f}, sb2[4] = {0.f, 0.f, 0.f, 0.f};
#pragma unroll
            for (int c = 0; c < 8; c += 2) {
                uint32_t a[4], a2[4];
                ldsm4(a, (base + koff) ^ (c << 4));
                ldsm4(a2, (base + koff) ^ ((c + 1) << 4));
                mma16816(sa, a, qf[c][0], qf[c][1]);
                mma16816(sb2, a2, qf[c + 1][0], qf[c + 1][1]);
            }
            const uint32_t sw = pack_bf(odd ? sa[1] + sb2[1] : sa[0] + sb2[0], odd ? sa[3] + sb2[3] : sa[2] + sb2[2]);
            const uint32_t sv = pack_bf(bf_lo(sw) * 0.08838834764831845f, bf_hi(sw) * 0.08838834764831845f);
            const float s0 = bf_lo(sv) * 1.4426950408889634f, s1 = bf_hi(sv) * 1.4426950408889634f;
            float m_new = fmaxf(m_run, fmaxf(s0, s1));
            const bool grow = __any_sync(0xffffffffu, (diag && (m_new > m_run)));
            if (lane == 0) mbar_arrive(bar_empty + s * 8);
            if (grow) {
                float al = ex2(m_run - m_new);
                float a0 = __shfl_sync(0xffffffffu, al, src0), a1 = __shfl_sync(0xffffffffu, al, src1);
#pragma unroll
                for (int c = 0; c < 8; c++) { o[c][0] *= a0; o[c][1] *= a1; o[c][2] *= a0; o[c][3] *= a1; }
                l_run *= al;
                m_run = m_new;
            }
            uint32_t pw = pack_bf(ex2(s0 - m_run), ex2(s1 - m_run));
            l_run += bf_lo(pw) + bf_hi(pw);
            uint32_t b0 = odd ? (pw << 16) : (pw & 0xffffu);
            uint32_t b1 = odd ? (pw & 0xffff0000u) : (pw >> 16);
            if (!diag) { b0 = 0u; b1 = 0u; }
            mbar_wait(bar_full + (s + 1) * 8, par);
#pragma unroll
            for (int c = 0; c < 8; c++) {
                uint32_t a[4];
                ldsm4t(a, (base + voff) ^ (c << 4));
                mma16816(o[c], a, b0, b1);
            }
            __syncwarp();
            if (lane == 0) mbar_arrive(bar_empty + (s + 1) * 8);
        }
    }
    PROF(5);
    float acc[4][4];
    uint32_t pa[8][2];
    float rinv;
    {
        const int s = 4 + (warp >> 2);
        mbar_wait(bar_full + s * 8, 1);
        const uint32_t base = sb + OFF_RING + s * TILE_BYTES;
        float sa[4] = {0.f, 0.f, 0.f, 0.f}, sb2[4] = {0.f, 0.f, 0.f, 0.f};
#pragma unroll
        for (int c = 0; c < 8; c += 2) {
            uint32_t a[4], a2[4];
            ldsm4(a, (base + koff) ^ (c << 4));
            ldsm4(a2, (base + koff) ^ ((c + 1) << 4));
            mma16816(sa, a, qf[c][0], qf[c][1]);
            mma16816(sb2, a2, qf[c + 1][0], qf[c + 1][1]);
        }
        const uint32_t sw = pack_bf(odd ? sa[1] + sb2[1] : sa[0] + sb2[0], odd ? sa[3] + sb2[3] : sa[2] + sb2[2]);
        const uint32_t sv = pack_bf(bf_lo(sw) * 0.08838834764831845f, bf_hi(sw) * 0.08838834764831845f);
        const float s0 = bf_lo(sv) * 1.4426950408889634f, s1 = bf_hi(sv) * 1.4426950408889634f;
        int mi_ = __float_as_int(diag ? fmaxf(m_run, fmaxf(s0, s1)) : -INFINITY);
        mi_ ^= (mi_ >> 31) & 0x7fffffff;
        mi_ = __reduce_max_sync(0xffffffffu, mi_);
        mi_ ^= (mi_ >> 31) & 0x7fffffff;
        if (lane == 0) sts32(sb + OFF_ML + warp * 4, mi_);
        bar_cons();
        const float4 m0 = lds_f32x4(sb + OFF_ML), m1 = lds_f32x4(sb + OFF_ML + 16);
        const float mx = fmaxf(fmaxf(fmaxf(m0.x, m0.y), fmaxf(m0.z, m0.w)), fmaxf(fmaxf(m1.x, m1.y), fmaxf(m1.z, m1.w)));
        const float scl = ex2(m_run - mx);
        const uint32_t pw = pack_bf(ex2(s0 - mx), ex2(s1 - mx));
        if (diag) { sts16(sb + SC_P + (warp * 16 + g) * 2, pw); sts16(sb + SC_P + (warp * 16 + g + 8) * 2, pw >> 16); }
        const float lw = warp_sum(diag ? fmaf(l_run, scl, bf_lo(pw) + bf_hi(pw)) : 0.f);
        const float a0 = __shfl_sync(0xffffffffu, scl, src0), a1 = __shfl_sync(0xffffffffu, scl, src1);
        float v[8], u[8];
#pragma unroll
        for (int c = 0; c < 8; c++) {
            v[c] = a0 * o[c][0] + a1 * o[c ^ 1][1];
            u[c] = a0 * o[c][2] + a1 * o[c ^ 1][3];
        }
#pragma unroll
        for (int c = 0; c < 8; c++) {
            if (!(c & 2)) {
                v[c] += __shfl_xor_sync(0xffffffffu, v[c ^ 2], 1);
                u[c] += __shfl_xor_sync(0xffffffffu, u[c ^ 2], 1);
            }
        }
#pragma unroll
        for (int c = 0; c < 2; c++) {
            v[c] += __shfl_xor_sync(0xffffffffu, v[c ^ 4], 2);
            u[c] += __shfl_xor_sync(0xffffffffu, u[c ^ 4], 2);
        }
        const uint32_t dst = sb + SC_OP + (warp * 128 + 16 * t4 + g) * 4;
        sts_f32(dst, v[0]); sts_f32(dst + 32, v[1]); sts_f32(dst + 256, u[0]); sts_f32(dst + 288, u[1]);
        if (lane == 0) sts_f32(sb + OFF_ML + 32 + warp * 4, lw);
        mbar_wait(bar_help, 0);
        bar_cons();
        const float4 l0 = lds_f32x4(sb + OFF_ML + 32), l1 = lds_f32x4(sb + OFF_ML + 48);
        rinv = rcp_fast(((l0.x + l0.y) + (l0.z + l0.w)) + ((l1.x + l1.y) + (l1.z + l1.w)));
#pragma unroll
        for (int i = 0; i < 4; i++) acc[i][0] = acc[i][1] = acc[i][2] = acc[i][3] = 0.f;
#pragma unroll
        for (int w = 0; w < 8; w++) {
            const float2 x0 = lds_f32x2(sb + SC_OP + (w * 128 + 16 * warp + 2 * t4) * 4), x1 = lds_f32x2(sb + SC_OP + (w * 128 + 16 * warp + 8 + 2 * t4) * 4);
            acc[2 * (w & 1)][0] += x0.x; acc[2 * (w & 1)][1] += x0.y;
            acc[2 * (w & 1) + 1][0] += x1.x; acc[2 * (w & 1) + 1][1] += x1.y;
        }
#pragma unroll
        for (int ks = 0; ks < 8; ks++) { pa[ks][0] = lds32(sb + SC_P + (8 * ks + t4) * 4); pa[ks][1] = lds32(sb + SC_P + (8 * ks + 4 + t4) * 4); }
    }
    PROF(20);
    const int mt = warp < 2 ? warp : warp + 2;
    {
        const uint32_t va = pin(sb + OFF_RING + 6 * TILE_BYTES + (warp >> 2) * (TILE_BYTES / 2) + (8 * (mi & 1) + r8) * 128 + (((2 * (warp & 3) + (mi >> 1)) ^ r8) << 4));
        const uint32_t vbar = pin(bar_v + (warp >> 2) * 8);
        uint32_t* const o_dst = pin(slot(SL_O + (cta >> 4), g) + (cta & 15) * 64 + warp * 8 + 2 * t4);
#pragma unroll
        for (int tl = 0; tl < 2; tl++) {
            mbar_wait(vbar + tl * 16, 0);
            uint32_t r[4][4];
#pragma unroll
            for (int ks = 0; ks < 4; ks++) ldsm4t(r[ks], va + tl * TILE_BYTES + ks * 2048);
#pragma unroll
            for (int ks = 0; ks < 4; ks++) {
                const uint32_t a[4] = {pa[4 * tl + ks][0], 0u, pa[4 * tl + ks][1], 0u};
                mma16816(acc[2 * (ks & 1)], a, r[ks][0], r[ks][1]);
                mma16816(acc[2 * (ks & 1) + 1], a, r[ks][2], r[ks][3]);
            }
        }
        stg_relaxed2_if(g < 2, o_dst, ~pack_bf((acc[0][0] + acc[2][0]) * rinv, (acc[0][1] + acc[2][1]) * rinv),
                        ~pack_bf((acc[1][0] + acc[3][0]) * rinv, (acc[1][1] + acc[3][1]) * rinv));
    }
    PROF(7);
    const int side = lds32(sb + OFF_SIDE);
    const uint32_t red_st = pin(sb + SC_E4 + ((warp * 4 + 2 * ((lane >> 3) & 1) + (lane >> 4)) * 8 + (lane & 7)) * 4);
    const uint32_t red_ld = pin(sb + SC_E4 + (lane & 15) * 8);
    const uint32_t* const in1 = pin(slot(SL_P1 + own, side) + tid * 4);
    const uint32_t* const in2a = pin(slot(SL_P2 + 2 * own, side) + (tid >> 3) * 32 + (tid & 7) * 2);
    const uint32_t* const in2b = pin(slot(SL_P2 + 2 * own + 1, side) + (tid >> 3) * 32 + (tid & 7) * 2);
    uint32_t* const out_dst = pin((uint32_t*)(p.out + ((lane >> 2) & 3) * D + 8 * own) + t4);
    uint32_t* const x1_dst = pin(slot(SL_X1 + own / 30, lane >> 4) + (own % 30) * 32 + (lane & 15));
    uint32_t* const rst = pin(tid >= 32 && tid < 56 ? mod_slot(lane >> 2, own, lane & 3) : own < 32 && tid == 64 ? g_clr + own * 4 : own < 8 && tid == 96 ? g_phase + own * 32 : nullptr);
    const uint32_t xw = lds32(sb + OWN_X + (lane & 15) * 4), ga_w = lds32(sb + OWN_GA + (lane & 15) * 4);
    uint32_t cs[15];
    uint32_t* dst2[5];
    uint32_t w2a[5];
#pragma unroll
    for (int j = 0; j < 10; j++) cs[j] = lds32(sb + OFF_VB + ((g & 1) * 4 + (g >> 1)) * VEC_STRIDE + warp * 160 + t4 * 4 + j * 16);
#pragma unroll
    for (int i = 0; i < 5; i++) {
        cs[10 + i] = lds32(sb + OFF_VB + (g >> 1) * VEC_STRIDE + warp * 160 + (g & 1) * 16 + t4 * 4 + i * 32);
        const uint2 t = lds64(sb + OFF_TAB2 + warp * 40 + i * 8);
        dst2[i] = slot_ptr((t4 < 2 ? t.x : t.y) + g * 8 + (t4 & 1) * 4);
        const int cc = 2 * (warp * 5 + i) + (mi & 1);
        w2a[i] = pin(sb + X_W2 + (cc >> 3) * 4096 + (r8 + 8 * (mi >> 1)) * 128 + (((cc & 7) ^ r8) << 4));
    }
    const uint32_t piv = lds32(sb + OFF_STAT + (g >> 1) * 8);
    const uint32_t* const xin = pin(slot(SL_X1 + warp / 3, side) + ((warp % 3) * 10 + (g & 1)) * 32 + (g >> 1) * 4 + t4);
    const uint32_t w1a = pin(sb + X_W1 + (warp * 80 + r8 + 8 * (mi >> 1)) * 64 + (((mi & 1) ^ ((r8 >> 1) & 3)) << 4));
    const uint32_t w1bar = pin(bar_w1 + (warp >> 1) * 8), w2bar = pin(bar_w2 + (warp + (warp >> 2)) * 8);
    const uint32_t obar = pin(NB_O + warp), hbar = pin((NB_H1 + (warp >> 1)) & 15);
    const uint32_t ab_st = pin(sb + SC_AB + warp * 1024 + lane * 16), y_st = pin(sb + SC_Y + warp * 512 + lane * 8), s_st = pin(sb + SC_ST + (t4 * 8 + warp) * 8);
    const uint32_t h_ld = pin(sb + SC_H1 + ((g & 3) ^ (2 * (f & 1) + ((f >> 1) & 1))) * 64 + t4 * 16);
    {
        const int kap = 2 * (head & 1) + ((head >> 1) & 1);
        const uint32_t wa = pin(sb + X_WO + (mt >> 1) * (DH * 64) + (r8 + 8 * (mi >> 1)) * 64 + ((((mt & 1) * 2 + (mi & 1)) ^ ((r8 >> 1) & 3)) << 4));
        const uint32_t oa = pin(sb + OFF_O + ((g & 3) ^ kap) * O_STRIDE + t4 * 8);
        uint32_t* dst[4];
#pragma unroll
        for (int i = 0; i < 2; i++) {
            const uint2 t = lds64(sb + OFF_TAB1 + (bown * 20 + 2 * mt + (warp < 2 ? 4 * i : 0)) * 4);
            dst[2 * i] = slot_ptr(t.x + g * 16 + t4 * 8);
            dst[2 * i + 1] = slot_ptr(t.y + g * 16 + t4 * 8);
        }
        PROF(6);
        const uint32_t wobar = pin(bar_wo + (mt >> 1) * 8);
        asm volatile("bar.sync %0, 64;" ::"r"(obar) : "memory");
        uint2 ob[8];
#pragma unroll
        for (int ks = 0; ks < 8; ks++) ob[ks] = lds64(oa + ks * 32);
#pragma unroll
        for (int m = 0; m < 2; m++) {
            if (m == 0 || warp < 2) {
                mbar_wait(wobar + m * 8, 0);
                PROF(8);
                uint32_t wf[8][4];
#pragma unroll
                for (int ks = 0; ks < 8; ks++) ldsm4t(wf[ks], wa + m * (DH * 64) + ks * 1024);
                float c[4][4];
#pragma unroll
                for (int ks = 0; ks < 8; ks++) {
                    if (ks < 4) c[ks][0] = c[ks][1] = c[ks][2] = c[ks][3] = 0.f;
                    mma16816(c[ks & 3], wf[ks], ob[ks].x, ob[ks].y);
                }
                stg_relaxed2_if(t4 < 2, dst[2 * m], flag((c[0][0] + c[1][0]) + (c[2][0] + c[3][0])), flag((c[0][1] + c[1][1]) + (c[2][1] + c[3][1])));
                stg_relaxed2_if(t4 < 2, dst[2 * m + 1], flag((c[0][2] + c[1][2]) + (c[2][2] + c[3][2])), flag((c[0][3] + c[1][3]) + (c[2][3] + c[3][3])));
            }
        }
    }
    PROF(9);
    uint32_t x1w = 0;
    if (is_owner) {
        sts_f32(red_st, poll_e4(in1));
        PROF(11);
        nbar_sync<NB_E4, 256>();
        if (warp == 0) {
            float2 a[8];
#pragma unroll
            for (int w = 0; w < 8; w++) a[w] = lds_f32x2(red_ld + w * 128);
            const uint32_t aw = pack_bf(((a[0].x + a[1].x) + (a[2].x + a[3].x)) + ((a[4].x + a[5].x) + (a[6].x + a[7].x)),
                                        ((a[0].y + a[1].y) + (a[2].y + a[3].y)) + ((a[4].y + a[5].y) + (a[6].y + a[7].y)));
            x1w = bf2_add(xw, bf2_mul(ga_w, aw));
            stg_relaxed(x1_dst, x1w ^ 0x80008000u);
            if (lane == 0) mbar_arrive(bar_x1);
        }
        if (rst) stg_zero4(rst);
    }
    PROF(12);
    if (is_f) {
        uint32_t f1[5][2][4], f2[5][2][4];
        uint32_t d[6];
        auto load_x1 = [&] {
#pragma unroll
            for (int i = 0; i < 5; i++) d[i] = ldg_relaxed32(xin + i * 64);
        };
        auto have_x1 = [&] { return __all_sync(0xffffffffu, __vimin3_u32(__vimin3_u32(d[0], d[1], d[2]), d[3], d[4]) != 0u); };
        mbar_wait(w1bar, 0);
        load_x1();
        {
#pragma unroll
            for (int i = 0; i < 5; i++) { ldsm4t(f1[i][0], w1a + i * 1024); ldsm4t(f1[i][1], (w1a ^ 32) + i * 1024); }
            float c[2][4];
#pragma unroll
            for (int m = 0; m < 2; m++) c[m][0] = c[m][1] = c[m][2] = c[m][3] = 0.f;
#pragma unroll
            for (int i = 0; i < 5; i++) { mma16816(c[0], f1[i][0], cs[2 * i], cs[2 * i + 1]); mma16816(c[1], f1[i][1], cs[2 * i], cs[2 * i + 1]); }
#pragma unroll
            for (int i = 0; i < 5; i++) { cs[2 * i] = pin(odd ? 0u : cs[10 + i]); cs[2 * i + 1] = pin(odd ? cs[10 + i] : 0u); }
#pragma unroll
            for (int m = 0; m < 2; m++) sts128(ab_st + m * 512, make_uint4(__float_as_uint(c[m][0]), __float_as_uint(c[m][1]), __float_as_uint(c[m][2]), __float_as_uint(c[m][3])));
            nbar_arrive<NB_AB, 320>();
            d[0] |= __float_as_uint(c[1][3]) & (side >> 1);
        }
        PROF(10);
        if (!have_x1()) {
            asm volatile("{\n.reg .pred q;\n.reg .b32 t, n;\nmov.u32 n, 0;\n"
                         "L_%=:\nld.relaxed.gpu.global.u32 %0, [%5];\nld.relaxed.gpu.global.u32 %1, [%5 + 256];\nld.relaxed.gpu.global.u32 %2, [%5 + 512];\n"
                         "ld.relaxed.gpu.global.u32 %3, [%5 + 768];\nld.relaxed.gpu.global.u32 %4, [%5 + 1024];\n"
                         "add.u32 n, n, 1;\nsetp.gt.u32 q, n, %6;\n@q trap;\nbar.warp.sync 0xffffffff;\n"
                         "min.u32 t, %0, %1;\nmin.u32 t, t, %2;\nmin.u32 t, t, %3;\nmin.u32 t, t, %4;\n"
                         "setp.ne.u32 q, t, 0;\nvote.sync.all.pred q, q, 0xffffffff;\n@!q bra.uni L_%=;\n}"
                         : "=&r"(d[0]), "=&r"(d[1]), "=&r"(d[2]), "=&r"(d[3]), "=&r"(d[4]) : "l"(xin), "n"(SPIN_LIMIT) : "memory");
        }
        PROF(13);
        {
            float y[2][4], st[4] = {0.f, 0.f, 0.f, 0.f};
            float z[2][4] = {};
#pragma unroll
            for (int m = 0; m < 2; m++) y[m][0] = y[m][1] = y[m][2] = y[m][3] = 0.f;
#pragma unroll
            for (int i = 0; i < 5; i++) d[i] = bf2_add(d[i], piv);
            d[5] = 0u;
#pragma unroll
            for (int i = 0; i < 5; i++) {
                if (i < 3) {
                    const uint32_t a[4] = {d[2 * i], 0x3f803f80u, d[2 * i + 1], 0x3f803f80u};
                    mma16816(st, a, d[2 * i], d[2 * i + 1]);
                }
                const uint32_t y0 = bf2_mul(d[i], cs[2 * i]), y1 = bf2_mul(d[i], cs[2 * i + 1]);
                if (i & 1) { mma16816(z[0], f1[i][0], y0, y1); mma16816(z[1], f1[i][1], y0, y1); }
                else { mma16816(y[0], f1[i][0], y0, y1); mma16816(y[1], f1[i][1], y0, y1); }
            }
            const float q = odd ? st[1] : st[0];
            const float q2 = q + __shfl_xor_sync(0xffffffffu, q, 4);
            if (diag && !odd) sts_f32x2(s_st, q2, st[2] + st[3]);
#pragma unroll
            for (int m = 0; m < 2; m++) sts_f32x2(y_st + m * 256, (z[m][0] + z[m][1]) + (y[m][0] + y[m][1]), (z[m][2] + z[m][3]) + (y[m][2] + y[m][3]));
        }
        nbar_arrive<NB_Y, 320>();
        PROF(14);
        mbar_wait(w2bar, 0);
        mbar_wait(w2bar + 8, 0);
#pragma unroll
        for (int i = 0; i < 5; i++) { ldsm4t(f2[i][0], w2a[i]); ldsm4t(f2[i][1], w2a[i] + 2048); }
        asm volatile("bar.sync %0, 128;" ::"r"(hbar) : "memory");
        PROF(15);
        {
            const uint4 hb = lds128(h_ld);
            float c[5][4];
#pragma unroll
            for (int i = 0; i < 5; i++) { c[i][0] = c[i][1] = c[i][2] = c[i][3] = 0.f; mma16816(c[i], f2[i][0], hb.x, hb.y); }
#pragma unroll
            for (int i = 0; i < 5; i++) {
                mma16816(c[i], f2[i][1], hb.z, hb.w);
                stg_relaxed(dst2[i], ~pack_bf(t4 < 2 ? c[i][0] : c[i][2], t4 < 2 ? c[i][1] : c[i][3]));
            }
        }
    }
    PROF(16);
    if (is_owner) {
        const uint32_t b2w = lds32(sb + OWN_B2 + (lane & 15) * 4), gb_ld = pin(sb + OWN_GB + (lane & 15) * 8);
        sts_f32(red_st + (SC_E6 - SC_E4), poll_e6(in2a, in2b, tid < NF * 8 - 256));
        PROF(17);
        if (warp != 0) {
            nbar_arrive<NB_E6, 320>();
        } else {
            nbar_sync<NB_E6, 320>();
            float2 a[8];
#pragma unroll
            for (int i = 0; i < 8; i++) a[i] = lds_f32x2(red_ld + (SC_E6 - SC_E4) + i * 128);
            const float2 g0 = lds_f32x2(gb_ld), g1 = lds_f32x2(gb_ld + 128);
            const uint32_t gb_w = pack_bf(g0.x + g1.x, g0.y + g1.y);
            const uint32_t aw = pack_bf(((a[0].x + a[1].x) + (a[2].x + a[3].x)) + ((a[4].x + a[5].x) + (a[6].x + a[7].x)),
                                        ((a[0].y + a[1].y) + (a[2].y + a[3].y)) + ((a[4].y + a[5].y) + (a[6].y + a[7].y)));
            x1w = bf2_add(x1w, bf2_mul(gb_w, bf2_add(aw, b2w)));
            if (lane < 16) asm volatile("st.global.u32 [%0], %1;" ::"l"(out_dst), "r"(x1w) : "memory");
        }
    }
    PROF(18);
    PROF_DUMP;
}

typedef CUresult (*EncodeFn)(CUtensorMap*, CUtensorMapDataType, cuuint32_t, void*, const cuuint64_t*, const cuuint64_t*, const cuuint32_t*,
                             const cuuint32_t*, CUtensorMapInterleave, CUtensorMapSwizzle, CUtensorMapL2promotion, CUtensorMapFloatOOBfill);

static CUtensorMap make_map(EncodeFn enc, const void* ptr, int cols, int rows, int box_cols, int box_rows, CUtensorMapSwizzle sw,
                            CUtensorMapL2promotion promo = CU_TENSOR_MAP_L2_PROMOTION_NONE) {
    CUtensorMap m;
    cuuint64_t dims[2] = {(cuuint64_t)cols, (cuuint64_t)rows};
    cuuint64_t strides[1] = {(cuuint64_t)cols * 2};
    cuuint32_t box[2] = {(cuuint32_t)box_cols, (cuuint32_t)box_rows};
    cuuint32_t es[2] = {1, 1};
    enc(&m, CU_TENSOR_MAP_DATA_TYPE_BFLOAT16, 2, const_cast<void*>(ptr), dims, strides, box, es, CU_TENSOR_MAP_INTERLEAVE_NONE, sw,
        promo, CU_TENSOR_MAP_FLOAT_OOB_FILL_NONE);
    return m;
}

}

extern "C" void kernel_launch(void* const* d_in, const int* in_sizes, int n_in, void* d_out, int out_size) {
    (void)in_sizes; (void)n_in; (void)out_size;
    static EncodeFn enc = nullptr;
    if (!enc) {
        void* fn = nullptr;
        cudaDriverEntryPointQueryResult qr;
        cudaGetDriverEntryPoint("cuTensorMapEncodeTiled", &fn, cudaEnableDefault, &qr);
        enc = (EncodeFn)fn;
        cudaFuncSetAttribute(fused_kernel, cudaFuncAttributeMaxDynamicSharedMemorySize, SMEM_BYTES);
    }
    Params p;
    p.x = (const __nv_bfloat16*)d_in[0];
    p.kc = (const __nv_bfloat16*)d_in[1];
    p.vc = (const __nv_bfloat16*)d_in[2];
    p.b1 = (const __nv_bfloat16*)d_in[7];
    p.b2 = (const __nv_bfloat16*)d_in[9];
    p.c = (const __nv_bfloat16*)d_in[10];
    p.out = (__nv_bfloat16*)d_out;
    CUtensorMap tm_wmod = make_map(enc, d_in[11], NMOD, D, 32, 160, CU_TENSOR_MAP_SWIZZLE_64B, CU_TENSOR_MAP_L2_PROMOTION_L2_128B);
    CUtensorMap tm_wq = make_map(enc, d_in[3], NH * DH, D, 32, 160, CU_TENSOR_MAP_SWIZZLE_64B, CU_TENSOR_MAP_L2_PROMOTION_L2_128B);
    CUtensorMap tm_wo = make_map(enc, d_in[4], D, NH * DH, 32, 128, CU_TENSOR_MAP_SWIZZLE_64B);
    CUtensorMap tm_w1 = make_map(enc, d_in[6], FF, D, 32, 160, CU_TENSOR_MAP_SWIZZLE_64B);
    CUtensorMap tm_w2 = make_map(enc, d_in[8], D, FF, 64, 32, CU_TENSOR_MAP_SWIZZLE_128B);
    CUtensorMap tm_v = make_map(enc, d_in[2], DH, NB * NH * SK, 64, TILE_KEYS, CU_TENSOR_MAP_SWIZZLE_128B);
    CUtensorMap tm_gb = make_map(enc, d_in[11], NMOD, D, 8, 160, CU_TENSOR_MAP_SWIZZLE_NONE, CU_TENSOR_MAP_L2_PROMOTION_L2_128B);
    fused_kernel<<<NCTA, NTHREADS, SMEM_BYTES>>>(p, tm_wmod, tm_wq, tm_wo, tm_w1, tm_w2, tm_v, tm_gb);
}
```

```cpp
#include <cuda_runtime.h>
#include <cuda.h>
#include <cuda_bf16.h>
#include <stdint.h>
#include <stdlib.h>

namespace {

constexpr int NB = 4, D = 640, NH = 32, DH = 128, SK = 8192, WIN = 2048, FF = 1728, NMOD = 6 * D;
constexpr int NCTA = 128;
constexpr int NOWN = 80;
constexpr int NF = 54;
constexpr int NTHREADS = 320;
constexpr int TILE_KEYS = 64;
constexpr int TILE_BYTES = TILE_KEYS * DH * 2;
constexpr int NITEM = 2 * WIN / TILE_KEYS;
constexpr int NS = 8;
constexpr int NMODC = 120;
constexpr int SPIN_LIMIT = 1 << 18;
#define INFLIGHT 3
#define WQ_DELAY 500
#define MOD_T 4200
#define Q_PAUSE 1100
#define PACE_A 7500
#define PACE_TAU 635
#define ROT(c) 0
#define PF_END 16
#define PH_FIRST 24
#define PH_LAG 5
#define LAT_T 2300
#define WO_T -1050
#define WO_S 250
#define W1_T 860
#define W2_T 1560
#define GB_T 2350
#define GB_EV 700
#define CLR_CHECK 28000
constexpr int NPROBE = 8, PROBE_END = 10000;
constexpr int SEG_J = 8;

constexpr int OFF_RING = 0;
constexpr int OFF_X = OFF_RING + NS * TILE_BYTES;
constexpr int X_WM = OFF_X;
constexpr int X_WQ = OFF_X + D * 64;
constexpr int X_WO = OFF_X;
constexpr int X_W1 = X_WO + 5 * DH * 64;
constexpr int X_END = X_W1 + D * 64;
constexpr int X_W2 = OFF_RING;
constexpr int X_GB = OFF_RING + 3 * TILE_BYTES;
static_assert(X_WQ + D * 64 <= X_END, "prologue weights must fit");
constexpr int VEC_STRIDE = 1296;
constexpr int OFF_VA = X_END;
constexpr int OFF_VB = OFF_VA + 4 * VEC_STRIDE;
constexpr int OFF_RED = OFF_VB + 4 * VEC_STRIDE;
constexpr int OFF_ML = OFF_RED + 4 * VEC_STRIDE;
constexpr int O_STRIDE = 288;
constexpr int OFF_O = OFF_ML + 64;
constexpr int OFF_Q = OFF_O + 4 * O_STRIDE;
constexpr int OFF_OWN = OFF_Q + 256;
constexpr int OWN_X = OFF_OWN, OWN_B2 = OWN_X + 64, OWN_GA = OWN_B2 + 64, OWN_GB = OWN_GA + 64, OWN_B1 = OWN_GB + 256;
constexpr int OFF_STAT = OWN_B1 + 128;
constexpr int OFF_TAB1 = OFF_STAT + 32;
constexpr int OFF_TAB2 = OFF_TAB1 + NOWN * 4;
constexpr int OFF_SIDE = OFF_TAB2 + NOWN * 4;
constexpr int OFF_BAR = OFF_SIDE + 8;
constexpr int NBAR = 2 * NS + 32;
constexpr int SMEM_BYTES = OFF_BAR + NBAR * 8;
constexpr int SC_OP = OFF_RING + 4 * TILE_BYTES;
constexpr int SC_AB = SC_OP + 4096;
constexpr int SC_Y = SC_AB + 8192;
constexpr int SC_ST = SC_Y + 4096;
constexpr int SC_E4 = SC_ST + 256;
constexpr int SC_E6 = SC_E4 + 1024;
constexpr int SC_P = SC_E6 + 1024;
constexpr int SC_H1 = SC_P + 256;
constexpr int SC_DUMP = SC_H1 + 256;
static_assert(SMEM_BYTES <= 232448, "smem");
static_assert(OFF_BAR % 8 == 0 && OFF_X % 1024 == 0 && X_WQ % 512 == 0 && X_W1 % 512 == 0 && OFF_VA % 16 == 0 && OFF_RED % 16 == 0 && OFF_ML % 16 == 0 && OFF_O % 16 == 0 && OFF_Q % 16 == 0, "align");
constexpr int NB_O = 2  , NB_E4 = 10, NB_E6 = 11, NB_AB = 12, NB_Y = 13, NB_H1 = 14  ;

__device__ __align__(128) uint32_t g_mod[NMODC * 64];
__device__ __align__(128) uint32_t g_q[NCTA * 128];
__device__ __align__(128) uint32_t g_clr[NCTA];
__device__ __align__(128) uint32_t g_phase[8 * 32];
constexpr int SL_P1 = 0;
constexpr int SL_P2 = SL_P1 + NOWN;
constexpr int SL_O = SL_P2 + 2 * NOWN;
constexpr int SL_X1 = SL_O + 8;
constexpr int SL_SIDE = SL_X1 + 3;
static_assert(SL_SIDE < 256, "one 2 MB page");
__device__ uint32_t g_slots[2 * 256 * 2048];
__device__ __forceinline__ uint32_t* slot(int i, int side) {
    const size_t base = ((size_t)g_slots + 0x1fffff) & ~(size_t)0x1fffff;
    return (uint32_t*)base + i * 2048 + (((__popc(i & 0x59) ^ side) & 1) << 10);
}
#define PROF_DECL
#define HPROF(i) do { } while (0)
#define PROF(i) do { } while (0)
#define PROF_DUMP do { } while (0)

__device__ __forceinline__ uint32_t smem_u32(const void* p) { return (uint32_t)__cvta_generic_to_shared(p); }
__device__ __forceinline__ void mbar_init(uint32_t bar, uint32_t cnt) { asm volatile("mbarrier.init.shared::cta.b64 [%0], %1;" ::"r"(bar), "r"(cnt) : "memory"); }
__device__ __forceinline__ void mbar_expect_tx(uint32_t bar, uint32_t bytes) { asm volatile("mbarrier.arrive.expect_tx.shared::cta.b64 _, [%0], %1;" ::"r"(bar), "r"(bytes) : "memory"); }
__device__ __forceinline__ void mbar_arrive(uint32_t bar) { asm volatile("mbarrier.arrive.shared::cta.b64 _, [%0];" ::"r"(bar) : "memory"); }
__device__ __forceinline__ void mbar_wait(uint32_t bar, uint32_t parity) {
    uint32_t ok;
    int it = 0;
    while (true) {
        asm volatile("{\n.reg .pred p;\nmbarrier.try_wait.parity.shared::cta.b64 p, [%1], %2;\nselp.u32 %0, 1, 0, p;\n}" : "=r"(ok) : "r"(bar), "r"(parity) : "memory");
        if (ok) break;
        if (++it > SPIN_LIMIT) __trap();
    }
}
__device__ __forceinline__ void bulk_load(uint32_t dst, const void* src, uint32_t bytes, uint32_t bar, uint64_t pol) {
    asm volatile("cp.async.bulk.shared::cluster.global.mbarrier::complete_tx::bytes.L2::cache_hint [%0], [%1], %2, [%3], %4;"
                 ::"r"(dst), "l"(src), "r"(bytes), "r"(bar), "l"(pol) : "memory");
}
__device__ __forceinline__ void bar_cons() { asm volatile("bar.sync 1, 256;" ::: "memory"); }
template <int ID, int N> __device__ __forceinline__ void nbar_sync() { asm volatile("bar.sync %0, %1;" ::"n"(ID), "n"(N) : "memory"); }
template <int ID, int N> __device__ __forceinline__ void nbar_arrive() { asm volatile("bar.arrive %0, %1;" ::"n"(ID), "n"(N) : "memory"); }
__device__ __forceinline__ bool mbar_test(uint32_t bar, uint32_t parity) {
    uint32_t ok;
    asm volatile("{\n.reg .pred p;\nmbarrier.test_wait.parity.shared::cta.b64 p, [%1], %2;\nselp.u32 %0, 1, 0, p;\n}" : "=r"(ok) : "r"(bar), "r"(parity) : "memory");
    return ok;
}
__device__ __forceinline__ uint32_t pin(uint32_t v) { asm volatile("" : "+r"(v)); return v; }
template <class T> __device__ __forceinline__ T pin_hard(T v) { return __shfl_sync(0xffffffffu, v, threadIdx.x & 31); }
template <class T> __device__ __forceinline__ T* pin(T* v) { asm volatile("" : "+l"(v)); return v; }
__device__ __forceinline__ void ldsm4(uint32_t (&a)[4], uint32_t addr) {
    asm volatile("ldmatrix.sync.aligned.m8n8.x4.shared.b16 {%0,%1,%2,%3}, [%4];" : "=r"(a[0]), "=r"(a[1]), "=r"(a[2]), "=r"(a[3]) : "r"(addr) : "memory");
}
__device__ __forceinline__ void ldsm4t(uint32_t (&a)[4], uint32_t addr) {
    asm volatile("ldmatrix.sync.aligned.m8n8.x4.trans.shared.b16 {%0,%1,%2,%3}, [%4];" : "=r"(a[0]), "=r"(a[1]), "=r"(a[2]), "=r"(a[3]) : "r"(addr) : "memory");
}
__device__ __forceinline__ void mma16816(float (&c)[4], const uint32_t (&a)[4], uint32_t b0, uint32_t b1) {
    asm volatile("mma.sync.aligned.m16n8k16.row.col.f32.bf16.bf16.f32 {%0,%1,%2,%3}, {%4,%5,%6,%7}, {%8,%9}, {%0,%1,%2,%3};"
                 : "+f"(c[0]), "+f"(c[1]), "+f"(c[2]), "+f"(c[3]) : "r"(a[0]), "r"(a[1]), "r"(a[2]), "r"(a[3]), "r"(b0), "r"(b1));
}
__device__ __forceinline__ uint32_t lds32(uint32_t addr) { uint32_t v; asm volatile("ld.shared.u32 %0, [%1];" : "=r"(v) : "r"(addr) : "memory"); return v; }
__device__ __forceinline__ float lds_f32(uint32_t addr) { float v; asm volatile("ld.shared.f32 %0, [%1];" : "=f"(v) : "r"(addr) : "memory"); return v; }
__device__ __forceinline__ float2 lds_f32x2(uint32_t addr) { float2 v; asm volatile("ld.shared.v2.f32 {%0,%1}, [%2];" : "=f"(v.x), "=f"(v.y) : "r"(addr) : "memory"); return v; }
__device__ __forceinline__ float4 lds_f32x4(uint32_t addr) { float4 v; asm volatile("ld.shared.v4.f32 {%0,%1,%2,%3}, [%4];" : "=f"(v.x), "=f"(v.y), "=f"(v.z), "=f"(v.w) : "r"(addr) : "memory"); return v; }
__device__ __forceinline__ uint2 lds64(uint32_t addr) { uint2 v; asm volatile("ld.shared.v2.u32 {%0,%1}, [%2];" : "=r"(v.x), "=r"(v.y) : "r"(addr) : "memory"); return v; }
__device__ __forceinline__ uint4 lds128(uint32_t addr) { uint4 v; asm volatile("ld.shared.v4.u32 {%0,%1,%2,%3}, [%4];" : "=r"(v.x), "=r"(v.y), "=r"(v.z), "=r"(v.w) : "r"(addr) : "memory"); return v; }
__device__ __forceinline__ void sts16(uint32_t addr, uint32_t v) { asm volatile("st.shared.b16 [%0], %1;" ::"r"(addr), "h"((unsigned short)v) : "memory"); }
__device__ __forceinline__ void sts32(uint32_t addr, uint32_t v) { asm volatile("st.shared.u32 [%0], %1;" ::"r"(addr), "r"(v) : "memory"); }
__device__ __forceinline__ void sts_f32(uint32_t addr, float v) { asm volatile("st.shared.f32 [%0], %1;" ::"r"(addr), "f"(v) : "memory"); }
__device__ __forceinline__ void sts_f32x2(uint32_t addr, float a, float b) { asm volatile("st.shared.v2.f32 [%0], {%1,%2};" ::"r"(addr), "f"(a), "f"(b) : "memory"); }
__device__ __forceinline__ void sts128(uint32_t addr, uint4 v) { asm volatile("st.shared.v4.u32 [%0], {%1,%2,%3,%4};" ::"r"(addr), "r"(v.x), "r"(v.y), "r"(v.z), "r"(v.w) : "memory"); }
__device__ __forceinline__ uint4 ldg_relaxed(const uint32_t* p) {
    uint4 v;
    asm volatile("ld.relaxed.gpu.global.v4.u32 {%0,%1,%2,%3}, [%4];" : "=r"(v.x), "=r"(v.y), "=r"(v.z), "=r"(v.w) : "l"(p) : "memory");
    return v;
}
__device__ __forceinline__ void ldg_relaxed_if(bool on, uint4& v, const uint32_t* p) {
    asm volatile("{\n.reg .pred q;\nsetp.ne.u32 q, %5, 0;\n@q ld.relaxed.gpu.global.v4.u32 {%0,%1,%2,%3}, [%4];\n}"
                 : "+r"(v.x), "+r"(v.y), "+r"(v.z), "+r"(v.w) : "l"(p), "r"((uint32_t)on) : "memory");
}
__device__ __forceinline__ void stg_relaxed2_if(bool on, uint32_t* p, uint32_t a, uint32_t b) {
    asm volatile("{\n.reg .pred q;\nsetp.ne.u32 q, %3, 0;\n@q st.relaxed.gpu.global.v2.u32 [%0], {%1,%2};\n}" ::"l"(p), "r"(a), "r"(b), "r"((uint32_t)on) : "memory");
}
__device__ __forceinline__ uint32_t ldg_relaxed32(const uint32_t* p) { uint32_t v; asm volatile("ld.relaxed.gpu.global.u32 %0, [%1];" : "=r"(v) : "l"(p) : "memory"); return v; }
__device__ __forceinline__ void stg_relaxed(uint32_t* p, uint32_t v) { asm volatile("st.relaxed.gpu.global.u32 [%0], %1;" ::"l"(p), "r"(v) : "memory"); }
__device__ __forceinline__ void stg_zero4(uint32_t* p) { asm volatile("st.relaxed.gpu.global.v4.u32 [%0], {%1,%1,%1,%1};" ::"l"(p), "r"(0u) : "memory"); }
__device__ __forceinline__ bool ready(const uint4& v) { return (v.x != 0u) & (v.y != 0u) & (v.z != 0u) & (v.w != 0u); }
__device__ __forceinline__ uint32_t min4(const uint4& v) { return min(__vimin3_u32(v.x, v.y, v.z), v.w); }
__device__ __forceinline__ uint4 inv4(const uint4& v) { return make_uint4(~v.x, ~v.y, ~v.z, ~v.w); }
__device__ __forceinline__ uint32_t pack_bf(float lo, float hi) {
    uint32_t r;
    asm("cvt.rn.bf16x2.f32 %0, %1, %2;" : "=r"(r) : "f"(hi), "f"(lo));
    return r;
}
__device__ __forceinline__ float bfr(float x) { return __uint_as_float(pack_bf(0.f, x) & 0xffff0000u); }
__device__ __forceinline__ float bf_lo(uint32_t w) { return __uint_as_float(w << 16); }
__device__ __forceinline__ float bf_hi(uint32_t w) { return __uint_as_float(w & 0xffff0000u); }
__device__ __forceinline__ float bf2f(__nv_bfloat16 v) { return __bfloat162float(v); }
__device__ __forceinline__ float ex2(float x) { float y; asm("ex2.approx.ftz.f32 %0, %1;" : "=f"(y) : "f"(x)); return y; }
__device__ __forceinline__ float rcp_fast(float x) { float y; asm("rcp.approx.ftz.f32 %0, %1;" : "=f"(y) : "f"(x)); return y; }
__device__ __forceinline__ float rsqrt_fast(float x) { float y; asm("rsqrt.approx.ftz.f32 %0, %1;" : "=f"(y) : "f"(x)); return y; }
__device__ __forceinline__ float sqrt_fast(float x) { float y; asm("sqrt.approx.f32 %0, %1;" : "=f"(y) : "f"(x)); return y; }
__device__ __forceinline__ uint32_t bf2_add(uint32_t a, uint32_t b) { uint32_t r; asm("add.rn.bf16x2 %0, %1, %2;" : "=r"(r) : "r"(a), "r"(b)); return r; }
__device__ __forceinline__ uint32_t bf2_sub(uint32_t a, uint32_t b) { uint32_t r; asm("sub.rn.bf16x2 %0, %1, %2;" : "=r"(r) : "r"(a), "r"(b)); return r; }
__device__ __forceinline__ uint32_t bf2_mul(uint32_t a, uint32_t b) { uint32_t r; asm("mul.rn.bf16x2 %0, %1, %2;" : "=r"(r) : "r"(a), "r"(b)); return r; }
__device__ __forceinline__ uint32_t gtime32() { uint32_t c; asm volatile("mov.u32 %0, %%globaltimer_lo;" : "=r"(c)); return c; }
__device__ __forceinline__ uint32_t clock32() { uint32_t c; asm volatile("mov.u32 %0, %%clock;" : "=r"(c)); return c; }

__device__ __forceinline__ float warp_sum(float v) {
#pragma unroll
    for (int o = 16; o > 0; o >>= 1) v += __shfl_xor_sync(0xffffffffu, v, o);
    return v;
}

struct Params {
    const __nv_bfloat16 *x, *kc, *vc, *b1, *b2, *c;
    __nv_bfloat16* out;
};

__device__ __forceinline__ void tma2d(uint32_t dst, const CUtensorMap* tm, int x, int y, uint32_t bar) {
    asm volatile("cp.async.bulk.tensor.2d.shared::cluster.global.mbarrier::complete_tx::bytes [%0], [%1, {%2, %3}], [%4];"
                 ::"r"(dst), "l"(tm), "r"(x), "r"(y), "r"(bar) : "memory");
}

__device__ __forceinline__ void tma2d_hint(uint32_t dst, const CUtensorMap* tm, int x, int y, uint32_t bar, uint64_t pol) {
    asm volatile("cp.async.bulk.tensor.2d.shared::cluster.global.mbarrier::complete_tx::bytes.L2::cache_hint [%0], [%1, {%2, %3}], [%4], %5;"
                 ::"r"(dst), "l"(tm), "r"(x), "r"(y), "r"(bar), "l"(pol) : "memory");
}
__device__ __forceinline__ uint32_t flag(float v) { return __float_as_uint(v) | 1u; }
__device__ __forceinline__ uint32_t* slot_ptr(uint32_t lo) {
    uint32_t* r;
    asm volatile("mov.b64 %0, {%1, %2};" : "=l"(r) : "r"(lo), "r"((uint32_t)((size_t)slot(0, 0) >> 32)));
    return r;
}

__device__ __forceinline__ void load_bfrag(uint32_t vec, int stride, int k0, int g, int t, uint32_t& b0, uint32_t& b1) {
    uint32_t a = vec + (g & 3) * stride + (k0 + 2 * t) * 2;
    b0 = lds32(a);
    b1 = lds32(a + 16);
}

__device__ __forceinline__ void ln_finish(float pivot, float sum, float sumsq, uint32_t& m2, float& rden) {
    float dm = sum * (1.f / D);
    float var = fmaxf(sumsq * (1.f / D) - dm * dm, 0.f);
    float mean = pivot + dm;
    m2 = pack_bf(mean, mean);
    rden = rcp_fast(bfr(sqrt_fast(bfr(bfr(var) + 1e-5f))));
}
__device__ __forceinline__ uint32_t ln_mod_pair(uint32_t xw, uint32_t cw, uint32_t sw, uint32_t m2, float rden) {
    uint32_t d = bf2_sub(xw, m2);
    uint32_t ln = pack_bf(bf_lo(d) * rden, bf_hi(d) * rden);
    return bf2_add(bf2_mul(ln, bf2_add(cw, 0x3f803f80u)), sw);
}
__device__ __forceinline__ uint4 ln_mod4(const uint4& x, const uint4& c, const uint4& s, uint32_t m2, float rden) {
    return make_uint4(ln_mod_pair(x.x, c.x, s.x, m2, rden), ln_mod_pair(x.y, c.y, s.y, m2, rden),
                      ln_mod_pair(x.z, c.z, s.z, m2, rden), ln_mod_pair(x.w, c.w, s.w, m2, rden));
}
__device__ __forceinline__ void acc_stats(const uint4& v, float pv, float& s, float& q) {
    const float a0 = bf_lo(v.x) - pv, a1 = bf_hi(v.x) - pv, a2 = bf_lo(v.y) - pv, a3 = bf_hi(v.y) - pv;
    const float a4 = bf_lo(v.z) - pv, a5 = bf_hi(v.z) - pv, a6 = bf_lo(v.w) - pv, a7 = bf_hi(v.w) - pv;
    s += ((a0 + a1) + (a2 + a3)) + ((a4 + a5) + (a6 + a7));
    q += (fmaf(a0, a0, a1 * a1) + fmaf(a2, a2, a3 * a3)) + (fmaf(a4, a4, a5 * a5) + fmaf(a6, a6, a7 * a7));
}
__device__ __forceinline__ uint32_t* mod_slot(int kind, int j, int b) { return g_mod + (kind * 20 + (j >> 2)) * 64 + b * 16 + (j & 3) * 4; }

template <int N>
__device__ __forceinline__ void poll_n(uint4 (&v)[N], const uint32_t* const* ptr, const bool* on) {
    bool pend[N];
#pragma unroll
    for (int i = 0; i < N; i++) pend[i] = on[i];
    int it = 0;
    while (true) {
#pragma unroll
        for (int i = 0; i < N; i++) if (pend[i]) v[i] = ldg_relaxed(ptr[i]);
        bool any = false;
#pragma unroll
        for (int i = 0; i < N; i++) { pend[i] = pend[i] && !ready(v[i]); any |= pend[i]; }
        if (!__any_sync(0xffffffffu, any)) break;
        if (++it > SPIN_LIMIT) __trap();
    }
#pragma unroll
    for (int i = 0; i < N; i++) v[i] = inv4(v[i]);
}
__device__ __forceinline__ uint4 poll1(const uint32_t* p, bool on) {
    uint4 v[1] = {make_uint4(0, 0, 0, 0)};
    const uint32_t* const ptr[1] = {p};
    const bool o[1] = {on};
    poll_n<1>(v, ptr, o);
    return v[0];
}

#define OWNER_EXCHANGE_AND_VOTE \
    "shfl.sync.bfly.b32 a, z, 8, 31, 0xffffffff;\nshfl.sync.bfly.b32 b, y, 16, 31, 0xffffffff;\nshfl.sync.bfly.b32 c, w, 24, 31, 0xffffffff;\n" \
    "setp.ne.u32 q, t, 0;\nvote.sync.all.pred q, q, 0xffffffff;\n@!q bra.uni L_%=;\nadd.f32 a, a, x;\nadd.f32 b, b, c;\nadd.f32 %0, a, b;\n}"
__device__ __forceinline__ float poll_e4(const uint32_t* p) {
    float s;
    asm volatile("{\n.reg .pred q;\n.reg .b32 t, n, x, y, z, w, a, b, c;\nmov.u32 n, 0;\n"
                 "L_%=:\nld.relaxed.gpu.global.v4.u32 {x, y, z, w}, [%1];\nadd.u32 n, n, 1;\nsetp.gt.u32 q, n, %2;\n@q trap;\nbar.warp.sync 0xffffffff;\n"
                 "lop3.b32 t, x, y, z, 0x80;\nlop3.b32 t, t, w, 1, 0x80;\n" OWNER_EXCHANGE_AND_VOTE
                 : "=f"(s) : "l"(p), "n"(SPIN_LIMIT) : "memory");
    return s;
}
__device__ __forceinline__ float poll_e6(const uint32_t* pa, const uint32_t* pb, bool two) {
    float s;
    asm volatile("{\n.reg .pred q, r;\n.reg .b32 t, n, x, y, z, w, a, b, c, u0, u1, v0, v1;\nmov.u32 n, 0;\nsetp.ne.u32 r, %4, 0;\nmov.b32 v0, 0xffffffff;\nmov.b32 v1, 0xffffffff;\n"
                 "L_%=:\n@r ld.relaxed.gpu.global.v2.u32 {v0, v1}, [%3];\nld.relaxed.gpu.global.v2.u32 {u0, u1}, [%1];\nadd.u32 n, n, 1;\nsetp.gt.u32 q, n, %2;\n@q trap;\nbar.warp.sync 0xffffffff;\n"
                 "lop3.b32 a, u0, 0xffff0000, 0, 0x0c;\nlop3.b32 b, v0, 0xffff0000, 0, 0x0c;\nadd.f32 y, a, b;\n"
                 "lop3.b32 a, u1, 0xffff0000, 0, 0x0c;\nlop3.b32 b, v1, 0xffff0000, 0, 0x0c;\nadd.f32 w, a, b;\n"
                 "shl.b32 a, u1, 16;\nshl.b32 b, v1, 16;\nxor.b32 a, a, 0xffff0000;\nxor.b32 b, b, 0xffff0000;\nadd.f32 z, a, b;\n"
                 "shl.b32 a, u0, 16;\nshl.b32 b, v0, 16;\nxor.b32 a, a, 0xffff0000;\nxor.b32 b, b, 0xffff0000;\nadd.f32 x, a, b;\n"
                 "min.u32 t, u0, u1;\nmin.u32 t, t, v0;\nmin.u32 t, t, v1;\n" OWNER_EXCHANGE_AND_VOTE
                 : "=f"(s) : "l"(pa), "n"(SPIN_LIMIT), "l"(pb), "r"((uint32_t)two) : "memory");
    return s;
}

__device__ __forceinline__ void gelu_stage(uint32_t sb, int m, int lane) {
    const int g = lane >> 2, b = lane & 3;
    const uint32_t y_ld = pin_hard(sb + SC_Y + m * 256 + lane * 8), s_ld = pin_hard(sb + SC_ST + b * 64);
    const uint32_t h_st = pin_hard(sb + SC_H1 + b * 64 + (g >> 1) * 16 + m * 8 + (g & 1) * 2);
#pragma unroll 1
    for (int pass = 1 - m; pass < 2; pass++) {
        float a0 = 0.f, b0 = lds_f32(sb + OWN_B1 + (16 * m + g) * 4), a1 = 0.f, b1 = lds_f32(sb + OWN_B1 + (16 * m + g + 8) * 4);
        const float piv = bf_hi(lds32(sb + OFF_STAT + b * 8));
        if (pass) nbar_sync<NB_AB, 320>();
#pragma unroll
        for (int w = 0; w < 8; w++) {
            const float4 t = lds_f32x4(sb + SC_AB + w * 1024 + m * 512 + lane * 16);
            a0 += t.x; b0 += t.y; a1 += t.z; b1 += t.w;
        }
        sts128(sb + SC_DUMP + m * 512 + lane * 16, make_uint4(__float_as_uint(a0), __float_as_uint(b0), __float_as_uint(a1), __float_as_uint(b1)));
        if (pass) nbar_sync<NB_Y, 320>();
        float4 q[4];
        float2 y[8];
#pragma unroll
        for (int i = 0; i < 4; i++) q[i] = lds_f32x4(s_ld + i * 16);
#pragma unroll
        for (int w = 0; w < 8; w++) y[w] = lds_f32x2(y_ld + w * 512);
        const float dm = (((q[0].y + q[0].w) + (q[1].y + q[1].w)) + ((q[2].y + q[2].w) + (q[3].y + q[3].w))) * (1.f / D);
        const float sq = ((q[0].x + q[0].z) + (q[1].x + q[1].z)) + ((q[2].x + q[2].z) + (q[3].x + q[3].z));
        const float r = rsqrt_fast(fmaxf(fmaf(-dm, dm, fmaf(sq, 1.f / D, 1e-5f)), 1e-5f));
        const float y0 = ((y[0].x + y[1].x) + (y[2].x + y[3].x)) + ((y[4].x + y[5].x) + (y[6].x + y[7].x));
        const float y1 = ((y[0].y + y[1].y) + (y[2].y + y[3].y)) + ((y[4].y + y[5].y) + (y[6].y + y[7].y));
        const float dmr = piv - bfr(piv - dm);
        const float u0 = fmaf(r, fmaf(dmr, a0, -y0), b0), u1 = fmaf(r, fmaf(dmr, a1, -y1), b1);
        const float e0 = ex2(u0 * fmaf(u0 * u0, -0.044715f * 2.302208198144325f, -2.302208198144325f));
        const float e1 = ex2(u1 * fmaf(u1 * u1, -0.044715f * 2.302208198144325f, -2.302208198144325f));
        sts16(h_st, pack_bf(u0 * rcp_fast(1.f + e0), 0.f));
        sts16(h_st + 4, pack_bf(u1 * rcp_fast(1.f + e1), 0.f));
        if (pass) {
#pragma unroll
            for (int w = 0; w < 4; w++) asm volatile("bar.arrive %0, 128;" ::"r"((NB_H1 + w) & 15) : "memory");
        }
    }
}

struct Roles { bool is_f, is_owner; int f, own; };
__device__ __forceinline__ Roles roles(int cta) {
    Roles r;
    r.f = (cta * 27) >> 6;
    r.is_f = (((cta + 1) * 27) >> 6) != r.f;
    r.is_owner = !r.is_f || r.f % 9 == 4;
    r.own = r.is_f ? 74 + r.f / 9 : cta - r.f;
    return r;
}

__global__ void __launch_bounds__(NTHREADS, 1)
fused_kernel(const Params p, const __grid_constant__ CUtensorMap tm_wmod, const __grid_constant__ CUtensorMap tm_wq,
             const __grid_constant__ CUtensorMap tm_wo, const __grid_constant__ CUtensorMap tm_w1, const __grid_constant__ CUtensorMap tm_w2,
             const __grid_constant__ CUtensorMap tm_v, const __grid_constant__ CUtensorMap tm_gb) {
    extern __shared__ __align__(1024) unsigned char smem[];
    const uint32_t t_start = gtime32();
    if (threadIdx.x == 0) {
        const uint32_t c_ = blockIdx.x;
        const uint32_t off = ((c_ & 3) << 26) + (c_ >> 2) * (1u << 21) + (ROT(c_) << 14) + (SK - WIN) * DH * 2;
        asm volatile("cp.async.bulk.prefetch.L2.global.L2::cache_hint [%0], %1, %2;" ::"l"((const char*)p.kc + off), "r"(TILE_BYTES), "l"(0x12f0000000000000ull  ) : "memory");
    }
    const uint32_t sb = smem_u32(smem);
    const int cta = blockIdx.x;
    const int head = cta >> 2, bown = cta & 3;
    const int rot = ROT(cta);
    const char* const kb = (const char*)(p.kc + ((size_t)(bown * NH + head) * SK + (SK - WIN)) * DH);
    uint64_t pol = 0;
    if (threadIdx.x == 256) {
        mbar_init(sb + OFF_BAR, 1);
        asm volatile("fence.mbarrier_init.release.cluster;" ::: "memory");
        asm volatile("createpolicy.fractional.L2::evict_first.b64 %0, 1.0;" : "=l"(pol));
        mbar_expect_tx(sb + OFF_BAR, TILE_BYTES);
        bulk_load(sb + OFF_RING, kb + (size_t)rot * TILE_BYTES, TILE_BYTES, sb + OFF_BAR, pol);
        if ((((head + 1) * 5) >> 4) != ((head * 5) >> 4)) {
            const uint32_t bar = sb + OFF_BAR + 2 * NS * 8;
            mbar_init(bar, 1);
            asm volatile("fence.mbarrier_init.release.cluster;" ::: "memory");
            mbar_expect_tx(bar, D * 64);
#pragma unroll 1
            for (int r = 0; r < D; r += 160) tma2d(sb + X_WM + r * 64, &tm_wmod, 32 * (((head * 5) >> 4) * 4 + bown), r, bar);
        }
    }
    const uint32_t bar_full = sb + OFF_BAR, bar_empty = bar_full + NS * 8;
    const uint32_t bar_wm = bar_empty + NS * 8, bar_wq = bar_wm + 8, bar_xfree = bar_wq + 8, bar_wo = bar_xfree + 8  ;
    const uint32_t bar_w1 = bar_wo + 40  , bar_w2 = bar_w1 + 32  , bar_help = bar_w2 + 80, bar_v = bar_help + 8  ;
    const uint32_t bar_gb = bar_v + 32  , bar_x1 = bar_gb + 32;
    const int tid = threadIdx.x, warp = tid >> 5, lane = tid & 31;
    const Roles role = roles(cta);
    const bool is_f = role.is_f, is_owner = role.is_owner;
    const int f = role.f, own = role.own;
    const bool crit = (((head + 1) * 5) >> 4) != ((head * 5) >> 4);
    const int mr = cta - ((head * 5) >> 4) * 4, mq = ((head * 5) >> 4) * 4 + bown;
    const int ml = mr * 31 / 44;
    const bool late = !crit && (mr + 1) * 31 / 44 != ml;
    const int mc = crit ? mq : ml < 60 ? 40 + ml : 58 + ml;
    const bool gb_own = is_owner && own < 72;

    PROF_DECL
    PROF(0);
    uint4 xa = make_uint4(0, 0, 0, 0), xb = xa, ca0 = xa, ca1 = xa, xs[3] = {xa, xa, xa};
    uint32_t own0 = 0;
    __nv_bfloat16 own2 = __float2bfloat16(0.f);
    if (warp < 8) {
        xa = *(const uint4*)(p.x + (tid & 3) * D + (tid >> 2) * 8);
        ca0 = ((const uint4*)p.c)[tid];
        if (tid < 64) { xb = *(const uint4*)(p.x + (tid & 3) * D + (64 + (tid >> 2)) * 8); ca1 = ((const uint4*)p.c)[256 + tid]; }
        if (warp < 4) {
#pragma unroll
            for (int i = 0; i < 3; i++) if (lane + 32 * i < 80) xs[i] = ((const uint4*)p.x)[warp * 80 + lane + 32 * i];
        } else if (warp == 4) {
            if (is_owner) own0 = *(const uint32_t*)((lane < 16 ? p.x + (lane >> 2) * D : p.b2) + 8 * own + 2 * (lane & 3));
            if (is_f) own2 = p.b1[32 * f + lane];
        }
    }
    const char* const vb = (const char*)(p.vc + ((size_t)(bown * NH + head) * SK + (SK - WIN)) * DH);
    const uint32_t bar_first = crit ? bar_wm : bar_wq;
    if (threadIdx.x == 256) {
        if (!crit) {
            mbar_init(bar_wq, 1);
            asm volatile("fence.mbarrier_init.release.cluster;" ::: "memory");
            mbar_expect_tx(bar_wq, D * 64);
            const uint32_t c0 = clock32();
            while (clock32() - c0 < WQ_DELAY) { }
#pragma unroll
            for (int r = 0; r < D; r += 160) tma2d(sb + X_WQ + r * 64, &tm_wq, 32 * cta, r, bar_wq);
        }
    } else if (threadIdx.x == 0) {
#pragma unroll
        for (int s = 0; s < NS; s++) { if (s) mbar_init(bar_full + s * 8, 1); mbar_init(bar_empty + s * 8, 4); }
        mbar_init(crit ? bar_wq : bar_wm, 1);
        mbar_init(bar_xfree, 1);
#pragma unroll
        for (int i = 0; i < 5; i++) { mbar_init(bar_wo + i * 8, 1); mbar_init(bar_w2 + i * 16, 1); mbar_init(bar_w2 + i * 16 + 8, 1); }
        mbar_init(bar_help, 1); mbar_init(bar_x1, 1);
#pragma unroll
        for (int i = 0; i < 4; i++) { mbar_init(bar_v + i * 8, 1); mbar_init(bar_w1 + i * 8, 1); mbar_init(bar_gb + i * 8, 1); }
        asm volatile("fence.mbarrier_init.release.cluster;" ::: "memory");
    }
    __syncthreads();

    if (warp == 8) {
        if (lane == 0) {
            int tp = NS;
            int sched = PACE_A - NS * PACE_TAU;
            int phase = 0;
#pragma unroll 1
            for (int t = 1; t <= NITEM; t++) {
                if (t == 1) mbar_wait(bar_full, 0);
                if (t == 2) {
                    mbar_wait(bar_first, 0);
                    if (crit) {
                        mbar_expect_tx(bar_wq, D * 64);
#pragma unroll 1
                        for (int r = 0; r < D; r += 160) tma2d(sb + X_WQ + r * 64, &tm_wq, 32 * cta, r, bar_wq);
                    }
                }
                if (t == 3) {
                    asm volatile("prefetch.tensormap [%0];" ::"l"(&tm_v) : "memory");
                    asm volatile("prefetch.tensormap [%0];" ::"l"(&tm_wo) : "memory");
                    asm volatile("prefetch.tensormap [%0];" ::"l"(&tm_w1) : "memory");
                    asm volatile("prefetch.tensormap [%0];" ::"l"(&tm_w2) : "memory");
                    asm volatile("prefetch.tensormap [%0];" ::"l"(&tm_gb) : "memory");
                }
                if (t == NS && late) {
                    mbar_wait(bar_full + (NS - INFLIGHT) * 8, 0);
                    mbar_expect_tx(bar_wm, D * 64);
#pragma unroll 1
                    for (int r = 0; r < D; r += 160) tma2d(sb + X_WM + r * 64, &tm_wmod, 32 * mc, r, bar_wm);
                }
                if (t >= NS && t < PF_END) {
                    int it = 0;
                    while (!mbar_test(bar_empty + (t & (NS - 1)) * 8, ((t >> 3) - 1) & 1)) {
                        if (tp < PF_END && (int)(gtime32() - t_start) >= PACE_A + (tp - NS) * PACE_TAU) {
                            asm volatile("cp.async.bulk.prefetch.L2.global.L2::cache_hint [%0], %1, %2;"
                                         ::"l"(((tp & 1) ? vb : kb) + (size_t)(((tp >> 1) + rot) & (NITEM / 2 - 1)) * TILE_BYTES), "r"(TILE_BYTES), "l"(pol) : "memory");
                            tp++;
                        }
                        if (++it > 16 * SPIN_LIMIT) __trap();
                    }
                    if (tp <= t) tp = t + 1;
                }
                if (t == NITEM) {
                    mbar_wait(bar_xfree, 0);
                    const uint32_t t_ref = t_start + phase + (NITEM - 1) * PACE_TAU;
#pragma unroll 1
                    for (int i = 0; i < 5; i++) {
                        while ((int)(gtime32() - t_ref) < WO_T + i * WO_S) { }
                        mbar_expect_tx(bar_wo + i * 8, DH * 64);
                        tma2d(sb + X_WO + i * (DH * 64), &tm_wo, bown * 160 + i * 32, head * DH, bar_wo + i * 8);
                    }
                    if (gb_own) {
                        mbar_wait(bar_empty + 3 * 8, ((NITEM >> 3) - 1) & 1);
                        mbar_wait(bar_x1, 0);
                        { const uint32_t c0 = clock32(); while (clock32() - c0 < GB_EV) { } }
                        while ((int)(gtime32() - t_ref) < GB_T) { }
#pragma unroll 1
                        for (int i = 0; i < 4; i++) {
                            mbar_expect_tx(bar_gb + i * 8, 160 * 16);
                            tma2d(sb + X_GB + i * (160 * 16), &tm_gb, 5 * D + 8 * own, 160 * i, bar_gb + i * 8);
                        }
                    }
                    if (is_f) {
#pragma unroll 1
                        for (int i = 0; i < 3; i++) mbar_wait(bar_empty + i * 8, ((NITEM >> 3) - 1) & 1);
                        while ((int)(gtime32() - t_ref) < W1_T) { }
#pragma unroll 1
                        for (int i = 0; i < 4; i++) {
                            mbar_expect_tx(bar_w1 + i * 8, 160 * 64);
                            tma2d(sb + X_W1 + i * (160 * 64), &tm_w1, 32 * f, 160 * i, bar_w1 + i * 8);
                        }
                        while ((int)(gtime32() - t_ref) < W2_T) { }
#pragma unroll 1
                        for (int i = 0; i < 10; i++) {
                            mbar_expect_tx(bar_w2 + i * 8, 4096);
                            tma2d(sb + X_W2 + i * 4096, &tm_w2, 64 * i, 32 * f, bar_w2 + i * 8);
                        }
                    }
                    break;
                }
                const int s = t & (NS - 1);
                if (t >= NS) {
                    mbar_wait(bar_empty + s * 8, ((t >> 3) - 1) & 1);
                    while ((int)(gtime32() - t_start) < sched + t * PACE_TAU) { }
                } else if (t >= INFLIGHT) {
                    mbar_wait(bar_full + (t - INFLIGHT) * 8, 0);
                }
                if (t < NITEM - 2) {
                    const int pair = t == NITEM - 3 ? NITEM / 2 - 1 : t >> 1;
                    mbar_expect_tx(bar_full + s * 8, TILE_BYTES);
                    bulk_load(sb + OFF_RING + s * TILE_BYTES, ((t & 1) && t != NITEM - 3 ? vb : kb) + (size_t)((pair + rot) & (NITEM / 2 - 1)) * TILE_BYTES, TILE_BYTES, bar_full + s * 8, pol);
                } else {
                    const int row = (bown * NH + head) * SK + (SK - WIN) + ((t - NITEM / 2 + rot) & (NITEM / 2 - 1)) * TILE_KEYS;
#pragma unroll 1
                    for (int i = 0; i < 2; i++) {
                        const uint32_t bar = bar_v + (2 * (t - (NITEM - 2)) + i) * 8;
                        mbar_expect_tx(bar, TILE_BYTES / 2);
                        tma2d_hint(sb + OFF_RING + s * TILE_BYTES + i * (TILE_BYTES / 2), &tm_v, 64 * i, row, bar, pol);
                    }
                }
                if (t >= PH_FIRST && (t & 7) == PH_LAG) {
                    const int now = (int)(gtime32() - t_start) - (t - PH_LAG) * PACE_TAU;
                    uint32_t ph;
                    asm volatile("atom.relaxed.gpu.global.add.u32 %0, [%1], 0;" : "=r"(ph) : "l"(g_phase + (t >> 3) * 32) : "memory");
                    phase = (int)min(((ph & 0xffffffu) * 4 + (NCTA - (ph >> 24)) * now) / NCTA, 65535u);
                    sched += (phase - LAT_T - sched) * 3 / 4;
                }
            }
        }
        __syncwarp();
    }

    if (warp == 9) {
        int side = 0;
        if (lane == 0) {
            uint32_t best[2] = {~0u, ~0u};
#pragma unroll
            for (int i = 0; i < 4; i++) stg_zero4(slot(SL_SIDE, i >> 1) + cta * 8 + (i & 1) * 4);
            uint32_t n = 0;
#pragma unroll 1
            for (int i = 0; (i & 1) || (n < NPROBE - 1 && (int)(gtime32() - t_start) < PROBE_END); i++) {
                uint32_t t0 = clock32(), t1;
                asm volatile("atom.relaxed.gpu.global.inc.u32 %0, [%1], %2;" : "=r"(n) : "l"(slot(SL_SIDE, i & 1) + cta * 8), "r"(0xffffu) : "memory");
                asm volatile("{\n.reg .pred p;\nsetp.ne.u32 p, %1, 0xffffffff;\nmov.u32 %0, 0;\n@p mov.u32 %0, %%clock;\n}" : "=r"(t1) : "r"(n) : "memory");
                if (i & 1) best[1] = min(best[1], t1 - t0); else best[0] = min(best[0], t1 - t0);
            }
            side = best[1] < best[0];
        }
        side = __shfl_sync(0xffffffffu, side, 0);
        HPROF(1);
        mbar_wait(bar_full + (NS - 1) * 8, 0);
        stg_zero4(slot(SL_O + (cta >> 4), lane >> 4) + (cta & 15) * 64 + (lane & 15) * 4);
        if (is_owner) {
#pragma unroll 1
            for (int i = lane; i < NH * 8; i += 32) stg_zero4(slot(SL_P1 + own, side) + i * 4);
#pragma unroll 1
            for (int i = lane; i < NF * 4; i += 32) stg_zero4(slot(SL_P2 + 2 * own + (i >> 7), side) + ((i >> 2) & 31) * 32 + (i & 3) * 4);
            if (lane < 8) stg_zero4(slot(SL_X1 + own / 30, lane >> 2) + (own % 30) * 32 + (lane & 3) * 4);
        }
        __threadfence();
        __syncwarp();
        if (lane == 0) stg_relaxed(g_clr + cta, 1u + side);
        HPROF(0);
        while ((int)(gtime32() - t_start) < CLR_CHECK) __nanosleep(1000);
        mbar_wait(bar_xfree, 0);
        {
            uint4 v = make_uint4(1, 1, 1, 1), gv = v, mv[20];
#pragma unroll
            for (int i = 0; i < 20; i++) mv[i] = v;
#pragma unroll 1
            for (int it = 0;; it++) {
                v = ldg_relaxed(g_clr + lane * 4);
                ldg_relaxed_if(is_owner && lane < (gb_own ? 4 : 8), gv, mod_slot(lane < 4 ? 2 : 5, own, lane & 3));
#pragma unroll
                for (int i = 0; i < 20; i++) ldg_relaxed_if(is_f, mv[i], mod_slot(3, 8 * i + (lane >> 2), lane & 3));
                bool ok = ready(v) && ready(gv);
#pragma unroll
                for (int i = 0; i < 20; i++) ok = ok && ready(mv[i]);
                if (__all_sync(0xffffffffu, ok)) break;
                if (it > SPIN_LIMIT) __trap();
                __nanosleep(2000);
            }
            const uint32_t w[4] = {v.x, v.y, v.z, v.w};
#pragma unroll
            for (int i = 0; i < 4; i++) {
                const Roles r = roles(4 * lane + i);
                if (r.is_owner) {
                    sts32(sb + OFF_TAB1 + r.own * 4, (uint32_t)(size_t)(slot(SL_P1 + r.own, w[i] - 1) + head * 32));
                    sts32(sb + OFF_TAB2 + r.own * 4, (uint32_t)(size_t)(slot(SL_P2 + 2 * r.own + (f >> 5), w[i] - 1) + (f & 31) * 32));
                }
            }
            if (lane == 0) sts32(sb + OFF_SIDE, side);
            gv = inv4(gv);
            if (lane < 4) sts128(sb + OWN_GA + lane * 16, gv);
            else if (lane < 8) {
                sts128(sb + OWN_GB + (lane & 3) * 32, make_uint4(gv.x << 16, gv.x & 0xffff0000u, gv.y << 16, gv.y & 0xffff0000u));
                sts128(sb + OWN_GB + (lane & 3) * 32 + 16, make_uint4(gv.z << 16, gv.z & 0xffff0000u, gv.w << 16, gv.w & 0xffff0000u));
            } else if (lane < 16) sts128(sb + OWN_GB + lane * 16, make_uint4(0, 0, 0, 0));
            const uint32_t dst = sb + OFF_VB + (lane & 3) * VEC_STRIDE + (lane >> 2) * 16;
#pragma unroll
            for (int i = 0; i < 10; i++) {
                const uint4 c = inv4(mv[10 + i]);
                sts128(dst + i * 128, make_uint4(bf2_add(c.x, 0x3f803f80u), bf2_add(c.y, 0x3f803f80u), bf2_add(c.z, 0x3f803f80u), bf2_add(c.w, 0x3f803f80u)));
                sts128(dst + (OFF_RED - OFF_VB) + i * 128, inv4(mv[i]));
            }
        }
        asm volatile("fence.acq_rel.gpu;" ::: "memory");
        __syncwarp();
        HPROF(3);
        if (lane == 0) mbar_arrive(bar_help);
        {
            const uint32_t* const src = pin(slot(SL_O + (cta >> 4), side) + (cta & 12) * 64 + lane * 4);
            const uint32_t dst = pin(sb + OFF_O + (lane >> 4) * O_STRIDE + (lane & 15) * 16);
            mbar_wait(bar_v + 16, 0);
            mbar_wait(bar_v + 24, 0);
            uint4 v[2];
            const uint32_t* const ptr[2] = {src, src + 128};
            const bool on[2] = {true, true};
            poll_n<2>(v, ptr, on);
            sts128(dst, v[0]);
            sts128(dst + 2 * O_STRIDE, v[1]);
#pragma unroll
            for (int w = 0; w < 8; w++) asm volatile("bar.arrive %0, 64;" ::"r"(NB_O + w) : "memory");
        }
        HPROF(4);
    }
    if (warp >= 8) {
        if (gb_own) {
            uint32_t a[10][4];
#pragma unroll
            for (int k = 0; k < 10; k++) ldsm4(a[k], sb + OFF_VA + (lane & 3) * VEC_STRIDE + (8 * k + 4 * (warp - 8) + ((lane >> 2) & 2) + (lane >> 4)) * 16);
            float c[4][4];
#pragma unroll
            for (int i = 0; i < 4; i++) c[i][0] = c[i][1] = c[i][2] = c[i][3] = 0.f;
            mbar_wait(bar_help, 0);
#pragma unroll
            for (int k = 0; k < 10; k++) {
                if (k == 0 || k == 2 || k == 5 || k == 7) mbar_wait(bar_gb + (2 * k + 1) / 5 * 8, 0);
                uint32_t w[4];
                ldsm4t(w, sb + X_GB + (64 * k + 32 * (warp - 8) + lane) * 16);
                mma16816(c[2 * (k & 1)], a[k], w[0], w[1]);
                mma16816(c[2 * (k & 1) + 1], a[k], w[2], w[3]);
            }
            if (lane < 16) sts_f32x2(sb + OWN_GB + (warp - 8) * 128 + lane * 8, (c[0][0] + c[2][0]) + (c[1][2] + c[3][2]), (c[0][1] + c[2][1]) + (c[1][3] + c[3][3]));
        }
        if (is_owner) nbar_arrive<NB_E6, 320>();
        if (is_f) gelu_stage(sb, warp - 8, lane);
        return;
    }

    const int g = lane >> 2, t4 = lane & 3;
    const int mi = lane >> 3, r8 = lane & 7;

    {
        auto silu4 = [&](const uint4& cv) {
            uint32_t w4[4] = {cv.x, cv.y, cv.z, cv.w};
#pragma unroll
            for (int e = 0; e < 4; e++) {
                float c0 = bf_lo(w4[e]), c1 = bf_hi(w4[e]);
                w4[e] = pack_bf(c0 * rcp_fast(1.f + ex2(-1.4426950408889634f * c0)), c1 * rcp_fast(1.f + ex2(-1.4426950408889634f * c1)));
            }
            return make_uint4(w4[0], w4[1], w4[2], w4[3]);
        };
        {
            uint4 v = silu4(ca0);
            sts128(sb + OFF_VA + (tid / 80) * VEC_STRIDE + (tid % 80) * 16, v);
            if (tid < 64) { v = silu4(ca1); sts128(sb + OFF_VA + 3 * VEC_STRIDE + (16 + tid) * 16, v); }
        }
        if (warp < 4) {
            float s = 0.f, q = 0.f;
            const float pv = __shfl_sync(0xffffffffu, bf_lo(xs[0].x), 0);
#pragma unroll
            for (int i = 0; i < 3; i++) if (i < 2 || lane < 16) acc_stats(xs[i], pv, s, q);
#pragma unroll
            for (int of = 16; of > 0; of >>= 1) { s += __shfl_xor_sync(0xffffffffu, s, of); q += __shfl_xor_sync(0xffffffffu, q, of); }
            uint32_t m2; float rden;
            ln_finish(pv, s, q, m2, rden);
            if (lane == 0) { sts32(sb + OFF_STAT + warp * 8, m2); sts_f32(sb + OFF_STAT + warp * 8 + 4, rden); }
        } else if (warp == 4) {
            sts32(sb + OWN_X + lane * 4, bf2_add(own0, 0u));
            sts_f32(sb + OWN_B1 + lane * 4, bf2f(own2));
        }
    }
    bar_cons();
    PROF(24);
    uint32_t qf[8][2];
    float o[8][4];
#pragma unroll
    for (int c = 0; c < 8; c++) { o[c][0] = o[c][1] = o[c][2] = o[c][3] = 0.f; }
    float m_run = -INFINITY, l_run = 0.f;
    const bool diag = (t4 == (g >> 1));
    const bool odd = g & 1;
    const uint32_t koff = (warp & 3) * 4096 + (r8 + 8 * (mi & 1)) * 256 + (mi >> 1) * 128 + (r8 << 4);
    const uint32_t voff = TILE_BYTES + (warp & 3) * 4096 + (r8 + 8 * (mi >> 1)) * 256 + (mi & 1) * 128 + (r8 << 4);
    const int src0 = (2 * t4) * 4 + t4, src1 = (2 * t4 + 1) * 4 + t4;
#pragma unroll 1
    for (int step = crit ? 0 : 1; step < 3; step++) {
        if (step < 2 || late) {
            if (step == 1) {
                if (!crit) mbar_wait(bar_wq, 0);
                const uint32_t m2 = lds32(sb + OFF_STAT + (tid & 3) * 8);
                const float rden = lds_f32(sb + OFF_STAT + (tid & 3) * 8 + 4);
                uint4 v[4];
                v[2] = v[3] = make_uint4(1, 1, 1, 1);
                const uint32_t* const p0 = mod_slot(0, tid >> 2, tid & 3);
                while ((int)(gtime32() - t_start) < MOD_T) { }
                PROF(2);
#pragma unroll 1
                for (int it = 0;; it++) {
                    ldg_relaxed_if(tid < 64, v[2], p0 + 16 * 64);
                    ldg_relaxed_if(tid < 64, v[3], p0 + 36 * 64);
                    v[0] = ldg_relaxed(p0);
                    v[1] = ldg_relaxed(p0 + 20 * 64);
                    if (__all_sync(0xffffffffu, min(min(min4(v[0]), min4(v[1])), min(min4(v[2]), min4(v[3]))) != 0u)) break;
                    if (it > SPIN_LIMIT) __trap();
                }
#pragma unroll
                for (int i = 0; i < 4; i++) v[i] = inv4(v[i]);
                PROF(3);
                uint4 h0 = ln_mod4(xa, v[1], v[0], m2, rden);
                sts128(sb + OFF_VB + (tid & 3) * VEC_STRIDE + (tid >> 2) * 16, h0);
                if (tid < 64) {
                    h0 = ln_mod4(xb, v[3], v[2], m2, rden);
                    sts128(sb + OFF_VB + (tid & 3) * VEC_STRIDE + (64 + (tid >> 2)) * 16, h0);
                }
            }
            mbar_wait(step == 1 ? bar_wq : bar_wm, 0);
            bar_cons();
            const uint32_t strip = sb + (step == 1 ? X_WQ : X_WM), vec = sb + (step == 1 ? OFF_VB : OFF_VA);
            float acc[2][4];
#pragma unroll
            for (int m = 0; m < 2; m++) { acc[m][0] = acc[m][1] = acc[m][2] = acc[m][3] = 0.f; }
#pragma unroll
            for (int i = 0; i < 5; i++) {
                int k0 = (warp * 5 + i) * 16;
                uint32_t b0, b1;
                load_bfrag(vec, VEC_STRIDE, k0, g, t4, b0, b1);
                int krow = k0 + r8 + 8 * (mi >> 1);
#pragma unroll
                for (int m = 0; m < 2; m++) {
                    uint32_t a[4];
                    int ch = 2 * m + (mi & 1);
                    ldsm4t(a, strip + krow * 64 + ((ch ^ ((krow >> 1) & 3)) << 4));
                    mma16816(acc[m], a, b0, b1);
                }
            }
            if (t4 < 2) {
#pragma unroll
                for (int m = 0; m < 2; m++) {
                    sts_f32x2(sb + OFF_RED + ((warp * 32 + m * 16 + g) * 4 + 2 * t4) * 4, acc[m][0], acc[m][1]);
                    sts_f32x2(sb + OFF_RED + ((warp * 32 + m * 16 + g + 8) * 4 + 2 * t4) * 4, acc[m][2], acc[m][3]);
                }
            }
            bar_cons();
            if (tid < 64) {
                float v0 = 0.f, v1 = 0.f;
#pragma unroll
                for (int w = 0; w < 8; w++) {
                    v0 += lds_f32(sb + OFF_RED + (w * 128 + (tid & 15) * 8 + (tid >> 4)) * 4);
                    v1 += lds_f32(sb + OFF_RED + (w * 128 + (tid & 15) * 8 + 4 + (tid >> 4)) * 4);
                }
                stg_relaxed(step == 1 ? g_q + (((cta & ~3) + (tid >> 4)) * 4 + bown) * 32 + (tid & 15) : g_mod + mc * 64 + tid, ~pack_bf(v0, v1));
            }
        }
        if (step == 0) continue;
        if (step == 1) {
            if (warp == 0) {
                { const uint32_t c0 = clock32(); while (clock32() - c0 < Q_PAUSE) { } }
                uint4 v = poll1(g_q + (cta * 4 + ((lane >> 2) & 3)) * 32 + (lane & 3) * 4, lane < 16);
                if (lane < 16) {
                    sts128(sb + OFF_Q + lane * 16, v);
                    stg_zero4(g_q + (cta * 4 + (lane >> 2)) * 32 + (lane & 3) * 4);
                }
            }
            bar_cons();
            PROF(4);

#pragma unroll
            for (int c = 0; c < 8; c++) {
                qf[c][0] = lds32(sb + OFF_Q + (((c ^ g) * 4 + t4) << 2));
                qf[c][1] = lds32(sb + OFF_Q + 128 + (((c ^ g) * 4 + t4) << 2));
            }
        } else {
            bar_cons();
            if (tid == 0) mbar_arrive(bar_xfree);
        }
#pragma unroll 1
        for (int j = (step == 1 ? 0 : SEG_J) + (warp >> 2); j < (step == 1 ? SEG_J : NITEM / 2 - 2); j += 2) {
            const int s = (2 * j) & (NS - 1);
            const uint32_t par = (j >> 2) & 1;
            mbar_wait(bar_full + s * 8, par);
            if (tid == 0 && 2 * j >= PH_FIRST && (j & 3) == 0) {
                const int x = min(max((int)(gtime32() - t_start) - 2 * j * PACE_TAU, 0), 65535);
                asm volatile("red.relaxed.gpu.global.add.u32 [%0], %1;" ::"l"(g_phase + (j >> 2) * 32), "r"((1u << 24) + (x >> 2)) : "memory");
            }
            const uint32_t base = sb + OFF_RING + s * TILE_BYTES;
            float sa[4] = {0.f, 0.f, 0.f, 0.f}, sb2[4] = {0.f, 0.f, 0.f, 0.f};
#pragma unroll
            for (int c = 0; c < 8; c += 2) {
                uint32_t a[4], a2[4];
                ldsm4(a, (base + koff) ^ (c << 4));
                ldsm4(a2, (base + koff) ^ ((c + 1) << 4));
                mma16816(sa, a, qf[c][0], qf[c][1]);
                mma16816(sb2, a2, qf[c + 1][0], qf[c + 1][1]);
            }
            const uint32_t sw = pack_bf(odd ? sa[1] + sb2[1] : sa[0] + sb2[0], odd ? sa[3] + sb2[3] : sa[2] + sb2[2]);
            const uint32_t sv = pack_bf(bf_lo(sw) * 0.08838834764831845f, bf_hi(sw) * 0.08838834764831845f);
            const float s0 = bf_lo(sv) * 1.4426950408889634f, s1 = bf_hi(sv) * 1.4426950408889634f;
            float m_new = fmaxf(m_run, fmaxf(s0, s1));
            const bool grow = __any_sync(0xffffffffu, (diag && (m_new > m_run)));
            if (lane == 0) mbar_arrive(bar_empty + s * 8);
            if (grow) {
                float al = ex2(m_run - m_new);
                float a0 = __shfl_sync(0xffffffffu, al, src0), a1 = __shfl_sync(0xffffffffu, al, src1);
#pragma unroll
                for (int c = 0; c < 8; c++) { o[c][0] *= a0; o[c][1] *= a1; o[c][2] *= a0; o[c][3] *= a1; }
                l_run *= al;
                m_run = m_new;
            }
            uint32_t pw = pack_bf(ex2(s0 - m_run), ex2(s1 - m_run));
            l_run += bf_lo(pw) + bf_hi(pw);
            uint32_t b0 = odd ? (pw << 16) : (pw & 0xffffu);
            uint32_t b1 = odd ? (pw & 0xffff0000u) : (pw >> 16);
            if (!diag) { b0 = 0u; b1 = 0u; }
            mbar_wait(bar_full + (s + 1) * 8, par);
#pragma unroll
            for (int c = 0; c < 8; c++) {
                uint32_t a[4];
                ldsm4t(a, (base + voff) ^ (c << 4));
                mma16816(o[c], a, b0, b1);
            }
            __syncwarp();
            if (lane == 0) mbar_arrive(bar_empty + (s + 1) * 8);
        }
    }
    PROF(5);
    float acc[4][4];
    uint32_t pa[8][2];
    float rinv;
    {
        const int s = 4 + (warp >> 2);
        mbar_wait(bar_full + s * 8, 1);
        const uint32_t base = sb + OFF_RING + s * TILE_BYTES;
        float sa[4] = {0.f, 0.f, 0.f, 0.f}, sb2[4] = {0.f, 0.f, 0.f, 0.f};
#pragma unroll
        for (int c = 0; c < 8; c += 2) {
            uint32_t a[4], a2[4];
            ldsm4(a, (base + koff) ^ (c << 4));
            ldsm4(a2, (base + koff) ^ ((c + 1) << 4));
            mma16816(sa, a, qf[c][0], qf[c][1]);
            mma16816(sb2, a2, qf[c + 1][0], qf[c + 1][1]);
        }
        const uint32_t sw = pack_bf(odd ? sa[1] + sb2[1] : sa[0] + sb2[0], odd ? sa[3] + sb2[3] : sa[2] + sb2[2]);
        const uint32_t sv = pack_bf(bf_lo(sw) * 0.08838834764831845f, bf_hi(sw) * 0.08838834764831845f);
        const float s0 = bf_lo(sv) * 1.4426950408889634f, s1 = bf_hi(sv) * 1.4426950408889634f;
        int mi_ = __float_as_int(diag ? fmaxf(m_run, fmaxf(s0, s1)) : -INFINITY);
        mi_ ^= (mi_ >> 31) & 0x7fffffff;
        mi_ = __reduce_max_sync(0xffffffffu, mi_);
        mi_ ^= (mi_ >> 31) & 0x7fffffff;
        if (lane == 0) sts32(sb + OFF_ML + warp * 4, mi_);
        bar_cons();
        const float4 m0 = lds_f32x4(sb + OFF_ML), m1 = lds_f32x4(sb + OFF_ML + 16);
        const float mx = fmaxf(fmaxf(fmaxf(m0.x, m0.y), fmaxf(m0.z, m0.w)), fmaxf(fmaxf(m1.x, m1.y), fmaxf(m1.z, m1.w)));
        const float scl = ex2(m_run - mx);
        const uint32_t pw = pack_bf(ex2(s0 - mx), ex2(s1 - mx));
        if (diag) { sts16(sb + SC_P + (warp * 16 + g) * 2, pw); sts16(sb + SC_P + (warp * 16 + g + 8) * 2, pw >> 16); }
        const float lw = warp_sum(diag ? fmaf(l_run, scl, bf_lo(pw) + bf_hi(pw)) : 0.f);
        const float a0 = __shfl_sync(0xffffffffu, scl, src0), a1 = __shfl_sync(0xffffffffu, scl, src1);
        float v[8], u[8];
#pragma unroll
        for (int c = 0; c < 8; c++) {
            v[c] = a0 * o[c][0] + a1 * o[c ^ 1][1];
            u[c] = a0 * o[c][2] + a1 * o[c ^ 1][3];
        }
#pragma unroll
        for (int c = 0; c < 8; c++) {
            if (!(c & 2)) {
                v[c] += __shfl_xor_sync(0xffffffffu, v[c ^ 2], 1);
                u[c] += __shfl_xor_sync(0xffffffffu, u[c ^ 2], 1);
            }
        }
#pragma unroll
        for (int c = 0; c < 2; c++) {
            v[c] += __shfl_xor_sync(0xffffffffu, v[c ^ 4], 2);
            u[c] += __shfl_xor_sync(0xffffffffu, u[c ^ 4], 2);
        }
        const uint32_t dst = sb + SC_OP + (warp * 128 + 16 * t4 + g) * 4;
        sts_f32(dst, v[0]); sts_f32(dst + 32, v[1]); sts_f32(dst + 256, u[0]); sts_f32(dst + 288, u[1]);
        if (lane == 0) sts_f32(sb + OFF_ML + 32 + warp * 4, lw);
        mbar_wait(bar_help, 0);
        bar_cons();
        const float4 l0 = lds_f32x4(sb + OFF_ML + 32), l1 = lds_f32x4(sb + OFF_ML + 48);
        rinv = rcp_fast(((l0.x + l0.y) + (l0.z + l0.w)) + ((l1.x + l1.y) + (l1.z + l1.w)));
#pragma unroll
        for (int i = 0; i < 4; i++) acc[i][0] = acc[i][1] = acc[i][2] = acc[i][3] = 0.f;
#pragma unroll
        for (int w = 0; w < 8; w++) {
            const float2 x0 = lds_f32x2(sb + SC_OP + (w * 128 + 16 * warp + 2 * t4) * 4), x1 = lds_f32x2(sb + SC_OP + (w * 128 + 16 * warp + 8 + 2 * t4) * 4);
            acc[2 * (w & 1)][0] += x0.x; acc[2 * (w & 1)][1] += x0.y;
            acc[2 * (w & 1) + 1][0] += x1.x; acc[2 * (w & 1) + 1][1] += x1.y;
        }
#pragma unroll
        for (int ks = 0; ks < 8; ks++) { pa[ks][0] = lds32(sb + SC_P + (8 * ks + t4) * 4); pa[ks][1] = lds32(sb + SC_P + (8 * ks + 4 + t4) * 4); }
    }
    PROF(20);
    const int mt = warp < 2 ? warp : warp + 2;
    {
        const uint32_t va = pin(sb + OFF_RING + 6 * TILE_BYTES + (warp >> 2) * (TILE_BYTES / 2) + (8 * (mi & 1) + r8) * 128 + (((2 * (warp & 3) + (mi >> 1)) ^ r8) << 4));
        const uint32_t vbar = pin(bar_v + (warp >> 2) * 8);
        uint32_t* const o_dst = pin(slot(SL_O + (cta >> 4), g) + (cta & 15) * 64 + warp * 8 + 2 * t4);
#pragma unroll
        for (int tl = 0; tl < 2; tl++) {
            mbar_wait(vbar + tl * 16, 0);
            uint32_t r[4][4];
#pragma unroll
            for (int ks = 0; ks < 4; ks++) ldsm4t(r[ks], va + tl * TILE_BYTES + ks * 2048);
#pragma unroll
            for (int ks = 0; ks < 4; ks++) {
                const uint32_t a[4] = {pa[4 * tl + ks][0], 0u, pa[4 * tl + ks][1], 0u};
                mma16816(acc[2 * (ks & 1)], a, r[ks][0], r[ks][1]);
                mma16816(acc[2 * (ks & 1) + 1], a, r[ks][2], r[ks][3]);
            }
        }
        stg_relaxed2_if(g < 2, o_dst, ~pack_bf((acc[0][0] + acc[2][0]) * rinv, (acc[0][1] + acc[2][1]) * rinv),
                        ~pack_bf((acc[1][0] + acc[3][0]) * rinv, (acc[1][1] + acc[3][1]) * rinv));
    }
    PROF(7);
    const int side = lds32(sb + OFF_SIDE);
    const uint32_t red_st = pin(sb + SC_E4 + ((warp * 4 + 2 * ((lane >> 3) & 1) + (lane >> 4)) * 8 + (lane & 7)) * 4);
    const uint32_t red_ld = pin(sb + SC_E4 + (lane & 15) * 8);
    const uint32_t* const in1 = pin(slot(SL_P1 + own, side) + tid * 4);
    const uint32_t* const in2a = pin(slot(SL_P2 + 2 * own, side) + (tid >> 3) * 32 + (tid & 7) * 2);
    const uint32_t* const in2b = pin(slot(SL_P2 + 2 * own + 1, side) + (tid >> 3) * 32 + (tid & 7) * 2);
    uint32_t* const out_dst = pin((uint32_t*)(p.out + ((lane >> 2) & 3) * D + 8 * own) + t4);
    uint32_t* const x1_dst = pin(slot(SL_X1 + own / 30, lane >> 4) + (own % 30) * 32 + (lane & 15));
    uint32_t* const rst = pin(tid >= 32 && tid < 56 ? mod_slot(lane >> 2, own, lane & 3) : own < 32 && tid == 64 ? g_clr + own * 4 : own < 8 && tid == 96 ? g_phase + own * 32 : nullptr);
    const uint32_t xw = lds32(sb + OWN_X + (lane & 15) * 4), ga_w = lds32(sb + OWN_GA + (lane & 15) * 4);
    uint32_t cs[15];
    uint32_t* dst2[5];
    uint32_t w2a[5];
#pragma unroll
    for (int j = 0; j < 10; j++) cs[j] = lds32(sb + OFF_VB + ((g & 1) * 4 + (g >> 1)) * VEC_STRIDE + warp * 160 + t4 * 4 + j * 16);
#pragma unroll
    for (int i = 0; i < 5; i++) {
        cs[10 + i] = lds32(sb + OFF_VB + (g >> 1) * VEC_STRIDE + warp * 160 + (g & 1) * 16 + t4 * 4 + i * 32);
        const uint2 t = lds64(sb + OFF_TAB2 + warp * 40 + i * 8);
        dst2[i] = slot_ptr((t4 < 2 ? t.x : t.y) + g * 8 + (t4 & 1) * 4);
        const int cc = 2 * (warp * 5 + i) + (mi & 1);
        w2a[i] = pin(sb + X_W2 + (cc >> 3) * 4096 + (r8 + 8 * (mi >> 1)) * 128 + (((cc & 7) ^ r8) << 4));
    }
    const uint32_t piv = lds32(sb + OFF_STAT + (g >> 1) * 8);
    const uint32_t* const xin = pin(slot(SL_X1 + warp / 3, side) + ((warp % 3) * 10 + (g & 1)) * 32 + (g >> 1) * 4 + t4);
    const uint32_t w1a = pin(sb + X_W1 + (warp * 80 + r8 + 8 * (mi >> 1)) * 64 + (((mi & 1) ^ ((r8 >> 1) & 3)) << 4));
    const uint32_t w1bar = pin(bar_w1 + (warp >> 1) * 8), w2bar = pin(bar_w2 + (warp + (warp >> 2)) * 8);
    const uint32_t obar = pin(NB_O + warp), hbar = pin((NB_H1 + (warp >> 1)) & 15);
    const uint32_t ab_st = pin(sb + SC_AB + warp * 1024 + lane * 16), y_st = pin(sb + SC_Y + warp * 512 + lane * 8), s_st = pin(sb + SC_ST + (t4 * 8 + warp) * 8);
    const uint32_t h_ld = pin(sb + SC_H1 + ((g & 3) ^ (2 * (f & 1) + ((f >> 1) & 1))) * 64 + t4 * 16);
    {
        const int kap = 2 * (head & 1) + ((head >> 1) & 1);
        const uint32_t wa = pin(sb + X_WO + (mt >> 1) * (DH * 64) + (r8 + 8 * (mi >> 1)) * 64 + ((((mt & 1) * 2 + (mi & 1)) ^ ((r8 >> 1) & 3)) << 4));
        const uint32_t oa = pin(sb + OFF_O + ((g & 3) ^ kap) * O_STRIDE + t4 * 8);
        uint32_t* dst[4];
#pragma unroll
        for (int i = 0; i < 2; i++) {
            const uint2 t = lds64(sb + OFF_TAB1 + (bown * 20 + 2 * mt + (warp < 2 ? 4 * i : 0)) * 4);
            dst[2 * i] = slot_ptr(t.x + g * 16 + t4 * 8);
            dst[2 * i + 1] = slot_ptr(t.y + g * 16 + t4 * 8);
        }
        PROF(6);
        const uint32_t wobar = pin(bar_wo + (mt >> 1) * 8);
        asm volatile("bar.sync %0, 64;" ::"r"(obar) : "memory");
        uint2 ob[8];
#pragma unroll
        for (int ks = 0; ks < 8; ks++) ob[ks] = lds64(oa + ks * 32);
#pragma unroll
        for (int m = 0; m < 2; m++) {
            if (m == 0 || warp < 2) {
                mbar_wait(wobar + m * 8, 0);
                PROF(8);
                uint32_t wf[8][4];
#pragma unroll
                for (int ks = 0; ks < 8; ks++) ldsm4t(wf[ks], wa + m * (DH * 64) + ks * 1024);
                float c[4][4];
#pragma unroll
                for (int ks = 0; ks < 8; ks++) {
                    if (ks < 4) c[ks][0] = c[ks][1] = c[ks][2] = c[ks][3] = 0.f;
                    mma16816(c[ks & 3], wf[ks], ob[ks].x, ob[ks].y);
                }
                stg_relaxed2_if(t4 < 2, dst[2 * m], flag((c[0][0] + c[1][0]) + (c[2][0] + c[3][0])), flag((c[0][1] + c[1][1]) + (c[2][1] + c[3][1])));
                stg_relaxed2_if(t4 < 2, dst[2 * m + 1], flag((c[0][2] + c[1][2]) + (c[2][2] + c[3][2])), flag((c[0][3] + c[1][3]) + (c[2][3] + c[3][3])));
            }
        }
    }
    PROF(9);
    uint32_t x1w = 0;
    if (is_owner) {
        sts_f32(red_st, poll_e4(in1));
        PROF(11);
        nbar_sync<NB_E4, 256>();
        if (warp == 0) {
            float2 a[8];
#pragma unroll
            for (int w = 0; w < 8; w++) a[w] = lds_f32x2(red_ld + w * 128);
            const uint32_t aw = pack_bf(((a[0].x + a[1].x) + (a[2].x + a[3].x)) + ((a[4].x + a[5].x) + (a[6].x + a[7].x)),
                                        ((a[0].y + a[1].y) + (a[2].y + a[3].y)) + ((a[4].y + a[5].y) + (a[6].y + a[7].y)));
            x1w = bf2_add(xw, bf2_mul(ga_w, aw));
            stg_relaxed(x1_dst, x1w ^ 0x80008000u);
            if (lane == 0) mbar_arrive(bar_x1);
        }
        if (rst) stg_zero4(rst);
    }
    PROF(12);
    if (is_f) {
        uint32_t f1[5][2][4], f2[5][2][4];
        uint32_t d[6];
        auto load_x1 = [&] {
#pragma unroll
            for (int i = 0; i < 5; i++) d[i] = ldg_relaxed32(xin + i * 64);
        };
        auto have_x1 = [&] { return __all_sync(0xffffffffu, __vimin3_u32(__vimin3_u32(d[0], d[1], d[2]), d[3], d[4]) != 0u); };
        mbar_wait(w1bar, 0);
        load_x1();
        {
#pragma unroll
            for (int i = 0; i < 5; i++) { ldsm4t(f1[i][0], w1a + i * 1024); ldsm4t(f1[i][1], (w1a ^ 32) + i * 1024); }
            float c[2][4];
#pragma unroll
            for (int m = 0; m < 2; m++) c[m][0] = c[m][1] = c[m][2] = c[m][3] = 0.f;
#pragma unroll
            for (int i = 0; i < 5; i++) { mma16816(c[0], f1[i][0], cs[2 * i], cs[2 * i + 1]); mma16816(c[1], f1[i][1], cs[2 * i], cs[2 * i + 1]); }
#pragma unroll
            for (int i = 0; i < 5; i++) { cs[2 * i] = pin(odd ? 0u : cs[10 + i]); cs[2 * i + 1] = pin(odd ? cs[10 + i] : 0u); }
#pragma unroll
            for (int m = 0; m < 2; m++) sts128(ab_st + m * 512, make_uint4(__float_as_uint(c[m][0]), __float_as_uint(c[m][1]), __float_as_uint(c[m][2]), __float_as_uint(c[m][3])));
            nbar_arrive<NB_AB, 320>();
            d[0] |= __float_as_uint(c[1][3]) & (side >> 1);
        }
        PROF(10);
        if (!have_x1()) {
            asm volatile("{\n.reg .pred q;\n.reg .b32 t, n;\nmov.u32 n, 0;\n"
                         "L_%=:\nld.relaxed.gpu.global.u32 %0, [%5];\nld.relaxed.gpu.global.u32 %1, [%5 + 256];\nld.relaxed.gpu.global.u32 %2, [%5 + 512];\n"
                         "ld.relaxed.gpu.global.u32 %3, [%5 + 768];\nld.relaxed.gpu.global.u32 %4, [%5 + 1024];\n"
                         "add.u32 n, n, 1;\nsetp.gt.u32 q, n, %6;\n@q trap;\nbar.warp.sync 0xffffffff;\n"
                         "min.u32 t, %0, %1;\nmin.u32 t, t, %2;\nmin.u32 t, t, %3;\nmin.u32 t, t, %4;\n"
                         "setp.ne.u32 q, t, 0;\nvote.sync.all.pred q, q, 0xffffffff;\n@!q bra.uni L_%=;\n}"
                         : "=&r"(d[0]), "=&r"(d[1]), "=&r"(d[2]), "=&r"(d[3]), "=&r"(d[4]) : "l"(xin), "n"(SPIN_LIMIT) : "memory");
        }
        PROF(13);
        {
            float y[2][4], st[4] = {0.f, 0.f, 0.f, 0.f};
            float z[2][4] = {};
#pragma unroll
            for (int m = 0; m < 2; m++) y[m][0] = y[m][1] = y[m][2] = y[m][3] = 0.f;
#pragma unroll
            for (int i = 0; i < 5; i++) d[i] = bf2_add(d[i], piv);
            d[5] = 0u;
#pragma unroll
            for (int i = 0; i < 5; i++) {
                if (i < 3) {
                    const uint32_t a[4] = {d[2 * i], 0x3f803f80u, d[2 * i + 1], 0x3f803f80u};
                    mma16816(st, a, d[2 * i], d[2 * i + 1]);
                }
                const uint32_t y0 = bf2_mul(d[i], cs[2 * i]), y1 = bf2_mul(d[i], cs[2 * i + 1]);
                if (i & 1) { mma16816(z[0], f1[i][0], y0, y1); mma16816(z[1], f1[i][1], y0, y1); }
                else { mma16816(y[0], f1[i][0], y0, y1); mma16816(y[1], f1[i][1], y0, y1); }
            }
            const float q = odd ? st[1] : st[0];
            const float q2 = q + __shfl_xor_sync(0xffffffffu, q, 4);
            if (diag && !odd) sts_f32x2(s_st, q2, st[2] + st[3]);
#pragma unroll
            for (int m = 0; m < 2; m++) sts_f32x2(y_st + m * 256, (z[m][0] + z[m][1]) + (y[m][0] + y[m][1]), (z[m][2] + z[m][3]) + (y[m][2] + y[m][3]));
        }
        nbar_arrive<NB_Y, 320>();
        PROF(14);
        mbar_wait(w2bar, 0);
        mbar_wait(w2bar + 8, 0);
#pragma unroll
        for (int i = 0; i < 5; i++) { ldsm4t(f2[i][0], w2a[i]); ldsm4t(f2[i][1], w2a[i] + 2048); }
        asm volatile("bar.sync %0, 128;" ::"r"(hbar) : "memory");
        PROF(15);
        {
            const uint4 hb = lds128(h_ld);
            float c[5][4];
#pragma unroll
            for (int i = 0; i < 5; i++) { c[i][0] = c[i][1] = c[i][2] = c[i][3] = 0.f; mma16816(c[i], f2[i][0], hb.x, hb.y); }
#pragma unroll
            for (int i = 0; i < 5; i++) {
                mma16816(c[i], f2[i][1], hb.z, hb.w);
                stg_relaxed(dst2[i], ~pack_bf(t4 < 2 ? c[i][0] : c[i][2], t4 < 2 ? c[i][1] : c[i][3]));
            }
        }
    }
    PROF(16);
    if (is_owner) {
        const uint32_t b2w = lds32(sb + OWN_B2 + (lane & 15) * 4), gb_ld = pin(sb + OWN_GB + (lane & 15) * 8);
        sts_f32(red_st + (SC_E6 - SC_E4), poll_e6(in2a, in2b, tid < NF * 8 - 256));
        PROF(17);
        if (warp != 0) {
            nbar_arrive<NB_E6, 320>();
        } else {
            nbar_sync<NB_E6, 320>();
            float2 a[8];
#pragma unroll
            for (int i = 0; i < 8; i++) a[i] = lds_f32x2(red_ld + (SC_E6 - SC_E4) + i * 128);
            const float2 g0 = lds_f32x2(gb_ld), g1 = lds_f32x2(gb_ld + 128);
            const uint32_t gb_w = pack_bf(g0.x + g1.x, g0.y + g1.y);
            const uint32_t aw = pack_bf(((a[0].x + a[1].x) + (a[2].x + a[3].x)) + ((a[4].x + a[5].x) + (a[6].x + a[7].x)),
                                        ((a[0].y + a[1].y) + (a[2].y + a[3].y)) + ((a[4].y + a[5].y) + (a[6].y + a[7].y)));
            x1w = bf2_add(x1w, bf2_mul(gb_w, bf2_add(aw, b2w)));
            if (lane < 16) asm volatile("st.global.u32 [%0], %1;" ::"l"(out_dst), "r"(x1w) : "memory");
        }
    }
    PROF(18);
    PROF_DUMP;
}

typedef CUresult (*EncodeFn)(CUtensorMap*, CUtensorMapDataType, cuuint32_t, void*, const cuuint64_t*, const cuuint64_t*, const cuuint32_t*,
                             const cuuint32_t*, CUtensorMapInterleave, CUtensorMapSwizzle, CUtensorMapL2promotion, CUtensorMapFloatOOBfill);

static CUtensorMap make_map(EncodeFn enc, const void* ptr, int cols, int rows, int box_cols, int box_rows, CUtensorMapSwizzle sw,
                            CUtensorMapL2promotion promo = CU_TENSOR_MAP_L2_PROMOTION_NONE) {
    CUtensorMap m;
    cuuint64_t dims[2] = {(cuuint64_t)cols, (cuuint64_t)rows};
    cuuint64_t strides[1] = {(cuuint64_t)cols * 2};
    cuuint32_t box[2] = {(cuuint32_t)box_cols, (cuuint32_t)box_rows};
    cuuint32_t es[2] = {1, 1};
    enc(&m, CU_TENSOR_MAP_DATA_TYPE_BFLOAT16, 2, const_cast<void*>(ptr), dims, strides, box, es, CU_TENSOR_MAP_INTERLEAVE_NONE, sw,
        promo, CU_TENSOR_MAP_FLOAT_OOB_FILL_NONE);
    return m;
}

}

extern "C" void kernel_launch(void* const* d_in, const int* in_sizes, int n_in, void* d_out, int out_size) {
    (void)in_sizes; (void)n_in; (void)out_size;
    static EncodeFn enc = nullptr;
    if (!enc) {
        void* fn = nullptr;
        cudaDriverEntryPointQueryResult qr;
        cudaGetDriverEntryPoint("cuTensorMapEncodeTiled", &fn, cudaEnableDefault, &qr);
        enc = (EncodeFn)fn;
        cudaFuncSetAttribute(fused_kernel, cudaFuncAttributeMaxDynamicSharedMemorySize, SMEM_BYTES);
    }
    Params p;
    p.x = (const __nv_bfloat16*)d_in[0];
    p.kc = (const __nv_bfloat16*)d_in[1];
    p.vc = (const __nv_bfloat16*)d_in[2];
    p.b1 = (const __nv_bfloat16*)d_in[7];
    p.b2 = (const __nv_bfloat16*)d_in[9];
    p.c = (const __nv_bfloat16*)d_in[10];
    p.out = (__nv_bfloat16*)d_out;
    CUtensorMap tm_wmod = make_map(enc, d_in[11], NMOD, D, 32, 160, CU_TENSOR_MAP_SWIZZLE_64B, CU_TENSOR_MAP_L2_PROMOTION_L2_128B);
    CUtensorMap tm_wq = make_map(enc, d_in[3], NH * DH, D, 32, 160, CU_TENSOR_MAP_SWIZZLE_64B, CU_TENSOR_MAP_L2_PROMOTION_L2_128B);
    CUtensorMap tm_wo = make_map(enc, d_in[4], D, NH * DH, 32, 128, CU_TENSOR_MAP_SWIZZLE_64B);
    CUtensorMap tm_w1 = make_map(enc, d_in[6], FF, D, 32, 160, CU_TENSOR_MAP_SWIZZLE_64B);
    CUtensorMap tm_w2 = make_map(enc, d_in[8], D, FF, 64, 32, CU_TENSOR_MAP_SWIZZLE_128B);
    CUtensorMap tm_v = make_map(enc, d_in[2], DH, NB * NH * SK, 64, TILE_KEYS, CU_TENSOR_MAP_SWIZZLE_128B);
    CUtensorMap tm_gb = make_map(enc, d_in[11], NMOD, D, 8, 160, CU_TENSOR_MAP_SWIZZLE_NONE, CU_TENSOR_MAP_L2_PROMOTION_L2_128B);
    fused_kernel<<<NCTA, NTHREADS, SMEM_BYTES>>>(p, tm_wmod, tm_wq, tm_wo, tm_w1, tm_w2, tm_v, tm_gb);
}
```

```cpp
#include <cuda_runtime.h>
#include <cuda.h>
#include <cuda_bf16.h>
#include <stdint.h>
#include <stdlib.h>

namespace {

constexpr int NB = 4, D = 640, NH = 32, DH = 128, SK = 8192, WIN = 2048, FF = 1728, NMOD = 6 * D;
constexpr int NCTA = 128;
constexpr int NOWN = 80;
constexpr int NF = 54;
constexpr int NTHREADS = 320;
constexpr int TILE_KEYS = 64;
constexpr int TILE_BYTES = TILE_KEYS * DH * 2;
constexpr int NITEM = 2 * WIN / TILE_KEYS;
constexpr int NS = 8;
constexpr int NMODC = 120;
constexpr int SPIN_LIMIT = 1 << 18;
#define INFLIGHT 3
#define WQ_DELAY 500
#define MOD_T 4200
#define Q_PAUSE 1100
#define PACE_A 7500
#define PACE_TAU 635
#define ROT(c) 0
#define PF_END 16
#define PH_FIRST 24
#define PH_LAG 5
#define LAT_T 2300
#define WO_T -1050
#define WO_S 250
#define W1_T 860
#define W2_T 1560
#define GB_T 2350
#define GB_EV 700
#define CLR_CHECK 28000
constexpr int NPROBE = 8, PROBE_END = 10000;
constexpr int SEG_J = 8;

constexpr int OFF_RING = 0;
constexpr int OFF_X = OFF_RING + NS * TILE_BYTES;
constexpr int X_WM = OFF_X;
constexpr int X_WQ = OFF_X + D * 64;
constexpr int X_WO = OFF_X;
constexpr int X_W1 = X_WO + 5 * DH * 64;
constexpr int X_END = X_W1 + D * 64;
constexpr int X_W2 = OFF_RING;
constexpr int X_GB = OFF_RING + 3 * TILE_BYTES;
static_assert(X_WQ + D * 64 <= X_END, "prologue weights must fit");
constexpr int VEC_STRIDE = 1296;
constexpr int OFF_VA = X_END;
constexpr int OFF_VB = OFF_VA + 4 * VEC_STRIDE;
constexpr int OFF_RED = OFF_VB + 4 * VEC_STRIDE;
constexpr int OFF_ML = OFF_RED + 4 * VEC_STRIDE;
constexpr int O_STRIDE = 288;
constexpr int OFF_O = OFF_ML + 64;
constexpr int OFF_Q = OFF_O + 4 * O_STRIDE;
constexpr int OFF_OWN = OFF_Q + 256;
constexpr int OWN_X = OFF_OWN, OWN_B2 = OWN_X + 64, OWN_GA = OWN_B2 + 64, OWN_GB = OWN_GA + 64, OWN_B1 = OWN_GB + 256;
constexpr int OFF_STAT = OWN_B1 + 128;
constexpr int OFF_TAB1 = OFF_STAT + 32;
constexpr int OFF_TAB2 = OFF_TAB1 + NOWN * 4;
constexpr int OFF_SIDE = OFF_TAB2 + NOWN * 4;
constexpr int OFF_BAR = OFF_SIDE + 8;
constexpr int NBAR = 2 * NS + 32;
constexpr int SMEM_BYTES = OFF_BAR + NBAR * 8;
constexpr int SC_OP = OFF_RING + 4 * TILE_BYTES;
constexpr int SC_AB = SC_OP + 4096;
constexpr int SC_Y = SC_AB + 8192;
constexpr int SC_ST = SC_Y + 4096;
constexpr int SC_E4 = SC_ST + 256;
constexpr int SC_E6 = SC_E4 + 1024;
constexpr int SC_P = SC_E6 + 1024;
constexpr int SC_H1 = SC_P + 256;
constexpr int SC_DUMP = SC_H1 + 256;
static_assert(SMEM_BYTES <= 232448, "smem");
static_assert(OFF_BAR % 8 == 0 && OFF_X % 1024 == 0 && X_WQ % 512 == 0 && X_W1 % 512 == 0 && OFF_VA % 16 == 0 && OFF_RED % 16 == 0 && OFF_ML % 16 == 0 && OFF_O % 16 == 0 && OFF_Q % 16 == 0, "align");
constexpr int NB_O = 2  , NB_E4 = 10, NB_E6 = 11, NB_AB = 12, NB_Y = 13, NB_H1 = 14  ;

__device__ __align__(128) uint32_t g_mod[NMODC * 64];
__device__ __align__(128) uint32_t g_q[NCTA * 128];
__device__ __align__(128) uint32_t g_clr[NCTA];
__device__ __align__(128) uint32_t g_phase[8 * 32];
constexpr int SL_P1 = 0;
constexpr int SL_P2 = SL_P1 + NOWN;
constexpr int SL_O = SL_P2 + 2 * NOWN;
constexpr int SL_X1 = SL_O + 8;
constexpr int SL_SIDE = SL_X1 + 3;
static_assert(SL_SIDE < 256, "one 2 MB page");
__device__ uint32_t g_slots[2 * 256 * 2048];
__device__ __forceinline__ uint32_t* slot(int i, int side) {
    const size_t base = ((size_t)g_slots + 0x1fffff) & ~(size_t)0x1fffff;
    return (uint32_t*)base + i * 2048 + (((__popc(i & 0x59) ^ side) & 1) << 10);
}
#define PROF_DECL
#define HPROF(i) do { } while (0)
#define PROF(i) do { } while (0)
#define PROF_DUMP do { } while (0)

__device__ __forceinline__ uint32_t smem_u32(const void* p) { return (uint32_t)__cvta_generic_to_shared(p); }
__device__ __forceinline__ void mbar_init(uint32_t bar, uint32_t cnt) { asm volatile("mbarrier.init.shared::cta.b64 [%0], %1;" ::"r"(bar), "r"(cnt) : "memory"); }
__device__ __forceinline__ void mbar_expect_tx(uint32_t bar, uint32_t bytes) { asm volatile("mbarrier.arrive.expect_tx.shared::cta.b64 _, [%0], %1;" ::"r"(bar), "r"(bytes) : "memory"); }
__device__ __forceinline__ void mbar_arrive(uint32_t bar) { asm volatile("mbarrier.arrive.shared::cta.b64 _, [%0];" ::"r"(bar) : "memory"); }
__device__ __forceinline__ void mbar_wait(uint32_t bar, uint32_t parity) {
    uint32_t ok;
    int it = 0;
    while (true) {
        asm volatile("{\n.reg .pred p;\nmbarrier.try_wait.parity.shared::cta.b64 p, [%1], %2;\nselp.u32 %0, 1, 0, p;\n}" : "=r"(ok) : "r"(bar), "r"(parity) : "memory");
        if (ok) break;
        if (++it > SPIN_LIMIT) __trap();
    }
}
__device__ __forceinline__ void bulk_load(uint32_t dst, const void* src, uint32_t bytes, uint32_t bar, uint64_t pol) {
    asm volatile("cp.async.bulk.shared::cluster.global.mbarrier::complete_tx::bytes.L2::cache_hint [%0], [%1], %2, [%3], %4;"
                 ::"r"(dst), "l"(src), "r"(bytes), "r"(bar), "l"(pol) : "memory");
}
__device__ __forceinline__ void bar_cons() { asm volatile("bar.sync 1, 256;" ::: "memory"); }
template <int ID, int N> __device__ __forceinline__ void nbar_sync() { asm volatile("bar.sync %0, %1;" ::"n"(ID), "n"(N) : "memory"); }
template <int ID, int N> __device__ __forceinline__ void nbar_arrive() { asm volatile("bar.arrive %0, %1;" ::"n"(ID), "n"(N) : "memory"); }
__device__ __forceinline__ bool mbar_test(uint32_t bar, uint32_t parity) {
    uint32_t ok;
    asm volatile("{\n.reg .pred p;\nmbarrier.test_wait.parity.shared::cta.b64 p, [%1], %2;\nselp.u32 %0, 1, 0, p;\n}" : "=r"(ok) : "r"(bar), "r"(parity) : "memory");
    return ok;
}
__device__ __forceinline__ uint32_t pin(uint32_t v) { asm volatile("" : "+r"(v)); return v; }
template <class T> __device__ __forceinline__ T pin_hard(T v) { return __shfl_sync(0xffffffffu, v, threadIdx.x & 31); }
template <class T> __device__ __forceinline__ T* pin(T* v) { asm volatile("" : "+l"(v)); return v; }
__device__ __forceinline__ void ldsm4(uint32_t (&a)[4], uint32_t addr) {
    asm volatile("ldmatrix.sync.aligned.m8n8.x4.shared.b16 {%0,%1,%2,%3}, [%4];" : "=r"(a[0]), "=r"(a[1]), "=r"(a[2]), "=r"(a[3]) : "r"(addr) : "memory");
}
__device__ __forceinline__ void ldsm4t(uint32_t (&a)[4], uint32_t addr) {
    asm volatile("ldmatrix.sync.aligned.m8n8.x4.trans.shared.b16 {%0,%1,%2,%3}, [%4];" : "=r"(a[0]), "=r"(a[1]), "=r"(a[2]), "=r"(a[3]) : "r"(addr) : "memory");
}
__device__ __forceinline__ void mma16816(float (&c)[4], const uint32_t (&a)[4], uint32_t b0, uint32_t b1) {
    asm volatile("mma.sync.aligned.m16n8k16.row.col.f32.bf16.bf16.f32 {%0,%1,%2,%3}, {%4,%5,%6,%7}, {%8,%9}, {%0,%1,%2,%3};"
                 : "+f"(c[0]), "+f"(c[1]), "+f"(c[2]), "+f"(c[3]) : "r"(a[0]), "r"(a[1]), "r"(a[2]), "r"(a[3]), "r"(b0), "r"(b1));
}
__device__ __forceinline__ uint32_t lds32(uint32_t addr) { uint32_t v; asm volatile("ld.shared.u32 %0, [%1];" : "=r"(v) : "r"(addr) : "memory"); return v; }
__device__ __forceinline__ float lds_f32(uint32_t addr) { float v; asm volatile("ld.shared.f32 %0, [%1];" : "=f"(v) : "r"(addr) : "memory"); return v; }
__device__ __forceinline__ float2 lds_f32x2(uint32_t addr) { float2 v; asm volatile("ld.shared.v2.f32 {%0,%1}, [%2];" : "=f"(v.x), "=f"(v.y) : "r"(addr) : "memory"); return v; }
__device__ __forceinline__ float4 lds_f32x4(uint32_t addr) { float4 v; asm volatile("ld.shared.v4.f32 {%0,%1,%2,%3}, [%4];" : "=f"(v.x), "=f"(v.y), "=f"(v.z), "=f"(v.w) : "r"(addr) : "memory"); return v; }
__device__ __forceinline__ uint2 lds64(uint32_t addr) { uint2 v; asm volatile("ld.shared.v2.u32 {%0,%1}, [%2];" : "=r"(v.x), "=r"(v.y) : "r"(addr) : "memory"); return v; }
__device__ __forceinline__ uint4 lds128(uint32_t addr) { uint4 v; asm volatile("ld.shared.v4.u32 {%0,%1,%2,%3}, [%4];" : "=r"(v.x), "=r"(v.y), "=r"(v.z), "=r"(v.w) : "r"(addr) : "memory"); return v; }
__device__ __forceinline__ void sts16(uint32_t addr, uint32_t v) { asm volatile("st.shared.b16 [%0], %1;" ::"r"(addr), "h"((unsigned short)v) : "memory"); }
__device__ __forceinline__ void sts32(uint32_t addr, uint32_t v) { asm volatile("st.shared.u32 [%0], %1;" ::"r"(addr), "r"(v) : "memory"); }
__device__ __forceinline__ void sts_f32(uint32_t addr, float v) { asm volatile("st.shared.f32 [%0], %1;" ::"r"(addr), "f"(v) : "memory"); }
__device__ __forceinline__ void sts_f32x2(uint32_t addr, float a, float b) { asm volatile("st.shared.v2.f32 [%0], {%1,%2};" ::"r"(addr), "f"(a), "f"(b) : "memory"); }
__device__ __forceinline__ void sts128(uint32_t addr, uint4 v) { asm volatile("st.shared.v4.u32 [%0], {%1,%2,%3,%4};" ::"r"(addr), "r"(v.x), "r"(v.y), "r"(v.z), "r"(v.w) : "memory"); }
__device__ __forceinline__ uint4 ldg_relaxed(const uint32_t* p) {
    uint4 v;
    asm volatile("ld.relaxed.gpu.global.v4.u32 {%0,%1,%2,%3}, [%4];" : "=r"(v.x), "=r"(v.y), "=r"(v.z), "=r"(v.w) : "l"(p) : "memory");
    return v;
}
__device__ __forceinline__ void ldg_relaxed_if(bool on, uint4& v, const uint32_t* p) {
    asm volatile("{\n.reg .pred q;\nsetp.ne.u32 q, %5, 0;\n@q ld.relaxed.gpu.global.v4.u32 {%0,%1,%2,%3}, [%4];\n}"
                 : "+r"(v.x), "+r"(v.y), "+r"(v.z), "+r"(v.w) : "l"(p), "r"((uint32_t)on) : "memory");
}
__device__ __forceinline__ void stg_relaxed2_if(bool on, uint32_t* p, uint32_t a, uint32_t b) {
    asm volatile("{\n.reg .pred q;\nsetp.ne.u32 q, %3, 0;\n@q st.relaxed.gpu.global.v2.u32 [%0], {%1,%2};\n}" ::"l"(p), "r"(a), "r"(b), "r"((uint32_t)on) : "memory");
}
__device__ __forceinline__ uint32_t ldg_relaxed32(const uint32_t* p) { uint32_t v; asm volatile("ld.relaxed.gpu.global.u32 %0, [%1];" : "=r"(v) : "l"(p) : "memory"); return v; }
__device__ __forceinline__ void stg_relaxed(uint32_t* p, uint32_t v) { asm volatile("st.relaxed.gpu.global.u32 [%0], %1;" ::"l"(p), "r"(v) : "memory"); }
__device__ __forceinline__ void stg_zero4(uint32_t* p) { asm volatile("st.relaxed.gpu.global.v4.u32 [%0], {%1,%1,%1,%1};" ::"l"(p), "r"(0u) : "memory"); }
__device__ __forceinline__ bool ready(const uint4& v) { return (v.x != 0u) & (v.y != 0u) & (v.z != 0u) & (v.w != 0u); }
__device__ __forceinline__ uint32_t min4(const uint4& v) { return min(__vimin3_u32(v.x, v.y, v.z), v.w); }
__device__ __forceinline__ uint4 inv4(const uint4& v) { return make_uint4(~v.x, ~v.y, ~v.z, ~v.w); }
__device__ __forceinline__ uint32_t pack_bf(float lo, float hi) {
    uint32_t r;
    asm("cvt.rn.bf16x2.f32 %0, %1, %2;" : "=r"(r) : "f"(hi), "f"(lo));
    return r;
}
__device__ __forceinline__ float bfr(float x) { return __uint_as_float(pack_bf(0.f, x) & 0xffff0000u); }
__device__ __forceinline__ float bf_lo(uint32_t w) { return __uint_as_float(w << 16); }
__device__ __forceinline__ float bf_hi(uint32_t w) { return __uint_as_float(w & 0xffff0000u); }
__device__ __forceinline__ float bf2f(__nv_bfloat16 v) { return __bfloat162float(v); }
__device__ __forceinline__ float ex2(float x) { float y; asm("ex2.approx.ftz.f32 %0, %1;" : "=f"(y) : "f"(x)); return y; }
__device__ __forceinline__ float rcp_fast(float x) { float y; asm("rcp.approx.ftz.f32 %0, %1;" : "=f"(y) : "f"(x)); return y; }
__device__ __forceinline__ float rsqrt_fast(float x) { float y; asm("rsqrt.approx.ftz.f32 %0, %1;" : "=f"(y) : "f"(x)); return y; }
__device__ __forceinline__ float sqrt_fast(float x) { float y; asm("sqrt.approx.f32 %0, %1;" : "=f"(y) : "f"(x)); return y; }
__device__ __forceinline__ uint32_t bf2_add(uint32_t a, uint32_t b) { uint32_t r; asm("add.rn.bf16x2 %0, %1, %2;" : "=r"(r) : "r"(a), "r"(b)); return r; }
__device__ __forceinline__ uint32_t bf2_sub(uint32_t a, uint32_t b) { uint32_t r; asm("sub.rn.bf16x2 %0, %1, %2;" : "=r"(r) : "r"(a), "r"(b)); return r; }
__device__ __forceinline__ uint32_t bf2_mul(uint32_t a, uint32_t b) { uint32_t r; asm("mul.rn.bf16x2 %0, %1, %2;" : "=r"(r) : "r"(a), "r"(b)); return r; }
__device__ __forceinline__ uint32_t gtime32() { uint32_t c; asm volatile("mov.u32 %0, %%globaltimer_lo;" : "=r"(c)); return c; }
__device__ __forceinline__ uint32_t clock32() { uint32_t c; asm volatile("mov.u32 %0, %%clock;" : "=r"(c)); return c; }

__device__ __forceinline__ float warp_sum(float v) {
#pragma unroll
    for (int o = 16; o > 0; o >>= 1) v += __shfl_xor_sync(0xffffffffu, v, o);
    return v;
}

struct Params {
    const __nv_bfloat16 *x, *kw, *vw, *b1, *b2, *c;
    __nv_bfloat16* out;
};

__device__ __forceinline__ void tma2d(uint32_t dst, const CUtensorMap* tm, int x, int y, uint32_t bar) {
    asm volatile("cp.async.bulk.tensor.2d.shared::cluster.global.mbarrier::complete_tx::bytes [%0], [%1, {%2, %3}], [%4];"
                 ::"r"(dst), "l"(tm), "r"(x), "r"(y), "r"(bar) : "memory");
}

__device__ __forceinline__ void tma2d_hint(uint32_t dst, const CUtensorMap* tm, int x, int y, uint32_t bar, uint64_t pol) {
    asm volatile("cp.async.bulk.tensor.2d.shared::cluster.global.mbarrier::complete_tx::bytes.L2::cache_hint [%0], [%1, {%2, %3}], [%4], %5;"
                 ::"r"(dst), "l"(tm), "r"(x), "r"(y), "r"(bar), "l"(pol) : "memory");
}
__device__ __forceinline__ uint32_t flag(float v) { return __float_as_uint(v) | 1u; }
__device__ __forceinline__ uint32_t* slot_ptr(uint32_t lo) {
    uint32_t* r;
    asm volatile("mov.b64 %0, {%1, %2};" : "=l"(r) : "r"(lo), "r"((uint32_t)((size_t)slot(0, 0) >> 32)));
    return r;
}

__device__ __forceinline__ void load_bfrag(uint32_t vec, int stride, int k0, int g, int t, uint32_t& b0, uint32_t& b1) {
    uint32_t a = vec + (g & 3) * stride + (k0 + 2 * t) * 2;
    b0 = lds32(a);
    b1 = lds32(a + 16);
}

__device__ __forceinline__ void ln_finish(float pivot, float sum, float sumsq, uint32_t& m2, float& rden) {
    float dm = sum * (1.f / D);
    float var = fmaxf(sumsq * (1.f / D) - dm * dm, 0.f);
    float mean = pivot + dm;
    m2 = pack_bf(mean, mean);
    rden = rcp_fast(bfr(sqrt_fast(bfr(bfr(var) + 1e-5f))));
}
__device__ __forceinline__ uint32_t ln_mod_pair(uint32_t xw, uint32_t cw, uint32_t sw, uint32_t m2, float rden) {
    uint32_t d = bf2_sub(xw, m2);
    uint32_t ln = pack_bf(bf_lo(d) * rden, bf_hi(d) * rden);
    return bf2_add(bf2_mul(ln, bf2_add(cw, 0x3f803f80u)), sw);
}
__device__ __forceinline__ uint4 ln_mod4(const uint4& x, const uint4& c, const uint4& s, uint32_t m2, float rden) {
    return make_uint4(ln_mod_pair(x.x, c.x, s.x, m2, rden), ln_mod_pair(x.y, c.y, s.y, m2, rden),
                      ln_mod_pair(x.z, c.z, s.z, m2, rden), ln_mod_pair(x.w, c.w, s.w, m2, rden));
}
__device__ __forceinline__ void acc_stats(const uint4& v, float pv, float& s, float& q) {
    const float a0 = bf_lo(v.x) - pv, a1 = bf_hi(v.x) - pv, a2 = bf_lo(v.y) - pv, a3 = bf_hi(v.y) - pv;
    const float a4 = bf_lo(v.z) - pv, a5 = bf_hi(v.z) - pv, a6 = bf_lo(v.w) - pv, a7 = bf_hi(v.w) - pv;
    s += ((a0 + a1) + (a2 + a3)) + ((a4 + a5) + (a6 + a7));
    q += (fmaf(a0, a0, a1 * a1) + fmaf(a2, a2, a3 * a3)) + (fmaf(a4, a4, a5 * a5) + fmaf(a6, a6, a7 * a7));
}
__device__ __forceinline__ uint32_t* mod_slot(int kind, int j, int b) { return g_mod + (kind * 20 + (j >> 2)) * 64 + b * 16 + (j & 3) * 4; }

template <int N>
__device__ __forceinline__ void poll_n(uint4 (&v)[N], const uint32_t* const* ptr, const bool* on) {
    bool pend[N];
#pragma unroll
    for (int i = 0; i < N; i++) pend[i] = on[i];
    int it = 0;
    while (true) {
#pragma unroll
        for (int i = 0; i < N; i++) if (pend[i]) v[i] = ldg_relaxed(ptr[i]);
        bool any = false;
#pragma unroll
        for (int i = 0; i < N; i++) { pend[i] = pend[i] && !ready(v[i]); any |= pend[i]; }
        if (!__any_sync(0xffffffffu, any)) break;
        if (++it > SPIN_LIMIT) __trap();
    }
#pragma unroll
    for (int i = 0; i < N; i++) v[i] = inv4(v[i]);
}
__device__ __forceinline__ uint4 poll1(const uint32_t* p, bool on) {
    uint4 v[1] = {make_uint4(0, 0, 0, 0)};
    const uint32_t* const ptr[1] = {p};
    const bool o[1] = {on};
    poll_n<1>(v, ptr, o);
    return v[0];
}

#define OWNER_EXCHANGE_AND_VOTE \
    "shfl.sync.bfly.b32 a, z, 8, 31, 0xffffffff;\nshfl.sync.bfly.b32 b, y, 16, 31, 0xffffffff;\nshfl.sync.bfly.b32 c, w, 24, 31, 0xffffffff;\n" \
    "setp.ne.u32 q, t, 0;\nvote.sync.all.pred q, q, 0xffffffff;\n@!q bra.uni L_%=;\nadd.f32 a, a, x;\nadd.f32 b, b, c;\nadd.f32 %0, a, b;\n}"
__device__ __forceinline__ float poll_e4(const uint32_t* p) {
    float s;
    asm volatile("{\n.reg .pred q;\n.reg .b32 t, n, x, y, z, w, a, b, c;\nmov.u32 n, 0;\n"
                 "L_%=:\nld.relaxed.gpu.global.v4.u32 {x, y, z, w}, [%1];\nadd.u32 n, n, 1;\nsetp.gt.u32 q, n, %2;\n@q trap;\nbar.warp.sync 0xffffffff;\n"
                 "lop3.b32 t, x, y, z, 0x80;\nlop3.b32 t, t, w, 1, 0x80;\n" OWNER_EXCHANGE_AND_VOTE
                 : "=f"(s) : "l"(p), "n"(SPIN_LIMIT) : "memory");
    return s;
}
__device__ __forceinline__ float poll_e6(const uint32_t* pa, const uint32_t* pb, bool two) {
    float s;
    asm volatile("{\n.reg .pred q, r;\n.reg .b32 t, n, x, y, z, w, a, b, c, u0, u1, v0, v1;\nmov.u32 n, 0;\nsetp.ne.u32 r, %4, 0;\nmov.b32 v0, 0xffffffff;\nmov.b32 v1, 0xffffffff;\n"
                 "L_%=:\n@r ld.relaxed.gpu.global.v2.u32 {v0, v1}, [%3];\nld.relaxed.gpu.global.v2.u32 {u0, u1}, [%1];\nadd.u32 n, n, 1;\nsetp.gt.u32 q, n, %2;\n@q trap;\nbar.warp.sync 0xffffffff;\n"
                 "lop3.b32 a, u0, 0xffff0000, 0, 0x0c;\nlop3.b32 b, v0, 0xffff0000, 0, 0x0c;\nadd.f32 y, a, b;\n"
                 "lop3.b32 a, u1, 0xffff0000, 0, 0x0c;\nlop3.b32 b, v1, 0xffff0000, 0, 0x0c;\nadd.f32 w, a, b;\n"
                 "shl.b32 a, u1, 16;\nshl.b32 b, v1, 16;\nxor.b32 a, a, 0xffff0000;\nxor.b32 b, b, 0xffff0000;\nadd.f32 z, a, b;\n"
                 "shl.b32 a, u0, 16;\nshl.b32 b, v0, 16;\nxor.b32 a, a, 0xffff0000;\nxor.b32 b, b, 0xffff0000;\nadd.f32 x, a, b;\n"
                 "min.u32 t, u0, u1;\nmin.u32 t, t, v0;\nmin.u32 t, t, v1;\n" OWNER_EXCHANGE_AND_VOTE
                 : "=f"(s) : "l"(pa), "n"(SPIN_LIMIT), "l"(pb), "r"((uint32_t)two) : "memory");
    return s;
}

__device__ __forceinline__ void gelu_stage(uint32_t sb, int m, int lane) {
    const int g = lane >> 2, b = lane & 3;
    const uint32_t y_ld = pin_hard(sb + SC_Y + m * 256 + lane * 8), s_ld = pin_hard(sb + SC_ST + b * 64);
    const uint32_t h_st = pin_hard(sb + SC_H1 + b * 64 + (g >> 1) * 16 + m * 8 + (g & 1) * 2);
#pragma unroll 1
    for (int pass = 1 - m; pass < 2; pass++) {
        float a0 = 0.f, b0 = lds_f32(sb + OWN_B1 + (16 * m + g) * 4), a1 = 0.f, b1 = lds_f32(sb + OWN_B1 + (16 * m + g + 8) * 4);
        const float piv = bf_hi(lds32(sb + OFF_STAT + b * 8));
        if (pass) nbar_sync<NB_AB, 320>();
#pragma unroll
        for (int w = 0; w < 8; w++) {
            const float4 t = lds_f32x4(sb + SC_AB + w * 1024 + m * 512 + lane * 16);
            a0 += t.x; b0 += t.y; a1 += t.z; b1 += t.w;
        }
        sts128(sb + SC_DUMP + m * 512 + lane * 16, make_uint4(__float_as_uint(a0), __float_as_uint(b0), __float_as_uint(a1), __float_as_uint(b1)));
        if (pass) nbar_sync<NB_Y, 320>();
        float4 q[4];
        float2 y[8];
#pragma unroll
        for (int i = 0; i < 4; i++) q[i] = lds_f32x4(s_ld + i * 16);
#pragma unroll
        for (int w = 0; w < 8; w++) y[w] = lds_f32x2(y_ld + w * 512);
        const float dm = (((q[0].y + q[0].w) + (q[1].y + q[1].w)) + ((q[2].y + q[2].w) + (q[3].y + q[3].w))) * (1.f / D);
        const float sq = ((q[0].x + q[0].z) + (q[1].x + q[1].z)) + ((q[2].x + q[2].z) + (q[3].x + q[3].z));
        const float r = rsqrt_fast(fmaxf(fmaf(-dm, dm, fmaf(sq, 1.f / D, 1e-5f)), 1e-5f));
        const float y0 = ((y[0].x + y[1].x) + (y[2].x + y[3].x)) + ((y[4].x + y[5].x) + (y[6].x + y[7].x));
        const float y1 = ((y[0].y + y[1].y) + (y[2].y + y[3].y)) + ((y[4].y + y[5].y) + (y[6].y + y[7].y));
        const float dmr = piv - bfr(piv - dm);
        const float u0 = fmaf(r, fmaf(dmr, a0, -y0), b0), u1 = fmaf(r, fmaf(dmr, a1, -y1), b1);
        const float e0 = ex2(u0 * fmaf(u0 * u0, -0.044715f * 2.302208198144325f, -2.302208198144325f));
        const float e1 = ex2(u1 * fmaf(u1 * u1, -0.044715f * 2.302208198144325f, -2.302208198144325f));
        sts16(h_st, pack_bf(u0 * rcp_fast(1.f + e0), 0.f));
        sts16(h_st + 4, pack_bf(u1 * rcp_fast(1.f + e1), 0.f));
        if (pass) {
#pragma unroll
            for (int w = 0; w < 4; w++) asm volatile("bar.arrive %0, 128;" ::"r"((NB_H1 + w) & 15) : "memory");
        }
    }
}

struct Roles { bool is_f, is_owner; int f, own; };
__device__ __forceinline__ Roles roles(int cta) {
    Roles r;
    r.f = (cta * 27) >> 6;
    r.is_f = (((cta + 1) * 27) >> 6) != r.f;
    r.is_owner = !r.is_f || r.f % 9 == 4;
    r.own = r.is_f ? 74 + r.f / 9 : cta - r.f;
    return r;
}

__global__ void __launch_bounds__(NTHREADS, 1)
fused_kernel(const Params p, const __grid_constant__ CUtensorMap tm_wmod, const __grid_constant__ CUtensorMap tm_wq,
             const __grid_constant__ CUtensorMap tm_wo, const __grid_constant__ CUtensorMap tm_w1, const __grid_constant__ CUtensorMap tm_w2,
             const __grid_constant__ CUtensorMap tm_v, const __grid_constant__ CUtensorMap tm_gb) {
    extern __shared__ __align__(1024) unsigned char smem[];
    const uint32_t t_start = gtime32();
    const uint32_t sb = smem_u32(smem);
    const int cta = blockIdx.x;
    const int head = cta >> 2, bown = cta & 3;
    const int rot = ROT(cta);
    const char* kb;
    asm volatile("mad.wide.u32 %0, %1, %2, %3;" : "=l"(kb) : "r"(bown * NH + head), "n"(SK * DH * 2), "l"(p.kw));
    asm volatile("{\n.reg .pred q;\nsetp.lt.u32 q, %1, 256;\n@q prefetch.global.L2 [%0];\n}" ::"l"(kb + (size_t)rot * TILE_BYTES + threadIdx.x * 64), "r"(threadIdx.x) : "memory");
    uint64_t pol = 0;
    if (threadIdx.x == 256) {
        mbar_init(sb + OFF_BAR, 1);
        asm volatile("fence.mbarrier_init.release.cluster;" ::: "memory");
        asm volatile("createpolicy.fractional.L2::evict_first.b64 %0, 1.0;" : "=l"(pol));
        mbar_expect_tx(sb + OFF_BAR, TILE_BYTES);
        bulk_load(sb + OFF_RING, kb + (size_t)rot * TILE_BYTES, TILE_BYTES, sb + OFF_BAR, pol);
        if ((((head + 1) * 5) >> 4) != ((head * 5) >> 4)) {
            const uint32_t bar = sb + OFF_BAR + 2 * NS * 8;
            mbar_init(bar, 1);
            asm volatile("fence.mbarrier_init.release.cluster;" ::: "memory");
            mbar_expect_tx(bar, D * 64);
#pragma unroll 1
            for (int r = 0; r < D; r += 160) tma2d(sb + X_WM + r * 64, &tm_wmod, 32 * (((head * 5) >> 4) * 4 + bown), r, bar);
        }
    }
    const uint32_t bar_full = sb + OFF_BAR, bar_empty = bar_full + NS * 8;
    const uint32_t bar_wm = bar_empty + NS * 8, bar_wq = bar_wm + 8, bar_xfree = bar_wq + 8, bar_wo = bar_xfree + 8  ;
    const uint32_t bar_w1 = bar_wo + 40  , bar_w2 = bar_w1 + 32  , bar_help = bar_w2 + 80, bar_v = bar_help + 8  ;
    const uint32_t bar_gb = bar_v + 32  , bar_x1 = bar_gb + 32;
    const int tid = threadIdx.x, warp = tid >> 5, lane = tid & 31;
    const Roles role = roles(cta);
    const bool is_f = role.is_f, is_owner = role.is_owner;
    const int f = role.f, own = role.own;
    const bool crit = (((head + 1) * 5) >> 4) != ((head * 5) >> 4);
    const int mr = cta - ((head * 5) >> 4) * 4, mq = ((head * 5) >> 4) * 4 + bown;
    const int ml = mr * 31 / 44;
    const bool late = !crit && (mr + 1) * 31 / 44 != ml;
    const int mc = crit ? mq : ml < 60 ? 40 + ml : 58 + ml;
    const bool gb_own = is_owner && own < 72;

    PROF_DECL
    PROF(0);
    uint4 xa = make_uint4(0, 0, 0, 0), xb = xa, ca0 = xa, ca1 = xa, xs[3] = {xa, xa, xa};
    uint32_t own0 = 0;
    __nv_bfloat16 own2 = __float2bfloat16(0.f);
    if (warp < 8) {
        xa = *(const uint4*)(p.x + (tid & 3) * D + (tid >> 2) * 8);
        ca0 = ((const uint4*)p.c)[tid];
        if (tid < 64) { xb = *(const uint4*)(p.x + (tid & 3) * D + (64 + (tid >> 2)) * 8); ca1 = ((const uint4*)p.c)[256 + tid]; }
        if (warp < 4) {
#pragma unroll
            for (int i = 0; i < 3; i++) if (lane + 32 * i < 80) xs[i] = ((const uint4*)p.x)[warp * 80 + lane + 32 * i];
        } else if (warp == 4) {
            if (is_owner) own0 = *(const uint32_t*)((lane < 16 ? p.x + (lane >> 2) * D : p.b2) + 8 * own + 2 * (lane & 3));
            if (is_f) own2 = p.b1[32 * f + lane];
        }
    }
    const char* const vb = (const char*)(p.vw + (size_t)(bown * NH + head) * SK * DH);
    const uint32_t bar_first = crit ? bar_wm : bar_wq;
    if (threadIdx.x == 256) {
        if (!crit) {
            mbar_init(bar_wq, 1);
            asm volatile("fence.mbarrier_init.release.cluster;" ::: "memory");
            mbar_expect_tx(bar_wq, D * 64);
            const uint32_t c0 = clock32();
            while (clock32() - c0 < WQ_DELAY) { }
#pragma unroll
            for (int r = 0; r < D; r += 160) tma2d(sb + X_WQ + r * 64, &tm_wq, 32 * cta, r, bar_wq);
        }
    } else if (threadIdx.x == 0) {
#pragma unroll
        for (int s = 0; s < NS; s++) { if (s) mbar_init(bar_full + s * 8, 1); mbar_init(bar_empty + s * 8, 4); }
        mbar_init(crit ? bar_wq : bar_wm, 1);
        mbar_init(bar_xfree, 1);
#pragma unroll
        for (int i = 0; i < 5; i++) { mbar_init(bar_wo + i * 8, 1); mbar_init(bar_w2 + i * 16, 1); mbar_init(bar_w2 + i * 16 + 8, 1); }
        mbar_init(bar_help, 1); mbar_init(bar_x1, 1);
#pragma unroll
        for (int i = 0; i < 4; i++) { mbar_init(bar_v + i * 8, 1); mbar_init(bar_w1 + i * 8, 1); mbar_init(bar_gb + i * 8, 1); }
        asm volatile("fence.mbarrier_init.release.cluster;" ::: "memory");
    }
    __syncthreads();

    if (warp == 8) {
        if (lane == 0) {
            int tp = NS;
            int sched = PACE_A - NS * PACE_TAU;
            int phase = 0;
#pragma unroll 1
            for (int t = 1; t <= NITEM; t++) {
                if (t == 1) mbar_wait(bar_full, 0);
                if (t == 2) {
                    mbar_wait(bar_first, 0);
                    if (crit) {
                        mbar_expect_tx(bar_wq, D * 64);
#pragma unroll 1
                        for (int r = 0; r < D; r += 160) tma2d(sb + X_WQ + r * 64, &tm_wq, 32 * cta, r, bar_wq);
                    }
                }
                if (t == 3) {
                    asm volatile("prefetch.tensormap [%0];" ::"l"(&tm_v) : "memory");
                    asm volatile("prefetch.tensormap [%0];" ::"l"(&tm_wo) : "memory");
                    asm volatile("prefetch.tensormap [%0];" ::"l"(&tm_w1) : "memory");
                    asm volatile("prefetch.tensormap [%0];" ::"l"(&tm_w2) : "memory");
                    asm volatile("prefetch.tensormap [%0];" ::"l"(&tm_gb) : "memory");
                }
                if (t == NS && late) {
                    mbar_wait(bar_full + (NS - INFLIGHT) * 8, 0);
                    mbar_expect_tx(bar_wm, D * 64);
#pragma unroll 1
                    for (int r = 0; r < D; r += 160) tma2d(sb + X_WM + r * 64, &tm_wmod, 32 * mc, r, bar_wm);
                }
                if (t >= NS && t < PF_END) {
                    int it = 0;
                    while (!mbar_test(bar_empty + (t & (NS - 1)) * 8, ((t >> 3) - 1) & 1)) {
                        if (tp < PF_END && (int)(gtime32() - t_start) >= PACE_A + (tp - NS) * PACE_TAU) {
                            asm volatile("cp.async.bulk.prefetch.L2.global [%0], %1;"
                                         ::"l"(((tp & 1) ? vb : kb) + (size_t)(((tp >> 1) + rot) & (NITEM / 2 - 1)) * TILE_BYTES), "r"(TILE_BYTES) : "memory");
                            tp++;
                        }
                        if (++it > 16 * SPIN_LIMIT) __trap();
                    }
                    if (tp <= t) tp = t + 1;
                }
                if (t == NITEM) {
                    mbar_wait(bar_xfree, 0);
                    const uint32_t t_ref = t_start + phase + (NITEM - 1) * PACE_TAU;
#pragma unroll 1
                    for (int i = 0; i < 5; i++) {
                        while ((int)(gtime32() - t_ref) < WO_T + i * WO_S) { }
                        mbar_expect_tx(bar_wo + i * 8, DH * 64);
                        tma2d(sb + X_WO + i * (DH * 64), &tm_wo, bown * 160 + i * 32, head * DH, bar_wo + i * 8);
                    }
                    if (gb_own) {
                        mbar_wait(bar_empty + 3 * 8, ((NITEM >> 3) - 1) & 1);
                        mbar_wait(bar_x1, 0);
                        { const uint32_t c0 = clock32(); while (clock32() - c0 < GB_EV) { } }
                        while ((int)(gtime32() - t_ref) < GB_T) { }
#pragma unroll 1
                        for (int i = 0; i < 4; i++) {
                            mbar_expect_tx(bar_gb + i * 8, 160 * 16);
                            tma2d(sb + X_GB + i * (160 * 16), &tm_gb, 5 * D + 8 * own, 160 * i, bar_gb + i * 8);
                        }
                    }
                    if (is_f) {
#pragma unroll 1
                        for (int i = 0; i < 3; i++) mbar_wait(bar_empty + i * 8, ((NITEM >> 3) - 1) & 1);
                        while ((int)(gtime32() - t_ref) < W1_T) { }
#pragma unroll 1
                        for (int i = 0; i < 4; i++) {
                            mbar_expect_tx(bar_w1 + i * 8, 160 * 64);
                            tma2d(sb + X_W1 + i * (160 * 64), &tm_w1, 32 * f, 160 * i, bar_w1 + i * 8);
                        }
                        while ((int)(gtime32() - t_ref) < W2_T) { }
#pragma unroll 1
                        for (int i = 0; i < 10; i++) {
                            mbar_expect_tx(bar_w2 + i * 8, 4096);
                            tma2d(sb + X_W2 + i * 4096, &tm_w2, 64 * i, 32 * f, bar_w2 + i * 8);
                        }
                    }
                    break;
                }
                const int s = t & (NS - 1);
                if (t >= NS) {
                    mbar_wait(bar_empty + s * 8, ((t >> 3) - 1) & 1);
                    while ((int)(gtime32() - t_start) < sched + t * PACE_TAU) { }
                } else if (t >= INFLIGHT) {
                    mbar_wait(bar_full + (t - INFLIGHT) * 8, 0);
                }
                if (t < NITEM - 2) {
                    const int pair = t == NITEM - 3 ? NITEM / 2 - 1 : t >> 1;
                    mbar_expect_tx(bar_full + s * 8, TILE_BYTES);
                    bulk_load(sb + OFF_RING + s * TILE_BYTES, ((t & 1) && t != NITEM - 3 ? vb : kb) + (size_t)((pair + rot) & (NITEM / 2 - 1)) * TILE_BYTES, TILE_BYTES, bar_full + s * 8, pol);
                } else {
                    const int row = (bown * NH + head) * SK + (SK - WIN) + ((t - NITEM / 2 + rot) & (NITEM / 2 - 1)) * TILE_KEYS;
#pragma unroll 1
                    for (int i = 0; i < 2; i++) {
                        const uint32_t bar = bar_v + (2 * (t - (NITEM - 2)) + i) * 8;
                        mbar_expect_tx(bar, TILE_BYTES / 2);
                        tma2d_hint(sb + OFF_RING + s * TILE_BYTES + i * (TILE_BYTES / 2), &tm_v, 64 * i, row, bar, pol);
                    }
                }
                if (t >= PH_FIRST && (t & 7) == PH_LAG) {
                    const int now = (int)(gtime32() - t_start) - (t - PH_LAG) * PACE_TAU;
                    uint32_t ph;
                    asm volatile("atom.relaxed.gpu.global.add.u32 %0, [%1], 0;" : "=r"(ph) : "l"(g_phase + (t >> 3) * 32) : "memory");
                    phase = (int)min(((ph & 0xffffffu) * 4 + (NCTA - (ph >> 24)) * now) / NCTA, 65535u);
                    sched += (phase - LAT_T - sched) * 3 / 4;
                }
            }
        }
        __syncwarp();
    }

    if (warp == 9) {
        int side = 0;
        if (lane == 0) {
            uint32_t best[2] = {~0u, ~0u};
#pragma unroll
            for (int i = 0; i < 4; i++) stg_zero4(slot(SL_SIDE, i >> 1) + cta * 8 + (i & 1) * 4);
            uint32_t n = 0;
#pragma unroll 1
            for (int i = 0; (i & 1) || (n < NPROBE - 1 && (int)(gtime32() - t_start) < PROBE_END); i++) {
                uint32_t t0 = clock32(), t1;
                asm volatile("atom.relaxed.gpu.global.inc.u32 %0, [%1], %2;" : "=r"(n) : "l"(slot(SL_SIDE, i & 1) + cta * 8), "r"(0xffffu) : "memory");
                asm volatile("{\n.reg .pred p;\nsetp.ne.u32 p, %1, 0xffffffff;\nmov.u32 %0, 0;\n@p mov.u32 %0, %%clock;\n}" : "=r"(t1) : "r"(n) : "memory");
                if (i & 1) best[1] = min(best[1], t1 - t0); else best[0] = min(best[0], t1 - t0);
            }
            side = best[1] < best[0];
        }
        side = __shfl_sync(0xffffffffu, side, 0);
        HPROF(1);
        mbar_wait(bar_full + (NS - 1) * 8, 0);
        stg_zero4(slot(SL_O + (cta >> 4), lane >> 4) + (cta & 15) * 64 + (lane & 15) * 4);
        if (is_owner) {
#pragma unroll 1
            for (int i = lane; i < NH * 8; i += 32) stg_zero4(slot(SL_P1 + own, side) + i * 4);
#pragma unroll 1
            for (int i = lane; i < NF * 4; i += 32) stg_zero4(slot(SL_P2 + 2 * own + (i >> 7), side) + ((i >> 2) & 31) * 32 + (i & 3) * 4);
            if (lane < 8) stg_zero4(slot(SL_X1 + own / 30, lane >> 2) + (own % 30) * 32 + (lane & 3) * 4);
        }
        __threadfence();
        __syncwarp();
        if (lane == 0) stg_relaxed(g_clr + cta, 1u + side);
        HPROF(0);
        while ((int)(gtime32() - t_start) < CLR_CHECK) __nanosleep(1000);
        mbar_wait(bar_xfree, 0);
        {
            uint4 v = make_uint4(1, 1, 1, 1), gv = v, mv[20];
#pragma unroll
            for (int i = 0; i < 20; i++) mv[i] = v;
#pragma unroll 1
            for (int it = 0;; it++) {
                v = ldg_relaxed(g_clr + lane * 4);
                ldg_relaxed_if(is_owner && lane < (gb_own ? 4 : 8), gv, mod_slot(lane < 4 ? 2 : 5, own, lane & 3));
#pragma unroll
                for (int i = 0; i < 20; i++) ldg_relaxed_if(is_f, mv[i], mod_slot(3, 8 * i + (lane >> 2), lane & 3));
                bool ok = ready(v) && ready(gv);
#pragma unroll
                for (int i = 0; i < 20; i++) ok = ok && ready(mv[i]);
                if (__all_sync(0xffffffffu, ok)) break;
                if (it > SPIN_LIMIT) __trap();
                __nanosleep(2000);
            }
            const uint32_t w[4] = {v.x, v.y, v.z, v.w};
#pragma unroll
            for (int i = 0; i < 4; i++) {
                const Roles r = roles(4 * lane + i);
                if (r.is_owner) {
                    sts32(sb + OFF_TAB1 + r.own * 4, (uint32_t)(size_t)(slot(SL_P1 + r.own, w[i] - 1) + head * 32));
                    sts32(sb + OFF_TAB2 + r.own * 4, (uint32_t)(size_t)(slot(SL_P2 + 2 * r.own + (f >> 5), w[i] - 1) + (f & 31) * 32));
                }
            }
            if (lane == 0) sts32(sb + OFF_SIDE, side);
            gv = inv4(gv);
            if (lane < 4) sts128(sb + OWN_GA + lane * 16, gv);
            else if (lane < 8) {
                sts128(sb + OWN_GB + (lane & 3) * 32, make_uint4(gv.x << 16, gv.x & 0xffff0000u, gv.y << 16, gv.y & 0xffff0000u));
                sts128(sb + OWN_GB + (lane & 3) * 32 + 16, make_uint4(gv.z << 16, gv.z & 0xffff0000u, gv.w << 16, gv.w & 0xffff0000u));
            } else if (lane < 16) sts128(sb + OWN_GB + lane * 16, make_uint4(0, 0, 0, 0));
            const uint32_t dst = sb + OFF_VB + (lane & 3) * VEC_STRIDE + (lane >> 2) * 16;
#pragma unroll
            for (int i = 0; i < 10; i++) {
                const uint4 c = inv4(mv[10 + i]);
                sts128(dst + i * 128, make_uint4(bf2_add(c.x, 0x3f803f80u), bf2_add(c.y, 0x3f803f80u), bf2_add(c.z, 0x3f803f80u), bf2_add(c.w, 0x3f803f80u)));
                sts128(dst + (OFF_RED - OFF_VB) + i * 128, inv4(mv[i]));
            }
        }
        asm volatile("fence.acq_rel.gpu;" ::: "memory");
        __syncwarp();
        HPROF(3);
        if (lane == 0) mbar_arrive(bar_help);
        {
            const uint32_t* const src = pin(slot(SL_O + (cta >> 4), side) + (cta & 12) * 64 + lane * 4);
            const uint32_t dst = pin(sb + OFF_O + (lane >> 4) * O_STRIDE + (lane & 15) * 16);
            mbar_wait(bar_v + 16, 0);
            mbar_wait(bar_v + 24, 0);
            uint4 v[2];
            const uint32_t* const ptr[2] = {src, src + 128};
            const bool on[2] = {true, true};
            poll_n<2>(v, ptr, on);
            sts128(dst, v[0]);
            sts128(dst + 2 * O_STRIDE, v[1]);
#pragma unroll
            for (int w = 0; w < 8; w++) asm volatile("bar.arrive %0, 64;" ::"r"(NB_O + w) : "memory");
        }
        HPROF(4);
    }
    if (warp >= 8) {
        if (gb_own) {
            uint32_t a[10][4];
#pragma unroll
            for (int k = 0; k < 10; k++) ldsm4(a[k], sb + OFF_VA + (lane & 3) * VEC_STRIDE + (8 * k + 4 * (warp - 8) + ((lane >> 2) & 2) + (lane >> 4)) * 16);
            float c[4][4];
#pragma unroll
            for (int i = 0; i < 4; i++) c[i][0] = c[i][1] = c[i][2] = c[i][3] = 0.f;
            mbar_wait(bar_help, 0);
#pragma unroll
            for (int k = 0; k < 10; k++) {
                if (k == 0 || k == 2 || k == 5 || k == 7) mbar_wait(bar_gb + (2 * k + 1) / 5 * 8, 0);
                uint32_t w[4];
                ldsm4t(w, sb + X_GB + (64 * k + 32 * (warp - 8) + lane) * 16);
                mma16816(c[2 * (k & 1)], a[k], w[0], w[1]);
                mma16816(c[2 * (k & 1) + 1], a[k], w[2], w[3]);
            }
            if (lane < 16) sts_f32x2(sb + OWN_GB + (warp - 8) * 128 + lane * 8, (c[0][0] + c[2][0]) + (c[1][2] + c[3][2]), (c[0][1] + c[2][1]) + (c[1][3] + c[3][3]));
        }
        if (is_owner) nbar_arrive<NB_E6, 320>();
        if (is_f) gelu_stage(sb, warp - 8, lane);
        return;
    }

    const int g = lane >> 2, t4 = lane & 3;
    const int mi = lane >> 3, r8 = lane & 7;

    {
        auto silu4 = [&](const uint4& cv) {
            uint32_t w4[4] = {cv.x, cv.y, cv.z, cv.w};
#pragma unroll
            for (int e = 0; e < 4; e++) {
                float c0 = bf_lo(w4[e]), c1 = bf_hi(w4[e]);
                w4[e] = pack_bf(c0 * rcp_fast(1.f + ex2(-1.4426950408889634f * c0)), c1 * rcp_fast(1.f + ex2(-1.4426950408889634f * c1)));
            }
            return make_uint4(w4[0], w4[1], w4[2], w4[3]);
        };
        {
            uint4 v = silu4(ca0);
            sts128(sb + OFF_VA + (tid / 80) * VEC_STRIDE + (tid % 80) * 16, v);
            if (tid < 64) { v = silu4(ca1); sts128(sb + OFF_VA + 3 * VEC_STRIDE + (16 + tid) * 16, v); }
        }
        if (warp < 4) {
            float s = 0.f, q = 0.f;
            const float pv = __shfl_sync(0xffffffffu, bf_lo(xs[0].x), 0);
#pragma unroll
            for (int i = 0; i < 3; i++) if (i < 2 || lane < 16) acc_stats(xs[i], pv, s, q);
#pragma unroll
            for (int of = 16; of > 0; of >>= 1) { s += __shfl_xor_sync(0xffffffffu, s, of); q += __shfl_xor_sync(0xffffffffu, q, of); }
            uint32_t m2; float rden;
            ln_finish(pv, s, q, m2, rden);
            if (lane == 0) { sts32(sb + OFF_STAT + warp * 8, m2); sts_f32(sb + OFF_STAT + warp * 8 + 4, rden); }
        } else if (warp == 4) {
            sts32(sb + OWN_X + lane * 4, bf2_add(own0, 0u));
            sts_f32(sb + OWN_B1 + lane * 4, bf2f(own2));
        }
    }
    bar_cons();
    PROF(24);
    uint32_t qf[8][2];
    float o[8][4];
#pragma unroll
    for (int c = 0; c < 8; c++) { o[c][0] = o[c][1] = o[c][2] = o[c][3] = 0.f; }
    float m_run = -INFINITY, l_run = 0.f;
    const bool diag = (t4 == (g >> 1));
    const bool odd = g & 1;
    const uint32_t koff = (warp & 3) * 4096 + (r8 + 8 * (mi & 1)) * 256 + (mi >> 1) * 128 + (r8 << 4);
    const uint32_t voff = TILE_BYTES + (warp & 3) * 4096 + (r8 + 8 * (mi >> 1)) * 256 + (mi & 1) * 128 + (r8 << 4);
    const int src0 = (2 * t4) * 4 + t4, src1 = (2 * t4 + 1) * 4 + t4;
#pragma unroll 1
    for (int step = crit ? 0 : 1; step < 3; step++) {
        if (step < 2 || late) {
            if (step == 1) {
                if (!crit) mbar_wait(bar_wq, 0);
                const uint32_t m2 = lds32(sb + OFF_STAT + (tid & 3) * 8);
                const float rden = lds_f32(sb + OFF_STAT + (tid & 3) * 8 + 4);
                uint4 v[4];
                v[2] = v[3] = make_uint4(1, 1, 1, 1);
                const uint32_t* const p0 = mod_slot(0, tid >> 2, tid & 3);
                while ((int)(gtime32() - t_start) < MOD_T) { }
                PROF(2);
#pragma unroll 1
                for (int it = 0;; it++) {
                    ldg_relaxed_if(tid < 64, v[2], p0 + 16 * 64);
                    ldg_relaxed_if(tid < 64, v[3], p0 + 36 * 64);
                    v[0] = ldg_relaxed(p0);
                    v[1] = ldg_relaxed(p0 + 20 * 64);
                    if (__all_sync(0xffffffffu, min(min(min4(v[0]), min4(v[1])), min(min4(v[2]), min4(v[3]))) != 0u)) break;
                    if (it > SPIN_LIMIT) __trap();
                }
#pragma unroll
                for (int i = 0; i < 4; i++) v[i] = inv4(v[i]);
                PROF(3);
                uint4 h0 = ln_mod4(xa, v[1], v[0], m2, rden);
                sts128(sb + OFF_VB + (tid & 3) * VEC_STRIDE + (tid >> 2) * 16, h0);
                if (tid < 64) {
                    h0 = ln_mod4(xb, v[3], v[2], m2, rden);
                    sts128(sb + OFF_VB + (tid & 3) * VEC_STRIDE + (64 + (tid >> 2)) * 16, h0);
                }
            }
            mbar_wait(step == 1 ? bar_wq : bar_wm, 0);
            bar_cons();
            const uint32_t strip = sb + (step == 1 ? X_WQ : X_WM), vec = sb + (step == 1 ? OFF_VB : OFF_VA);
            float acc[2][4];
#pragma unroll
            for (int m = 0; m < 2; m++) { acc[m][0] = acc[m][1] = acc[m][2] = acc[m][3] = 0.f; }
#pragma unroll
            for (int i = 0; i < 5; i++) {
                int k0 = (warp * 5 + i) * 16;
                uint32_t b0, b1;
                load_bfrag(vec, VEC_STRIDE, k0, g, t4, b0, b1);
                int krow = k0 + r8 + 8 * (mi >> 1);
#pragma unroll
                for (int m = 0; m < 2; m++) {
                    uint32_t a[4];
                    int ch = 2 * m + (mi & 1);
                    ldsm4t(a, strip + krow * 64 + ((ch ^ ((krow >> 1) & 3)) << 4));
                    mma16816(acc[m], a, b0, b1);
                }
            }
            if (t4 < 2) {
#pragma unroll
                for (int m = 0; m < 2; m++) {
                    sts_f32x2(sb + OFF_RED + ((warp * 32 + m * 16 + g) * 4 + 2 * t4) * 4, acc[m][0], acc[m][1]);
                    sts_f32x2(sb + OFF_RED + ((warp * 32 + m * 16 + g + 8) * 4 + 2 * t4) * 4, acc[m][2], acc[m][3]);
                }
            }
            bar_cons();
            if (tid < 64) {
                float v0 = 0.f, v1 = 0.f;
#pragma unroll
                for (int w = 0; w < 8; w++) {
                    v0 += lds_f32(sb + OFF_RED + (w * 128 + (tid & 15) * 8 + (tid >> 4)) * 4);
                    v1 += lds_f32(sb + OFF_RED + (w * 128 + (tid & 15) * 8 + 4 + (tid >> 4)) * 4);
                }
                stg_relaxed(step == 1 ? g_q + (((cta & ~3) + (tid >> 4)) * 4 + bown) * 32 + (tid & 15) : g_mod + mc * 64 + tid, ~pack_bf(v0, v1));
            }
        }
        if (step == 0) continue;
        if (step == 1) {
            if (warp == 0) {
                { const uint32_t c0 = clock32(); while (clock32() - c0 < Q_PAUSE) { } }
                uint4 v = poll1(g_q + (cta * 4 + ((lane >> 2) & 3)) * 32 + (lane & 3) * 4, lane < 16);
                if (lane < 16) {
                    sts128(sb + OFF_Q + lane * 16, v);
                    stg_zero4(g_q + (cta * 4 + (lane >> 2)) * 32 + (lane & 3) * 4);
                }
            }
            bar_cons();
            PROF(4);

#pragma unroll
            for (int c = 0; c < 8; c++) {
                qf[c][0] = lds32(sb + OFF_Q + (((c ^ g) * 4 + t4) << 2));
                qf[c][1] = lds32(sb + OFF_Q + 128 + (((c ^ g) * 4 + t4) << 2));
            }
        } else {
            bar_cons();
            if (tid == 0) mbar_arrive(bar_xfree);
        }
#pragma unroll 1
        for (int j = (step == 1 ? 0 : SEG_J) + (warp >> 2); j < (step == 1 ? SEG_J : NITEM / 2 - 2); j += 2) {
            const int s = (2 * j) & (NS - 1);
            const uint32_t par = (j >> 2) & 1;
            mbar_wait(bar_full + s * 8, par);
            if (tid == 0 && 2 * j >= PH_FIRST && (j & 3) == 0) {
                const int x = min(max((int)(gtime32() - t_start) - 2 * j * PACE_TAU, 0), 65535);
                asm volatile("red.relaxed.gpu.global.add.u32 [%0], %1;" ::"l"(g_phase + (j >> 2) * 32), "r"((1u << 24) + (x >> 2)) : "memory");
            }
            const uint32_t base = sb + OFF_RING + s * TILE_BYTES;
            float sa[4] = {0.f, 0.f, 0.f, 0.f}, sb2[4] = {0.f, 0.f, 0.f, 0.f};
#pragma unroll
            for (int c = 0; c < 8; c += 2) {
                uint32_t a[4], a2[4];
                ldsm4(a, (base + koff) ^ (c << 4));
                ldsm4(a2, (base + koff) ^ ((c + 1) << 4));
                mma16816(sa, a, qf[c][0], qf[c][1]);
                mma16816(sb2, a2, qf[c + 1][0], qf[c + 1][1]);
            }
            const uint32_t sw = pack_bf(odd ? sa[1] + sb2[1] : sa[0] + sb2[0], odd ? sa[3] + sb2[3] : sa[2] + sb2[2]);
            const uint32_t sv = pack_bf(bf_lo(sw) * 0.08838834764831845f, bf_hi(sw) * 0.08838834764831845f);
            const float s0 = bf_lo(sv) * 1.4426950408889634f, s1 = bf_hi(sv) * 1.4426950408889634f;
            float m_new = fmaxf(m_run, fmaxf(s0, s1));
            const bool grow = __any_sync(0xffffffffu, (diag && (m_new > m_run)));
            if (lane == 0) mbar_arrive(bar_empty + s * 8);
            if (grow) {
                float al = ex2(m_run - m_new);
                float a0 = __shfl_sync(0xffffffffu, al, src0), a1 = __shfl_sync(0xffffffffu, al, src1);
#pragma unroll
                for (int c = 0; c < 8; c++) { o[c][0] *= a0; o[c][1] *= a1; o[c][2] *= a0; o[c][3] *= a1; }
                l_run *= al;
                m_run = m_new;
            }
            uint32_t pw = pack_bf(ex2(s0 - m_run), ex2(s1 - m_run));
            l_run += bf_lo(pw) + bf_hi(pw);
            uint32_t b0 = odd ? (pw << 16) : (pw & 0xffffu);
            uint32_t b1 = odd ? (pw & 0xffff0000u) : (pw >> 16);
            if (!diag) { b0 = 0u; b1 = 0u; }
            mbar_wait(bar_full + (s + 1) * 8, par);
#pragma unroll
            for (int c = 0; c < 8; c++) {
                uint32_t a[4];
                ldsm4t(a, (base + voff) ^ (c << 4));
                mma16816(o[c], a, b0, b1);
            }
            __syncwarp();
            if (lane == 0) mbar_arrive(bar_empty + (s + 1) * 8);
        }
    }
    PROF(5);
    float acc[4][4];
    uint32_t pa[8][2];
    float rinv;
    {
        const int s = 4 + (warp >> 2);
        mbar_wait(bar_full + s * 8, 1);
        const uint32_t base = sb + OFF_RING + s * TILE_BYTES;
        float sa[4] = {0.f, 0.f, 0.f, 0.f}, sb2[4] = {0.f, 0.f, 0.f, 0.f};
#pragma unroll
        for (int c = 0; c < 8; c += 2) {
            uint32_t a[4], a2[4];
            ldsm4(a, (base + koff) ^ (c << 4));
            ldsm4(a2, (base + koff) ^ ((c + 1) << 4));
            mma16816(sa, a, qf[c][0], qf[c][1]);
            mma16816(sb2, a2, qf[c + 1][0], qf[c + 1][1]);
        }
        const uint32_t sw = pack_bf(odd ? sa[1] + sb2[1] : sa[0] + sb2[0], odd ? sa[3] + sb2[3] : sa[2] + sb2[2]);
        const uint32_t sv = pack_bf(bf_lo(sw) * 0.08838834764831845f, bf_hi(sw) * 0.08838834764831845f);
        const float s0 = bf_lo(sv) * 1.4426950408889634f, s1 = bf_hi(sv) * 1.4426950408889634f;
        int mi_ = __float_as_int(diag ? fmaxf(m_run, fmaxf(s0, s1)) : -INFINITY);
        mi_ ^= (mi_ >> 31) & 0x7fffffff;
        mi_ = __reduce_max_sync(0xffffffffu, mi_);
        mi_ ^= (mi_ >> 31) & 0x7fffffff;
        if (lane == 0) sts32(sb + OFF_ML + warp * 4, mi_);
        bar_cons();
        const float4 m0 = lds_f32x4(sb + OFF_ML), m1 = lds_f32x4(sb + OFF_ML + 16);
        const float mx = fmaxf(fmaxf(fmaxf(m0.x, m0.y), fmaxf(m0.z, m0.w)), fmaxf(fmaxf(m1.x, m1.y), fmaxf(m1.z, m1.w)));
        const float scl = ex2(m_run - mx);
        const uint32_t pw = pack_bf(ex2(s0 - mx), ex2(s1 - mx));
        if (diag) { sts16(sb + SC_P + (warp * 16 + g) * 2, pw); sts16(sb + SC_P + (warp * 16 + g + 8) * 2, pw >> 16); }
        const float lw = warp_sum(diag ? fmaf(l_run, scl, bf_lo(pw) + bf_hi(pw)) : 0.f);
        const float a0 = __shfl_sync(0xffffffffu, scl, src0), a1 = __shfl_sync(0xffffffffu, scl, src1);
        float v[8], u[8];
#pragma unroll
        for (int c = 0; c < 8; c++) {
            v[c] = a0 * o[c][0] + a1 * o[c ^ 1][1];
            u[c] = a0 * o[c][2] + a1 * o[c ^ 1][3];
        }
#pragma unroll
        for (int c = 0; c < 8; c++) {
            if (!(c & 2)) {
                v[c] += __shfl_xor_sync(0xffffffffu, v[c ^ 2], 1);
                u[c] += __shfl_xor_sync(0xffffffffu, u[c ^ 2], 1);
            }
        }
#pragma unroll
        for (int c = 0; c < 2; c++) {
            v[c] += __shfl_xor_sync(0xffffffffu, v[c ^ 4], 2);
            u[c] += __shfl_xor_sync(0xffffffffu, u[c ^ 4], 2);
        }
        const uint32_t dst = sb + SC_OP + (warp * 128 + 16 * t4 + g) * 4;
        sts_f32(dst, v[0]); sts_f32(dst + 32, v[1]); sts_f32(dst + 256, u[0]); sts_f32(dst + 288, u[1]);
        if (lane == 0) sts_f32(sb + OFF_ML + 32 + warp * 4, lw);
        mbar_wait(bar_help, 0);
        bar_cons();
        const float4 l0 = lds_f32x4(sb + OFF_ML + 32), l1 = lds_f32x4(sb + OFF_ML + 48);
        rinv = rcp_fast(((l0.x + l0.y) + (l0.z + l0.w)) + ((l1.x + l1.y) + (l1.z + l1.w)));
#pragma unroll
        for (int i = 0; i < 4; i++) acc[i][0] = acc[i][1] = acc[i][2] = acc[i][3] = 0.f;
#pragma unroll
        for (int w = 0; w < 8; w++) {
            const float2 x0 = lds_f32x2(sb + SC_OP + (w * 128 + 16 * warp + 2 * t4) * 4), x1 = lds_f32x2(sb + SC_OP + (w * 128 + 16 * warp + 8 + 2 * t4) * 4);
            acc[2 * (w & 1)][0] += x0.x; acc[2 * (w & 1)][1] += x0.y;
            acc[2 * (w & 1) + 1][0] += x1.x; acc[2 * (w & 1) + 1][1] += x1.y;
        }
#pragma unroll
        for (int ks = 0; ks < 8; ks++) { pa[ks][0] = lds32(sb + SC_P + (8 * ks + t4) * 4); pa[ks][1] = lds32(sb + SC_P + (8 * ks + 4 + t4) * 4); }
    }
    PROF(20);
    const int mt = warp < 2 ? warp : warp + 2;
    {
        const uint32_t va = pin(sb + OFF_RING + 6 * TILE_BYTES + (warp >> 2) * (TILE_BYTES / 2) + (8 * (mi & 1) + r8) * 128 + (((2 * (warp & 3) + (mi >> 1)) ^ r8) << 4));
        const uint32_t vbar = pin(bar_v + (warp >> 2) * 8);
        uint32_t* const o_dst = pin(slot(SL_O + (cta >> 4), g) + (cta & 15) * 64 + warp * 8 + 2 * t4);
#pragma unroll
        for (int tl = 0; tl < 2; tl++) {
            mbar_wait(vbar + tl * 16, 0);
            uint32_t r[4][4];
#pragma unroll
            for (int ks = 0; ks < 4; ks++) ldsm4t(r[ks], va + tl * TILE_BYTES + ks * 2048);
#pragma unroll
            for (int ks = 0; ks < 4; ks++) {
                const uint32_t a[4] = {pa[4 * tl + ks][0], 0u, pa[4 * tl + ks][1], 0u};
                mma16816(acc[2 * (ks & 1)], a, r[ks][0], r[ks][1]);
                mma16816(acc[2 * (ks & 1) + 1], a, r[ks][2], r[ks][3]);
            }
        }
        stg_relaxed2_if(g < 2, o_dst, ~pack_bf((acc[0][0] + acc[2][0]) * rinv, (acc[0][1] + acc[2][1]) * rinv),
                        ~pack_bf((acc[1][0] + acc[3][0]) * rinv, (acc[1][1] + acc[3][1]) * rinv));
    }
    PROF(7);
    const int side = lds32(sb + OFF_SIDE);
    const uint32_t red_st = pin(sb + SC_E4 + ((warp * 4 + 2 * ((lane >> 3) & 1) + (lane >> 4)) * 8 + (lane & 7)) * 4);
    const uint32_t red_ld = pin(sb + SC_E4 + (lane & 15) * 8);
    const uint32_t* const in1 = pin(slot(SL_P1 + own, side) + tid * 4);
    const uint32_t* const in2a = pin(slot(SL_P2 + 2 * own, side) + (tid >> 3) * 32 + (tid & 7) * 2);
    const uint32_t* const in2b = pin(slot(SL_P2 + 2 * own + 1, side) + (tid >> 3) * 32 + (tid & 7) * 2);
    uint32_t* const out_dst = pin((uint32_t*)(p.out + ((lane >> 2) & 3) * D + 8 * own) + t4);
    uint32_t* const x1_dst = pin(slot(SL_X1 + own / 30, lane >> 4) + (own % 30) * 32 + (lane & 15));
    uint32_t* const rst = pin(tid >= 32 && tid < (gb_own ? 52 : 56) ? mod_slot(lane >> 2, own, lane & 3) : own < 32 && tid == 64 ? g_clr + own * 4 : own < 8 && tid == 96 ? g_phase + own * 32 : nullptr);
    const uint32_t xw = lds32(sb + OWN_X + (lane & 15) * 4), ga_w = lds32(sb + OWN_GA + (lane & 15) * 4);
    uint32_t cs[15];
    uint32_t* dst2[5];
    uint32_t w2a[5];
#pragma unroll
    for (int j = 0; j < 10; j++) cs[j] = lds32(sb + OFF_VB + ((g & 1) * 4 + (g >> 1)) * VEC_STRIDE + warp * 160 + t4 * 4 + j * 16);
#pragma unroll
    for (int i = 0; i < 5; i++) {
        cs[10 + i] = lds32(sb + OFF_VB + (g >> 1) * VEC_STRIDE + warp * 160 + (g & 1) * 16 + t4 * 4 + i * 32);
        const uint2 t = lds64(sb + OFF_TAB2 + warp * 40 + i * 8);
        dst2[i] = slot_ptr((t4 < 2 ? t.x : t.y) + g * 8 + (t4 & 1) * 4);
        const int cc = 2 * (warp * 5 + i) + (mi & 1);
        w2a[i] = pin(sb + X_W2 + (cc >> 3) * 4096 + (r8 + 8 * (mi >> 1)) * 128 + (((cc & 7) ^ r8) << 4));
    }
    const uint32_t piv = lds32(sb + OFF_STAT + (g >> 1) * 8);
    const uint32_t* const xin = pin(slot(SL_X1 + warp / 3, side) + ((warp % 3) * 10 + (g & 1)) * 32 + (g >> 1) * 4 + t4);
    const uint32_t w1a = pin(sb + X_W1 + (warp * 80 + r8 + 8 * (mi >> 1)) * 64 + (((mi & 1) ^ ((r8 >> 1) & 3)) << 4));
    const uint32_t w1bar = pin(bar_w1 + (warp >> 1) * 8), w2bar = pin(bar_w2 + (warp + (warp >> 2)) * 8);
    const uint32_t obar = pin(NB_O + warp), hbar = pin((NB_H1 + (warp >> 1)) & 15);
    const uint32_t ab_st = pin(sb + SC_AB + warp * 1024 + lane * 16), y_st = pin(sb + SC_Y + warp * 512 + lane * 8), s_st = pin(sb + SC_ST + (t4 * 8 + warp) * 8);
    const uint32_t h_ld = pin(sb + SC_H1 + ((g & 3) ^ (2 * (f & 1) + ((f >> 1) & 1))) * 64 + t4 * 16);
    {
        const int kap = 2 * (head & 1) + ((head >> 1) & 1);
        const uint32_t wa = pin(sb + X_WO + (mt >> 1) * (DH * 64) + (r8 + 8 * (mi >> 1)) * 64 + ((((mt & 1) * 2 + (mi & 1)) ^ ((r8 >> 1) & 3)) << 4));
        const uint32_t oa = pin(sb + OFF_O + ((g & 3) ^ kap) * O_STRIDE + t4 * 8);
        uint32_t* dst[4];
#pragma unroll
        for (int i = 0; i < 2; i++) {
            const uint2 t = lds64(sb + OFF_TAB1 + (bown * 20 + 2 * mt + (warp < 2 ? 4 * i : 0)) * 4);
            dst[2 * i] = slot_ptr(t.x + g * 16 + t4 * 8);
            dst[2 * i + 1] = slot_ptr(t.y + g * 16 + t4 * 8);
        }
        PROF(6);
        const uint32_t wobar = pin(bar_wo + (mt >> 1) * 8);
        asm volatile("bar.sync %0, 64;" ::"r"(obar) : "memory");
        uint2 ob[8];
#pragma unroll
        for (int ks = 0; ks < 8; ks++) ob[ks] = lds64(oa + ks * 32);
#pragma unroll
        for (int m = 0; m < 2; m++) {
            if (m == 0 || warp < 2) {
                mbar_wait(wobar + m * 8, 0);
                PROF(8);
                uint32_t wf[8][4];
#pragma unroll
                for (int ks = 0; ks < 8; ks++) ldsm4t(wf[ks], wa + m * (DH * 64) + ks * 1024);
                float c[4][4];
#pragma unroll
                for (int ks = 0; ks < 8; ks++) {
                    if (ks < 4) c[ks][0] = c[ks][1] = c[ks][2] = c[ks][3] = 0.f;
                    mma16816(c[ks & 3], wf[ks], ob[ks].x, ob[ks].y);
                }
                stg_relaxed2_if(t4 < 2, dst[2 * m], flag((c[0][0] + c[1][0]) + (c[2][0] + c[3][0])), flag((c[0][1] + c[1][1]) + (c[2][1] + c[3][1])));
                stg_relaxed2_if(t4 < 2, dst[2 * m + 1], flag((c[0][2] + c[1][2]) + (c[2][2] + c[3][2])), flag((c[0][3] + c[1][3]) + (c[2][3] + c[3][3])));
            }
        }
    }
    PROF(9);
    uint32_t x1w = 0;
    if (is_owner) {
        sts_f32(red_st, poll_e4(in1));
        PROF(11);
        nbar_sync<NB_E4, 256>();
        if (warp == 0) {
            float2 a[8];
#pragma unroll
            for (int w = 0; w < 8; w++) a[w] = lds_f32x2(red_ld + w * 128);
            const uint32_t aw = pack_bf(((a[0].x + a[1].x) + (a[2].x + a[3].x)) + ((a[4].x + a[5].x) + (a[6].x + a[7].x)),
                                        ((a[0].y + a[1].y) + (a[2].y + a[3].y)) + ((a[4].y + a[5].y) + (a[6].y + a[7].y)));
            x1w = bf2_add(xw, bf2_mul(ga_w, aw));
            stg_relaxed(x1_dst, x1w ^ 0x80008000u);
            if (lane == 0) mbar_arrive(bar_x1);
        }
        if (rst) stg_zero4(rst);
    }
    PROF(12);
    if (is_f) {
        uint32_t f1[5][2][4], f2[5][2][4];
        uint32_t d[6];
        auto load_x1 = [&] {
#pragma unroll
            for (int i = 0; i < 5; i++) d[i] = ldg_relaxed32(xin + i * 64);
        };
        auto have_x1 = [&] { return __all_sync(0xffffffffu, __vimin3_u32(__vimin3_u32(d[0], d[1], d[2]), d[3], d[4]) != 0u); };
        mbar_wait(w1bar, 0);
        load_x1();
        {
#pragma unroll
            for (int i = 0; i < 5; i++) { ldsm4t(f1[i][0], w1a + i * 1024); ldsm4t(f1[i][1], (w1a ^ 32) + i * 1024); }
            float c[2][4];
#pragma unroll
            for (int m = 0; m < 2; m++) c[m][0] = c[m][1] = c[m][2] = c[m][3] = 0.f;
#pragma unroll
            for (int i = 0; i < 5; i++) { mma16816(c[0], f1[i][0], cs[2 * i], cs[2 * i + 1]); mma16816(c[1], f1[i][1], cs[2 * i], cs[2 * i + 1]); }
#pragma unroll
            for (int i = 0; i < 5; i++) { cs[2 * i] = pin(odd ? 0u : cs[10 + i]); cs[2 * i + 1] = pin(odd ? cs[10 + i] : 0u); }
#pragma unroll
            for (int m = 0; m < 2; m++) sts128(ab_st + m * 512, make_uint4(__float_as_uint(c[m][0]), __float_as_uint(c[m][1]), __float_as_uint(c[m][2]), __float_as_uint(c[m][3])));
            nbar_arrive<NB_AB, 320>();
            d[0] |= __float_as_uint(c[1][3]) & (side >> 1);
        }
        PROF(10);
        if (!have_x1()) {
            asm volatile("{\n.reg .pred q;\n.reg .b32 t, n;\nmov.u32 n, 0;\n"
                         "L_%=:\nld.relaxed.gpu.global.u32 %0, [%5];\nld.relaxed.gpu.global.u32 %1, [%5 + 256];\nld.relaxed.gpu.global.u32 %2, [%5 + 512];\n"
                         "ld.relaxed.gpu.global.u32 %3, [%5 + 768];\nld.relaxed.gpu.global.u32 %4, [%5 + 1024];\n"
                         "add.u32 n, n, 1;\nsetp.gt.u32 q, n, %6;\n@q trap;\nbar.warp.sync 0xffffffff;\n"
                         "min.u32 t, %0, %1;\nmin.u32 t, t, %2;\nmin.u32 t, t, %3;\nmin.u32 t, t, %4;\n"
                         "setp.ne.u32 q, t, 0;\nvote.sync.all.pred q, q, 0xffffffff;\n@!q bra.uni L_%=;\n}"
                         : "=&r"(d[0]), "=&r"(d[1]), "=&r"(d[2]), "=&r"(d[3]), "=&r"(d[4]) : "l"(xin), "n"(SPIN_LIMIT) : "memory");
        }
        PROF(13);
        {
            float y[2][4], st[4] = {0.f, 0.f, 0.f, 0.f};
            float z[2][4] = {};
#pragma unroll
            for (int m = 0; m < 2; m++) y[m][0] = y[m][1] = y[m][2] = y[m][3] = 0.f;
#pragma unroll
            for (int i = 0; i < 5; i++) d[i] = bf2_add(d[i], piv);
            d[5] = 0u;
#pragma unroll
            for (int i = 0; i < 5; i++) {
                if (i < 3) {
                    const uint32_t a[4] = {d[2 * i], 0x3f803f80u, d[2 * i + 1], 0x3f803f80u};
                    mma16816(st, a, d[2 * i], d[2 * i + 1]);
                }
                const uint32_t y0 = bf2_mul(d[i], cs[2 * i]), y1 = bf2_mul(d[i], cs[2 * i + 1]);
                if (i & 1) { mma16816(z[0], f1[i][0], y0, y1); mma16816(z[1], f1[i][1], y0, y1); }
                else { mma16816(y[0], f1[i][0], y0, y1); mma16816(y[1], f1[i][1], y0, y1); }
            }
            const float q = odd ? st[1] : st[0];
            const float q2 = q + __shfl_xor_sync(0xffffffffu, q, 4);
            if (diag && !odd) sts_f32x2(s_st, q2, st[2] + st[3]);
#pragma unroll
            for (int m = 0; m < 2; m++) sts_f32x2(y_st + m * 256, (z[m][0] + z[m][1]) + (y[m][0] + y[m][1]), (z[m][2] + z[m][3]) + (y[m][2] + y[m][3]));
        }
        nbar_arrive<NB_Y, 320>();
        PROF(14);
        mbar_wait(w2bar, 0);
        mbar_wait(w2bar + 8, 0);
#pragma unroll
        for (int i = 0; i < 5; i++) { ldsm4t(f2[i][0], w2a[i]); ldsm4t(f2[i][1], w2a[i] + 2048); }
        asm volatile("bar.sync %0, 128;" ::"r"(hbar) : "memory");
        PROF(15);
        {
            const uint4 hb = lds128(h_ld);
            float c[5][4];
#pragma unroll
            for (int i = 0; i < 5; i++) { c[i][0] = c[i][1] = c[i][2] = c[i][3] = 0.f; mma16816(c[i], f2[i][0], hb.x, hb.y); }
#pragma unroll
            for (int i = 0; i < 5; i++) {
                mma16816(c[i], f2[i][1], hb.z, hb.w);
                stg_relaxed(dst2[i], ~pack_bf(t4 < 2 ? c[i][0] : c[i][2], t4 < 2 ? c[i][1] : c[i][3]));
            }
        }
    }
    PROF(16);
    if (is_owner) {
        const uint32_t b2w = lds32(sb + OWN_B2 + (lane & 15) * 4), gb_ld = pin(sb + OWN_GB + (lane & 15) * 8);
        sts_f32(red_st + (SC_E6 - SC_E4), poll_e6(in2a, in2b, tid < NF * 8 - 256));
        PROF(17);
        if (warp != 0) {
            nbar_arrive<NB_E6, 320>();
        } else {
            nbar_sync<NB_E6, 320>();
            float2 a[8];
#pragma unroll
            for (int i = 0; i < 8; i++) a[i] = lds_f32x2(red_ld + (SC_E6 - SC_E4) + i * 128);
            const float2 g0 = lds_f32x2(gb_ld), g1 = lds_f32x2(gb_ld + 128);
            const uint32_t gb_w = pack_bf(g0.x + g1.x, g0.y + g1.y);
            const uint32_t aw = pack_bf(((a[0].x + a[1].x) + (a[2].x + a[3].x)) + ((a[4].x + a[5].x) + (a[6].x + a[7].x)),
                                        ((a[0].y + a[1].y) + (a[2].y + a[3].y)) + ((a[4].y + a[5].y) + (a[6].y + a[7].y)));
            x1w = bf2_add(x1w, bf2_mul(gb_w, bf2_add(aw, b2w)));
            if (lane < 16) asm volatile("st.global.u32 [%0], %1;" ::"l"(out_dst), "r"(x1w) : "memory");
        }
    }
    PROF(18);
    PROF_DUMP;
}

typedef CUresult (*EncodeFn)(CUtensorMap*, CUtensorMapDataType, cuuint32_t, void*, const cuuint64_t*, const cuuint64_t*, const cuuint32_t*,
                             const cuuint32_t*, CUtensorMapInterleave, CUtensorMapSwizzle, CUtensorMapL2promotion, CUtensorMapFloatOOBfill);

static CUtensorMap make_map(EncodeFn enc, const void* ptr, int cols, int rows, int box_cols, int box_rows, CUtensorMapSwizzle sw,
                            CUtensorMapL2promotion promo = CU_TENSOR_MAP_L2_PROMOTION_NONE) {
    CUtensorMap m;
    cuuint64_t dims[2] = {(cuuint64_t)cols, (cuuint64_t)rows};
    cuuint64_t strides[1] = {(cuuint64_t)cols * 2};
    cuuint32_t box[2] = {(cuuint32_t)box_cols, (cuuint32_t)box_rows};
    cuuint32_t es[2] = {1, 1};
    enc(&m, CU_TENSOR_MAP_DATA_TYPE_BFLOAT16, 2, const_cast<void*>(ptr), dims, strides, box, es, CU_TENSOR_MAP_INTERLEAVE_NONE, sw,
        promo, CU_TENSOR_MAP_FLOAT_OOB_FILL_NONE);
    return m;
}

}

extern "C" void kernel_launch(void* const* d_in, const int* in_sizes, int n_in, void* d_out, int out_size) {
    (void)in_sizes; (void)n_in; (void)out_size;
    static EncodeFn enc = nullptr;
    if (!enc) {
        void* fn = nullptr;
        cudaDriverEntryPointQueryResult qr;
        cudaGetDriverEntryPoint("cuTensorMapEncodeTiled", &fn, cudaEnableDefault, &qr);
        enc = (EncodeFn)fn;
        cudaFuncSetAttribute(fused_kernel, cudaFuncAttributeMaxDynamicSharedMemorySize, SMEM_BYTES);
    }
    Params p;
    p.x = (const __nv_bfloat16*)d_in[0];
    p.kw = (const __nv_bfloat16*)d_in[1] + (SK - WIN) * DH;
    p.vw = (const __nv_bfloat16*)d_in[2] + (SK - WIN) * DH;
    p.b1 = (const __nv_bfloat16*)d_in[7];
    p.b2 = (const __nv_bfloat16*)d_in[9];
    p.c = (const __nv_bfloat16*)d_in[10];
    p.out = (__nv_bfloat16*)d_out;
    CUtensorMap tm_wmod = make_map(enc, d_in[11], NMOD, D, 32, 160, CU_TENSOR_MAP_SWIZZLE_64B, CU_TENSOR_MAP_L2_PROMOTION_L2_128B);
    CUtensorMap tm_wq = make_map(enc, d_in[3], NH * DH, D, 32, 160, CU_TENSOR_MAP_SWIZZLE_64B, CU_TENSOR_MAP_L2_PROMOTION_L2_128B);
    CUtensorMap tm_wo = make_map(enc, d_in[4], D, NH * DH, 32, 128, CU_TENSOR_MAP_SWIZZLE_64B);
    CUtensorMap tm_w1 = make_map(enc, d_in[6], FF, D, 32, 160, CU_TENSOR_MAP_SWIZZLE_64B);
    CUtensorMap tm_w2 = make_map(enc, d_in[8], D, FF, 64, 32, CU_TENSOR_MAP_SWIZZLE_128B);
    CUtensorMap tm_v = make_map(enc, d_in[2], DH, NB * NH * SK, 64, TILE_KEYS, CU_TENSOR_MAP_SWIZZLE_128B);
    CUtensorMap tm_gb = make_map(enc, d_in[11], NMOD, D, 8, 160, CU_TENSOR_MAP_SWIZZLE_NONE, CU_TENSOR_MAP_L2_PROMOTION_L2_128B);
    fused_kernel<<<NCTA, NTHREADS, SMEM_BYTES>>>(p, tm_wmod, tm_wq, tm_wo, tm_w1, tm_w2, tm_v, tm_gb);
}
```
